```python
import torch

def _softmax(x, axis=-1):
    return torch.softmax(x, dim=axis)

def _gelu(x):
    return torch.nn.functional.gelu(x, approximate='tanh')

def _silu(x):
    return torch.nn.functional.silu(x)

def _sigmoid(x):
    return torch.sigmoid(x)

def _layernorm(x, axis=-1, eps=1e-05):
    m = x.mean(dim=axis, keepdim=True)
    v = x.var(dim=axis, keepdim=True, unbiased=False)
    return (x - m) / torch.sqrt(v + eps)

def _scatter_add(tgt, idx, src, axis=0):
    return tgt.clone().index_add_(axis, idx, src)

def _segment_sum(src, seg, n):
    out = torch.zeros((n,) + src.shape[1:], dtype=src.dtype)
    return out.index_add_(0, seg, src)

def _pad(x, pw):
    flat = tuple((v for pair in reversed(pw) for v in pair))
    return torch.nn.functional.pad(x, flat)
kernel_name = 'adaLN_cond__spectral_gfnet__glu_gated_geglu__prompt'

def setup_inputs():

    _w = lambda a: (lambda t: t.to(torch.bfloat16) if t.is_floating_point() else t)(torch.as_tensor(a))

    def _A_setup():
        B, S, D = (1, 2048, 640)
        Df = D // 2 + 1
        return {'x': _w((lambda *s: torch.randn(*s, dtype=torch.bfloat16) * 0.05)(B, S, D)), 'w_r': _w((lambda *s: torch.randn(*s, dtype=torch.bfloat16) * 3.2)(S, Df) * 0.02), 'w_i': _w((lambda *s: torch.randn(*s, dtype=torch.bfloat16) * 3.2)(S, Df) * 0.02)}
    _A_in = _A_setup()

    def _B_setup():
        B, S, Dm, Df = (1, 2048, 640, 1536)
        return {'x': _w((lambda *s: torch.randn(*s, dtype=torch.bfloat16) * 0.05)(B, S, Dm)), 'w_gate': _w((lambda *s: torch.randn(*s, dtype=torch.bfloat16) * 0.4)(Dm, Df) * Dm ** (-0.5)), 'w_up': _w((lambda *s: torch.randn(*s, dtype=torch.bfloat16) * 0.4)(Dm, Df) * Dm ** (-0.5)), 'w_down': _w((lambda *s: torch.randn(*s, dtype=torch.bfloat16) * 0.4)(Df, Dm) * Df ** (-0.5))}
    _B_in = _B_setup()
    return {'A_x': _A_in['x'], 'A_w_r': _A_in['w_r'], 'A_w_i': _A_in['w_i'], 'B_x': _B_in['x'], 'B_w_gate': _B_in['w_gate'], 'B_w_up': _B_in['w_up'], 'B_w_down': _B_in['w_down'], 'c': _w((lambda *s: torch.randn(*s, dtype=torch.bfloat16) * 0.1)(1, 640) * 8.0), 'w_mod': _w((lambda *s: torch.randn(*s, dtype=torch.bfloat16) * 0.1)(640, 6 * 640) * 640 ** (-0.5) * 8.0)}

def reference(A_x, A_w_r, A_w_i, B_x, B_w_gate, B_w_up, B_w_down, c, w_mod):

    def _A_ref(x, w_r, w_i):
        B, S, D = x.shape
        X = (lambda x, axes=(-2, -1): torch.fft.rfft2(x.float(), dim=axes))(x, axes=(-2, -1))
        W = w_r + 1j * w_i
        X = X * W
        y = (lambda x, s, axes=(-2, -1): torch.fft.irfft2(x, s=s, dim=axes).to(torch.bfloat16))(X, (S, D), axes=(-2, -1))
        return y

    def _B_ref(x, w_gate, w_up, w_down):
        g = torch.einsum('bsd,df->bsf', x, w_gate)
        u = torch.einsum('bsd,df->bsf', x, w_up)
        h = _gelu(g) * u
        return torch.einsum('bsf,fd->bsd', h, w_down)
    x = A_x
    mod = (_silu(c) @ w_mod).reshape(c.shape[0], 6, 1, -1)
    sa, ca, ga, sb, cb, gb = (mod[:, 0].clone(), mod[:, 1].clone(), mod[:, 2].clone(), mod[:, 3].clone(), mod[:, 4].clone(), mod[:, 5].clone())
    h = _layernorm(x, axis=-1) * (1 + ca) + sa
    x = x + ga * _A_ref(h, A_w_r, A_w_i)
    h = _layernorm(x, axis=-1) * (1 + cb) + sb
    x = x + gb * _B_ref(h, B_w_gate, B_w_up, B_w_down)
    return x
```

```cpp
#include <cuda_runtime.h>
#include <cuda_bf16.h>
#include <cuda.h>
#include <stdint.h>

namespace {

constexpr int NCTA = 128;
constexpr int NTHR = 384;

constexpr int OFF_XS = 0;
constexpr int OFF_TS = 20480;
constexpr int OFF_MODS = 43264;
constexpr int OFF_BUFA = 49664;
constexpr int OFF_BUFB = 70144;
constexpr int OFF_WT = 20480;
constexpr int OFF_P2A = 90624;
constexpr int OFF_WR = 90624;
constexpr int OFF_WI = 104960;
constexpr int OFF_AB = 119296;
constexpr int OFF_SC = 121344;
constexpr int OFF_H2S = 107520;
constexpr int OFF_WDS = 128000;
constexpr int OFF_X1 = 143360;
constexpr int OFF_B = 163840;
constexpr int OFF_COL = OFF_B + 32768;
constexpr int OFF_G2X = OFF_B + 20480;
constexpr int OFF_TC = OFF_B + 20480;
constexpr int OFF_T2 = OFF_B + 25600;
constexpr int OFF_T1 = 128000;
constexpr int OFF_T3 = OFF_B + 32768;
constexpr int OFF_BAR = 229376;
constexpr int OFF_GB = OFF_BAR + 1152;
constexpr int OFF_EP = OFF_BAR + 1472;
constexpr int OFF_RED = 122624;
constexpr int SMEM_BYTES = OFF_BAR + 3072;
__device__ __forceinline__ uint32_t g2_b(int s) { return s < 6 ? s * 28672 : OFF_G2X; }
__device__ __forceinline__ uint32_t g2_a(int s) { return s < 5 ? s * 28672 + 20480 : OFF_G2X + 20480 + (s - 5) * 8192; }
constexpr int TS_P = 712, TS_J = 44;

enum { BAR_BFULL = 0  , BAR_G2FULL = 30  , BAR_X1 = 54, BAR_BEMPTY = 56,
       BAR_G2EMPTY = 60  , BAR_EPI = 86, BAR_H2 = 87, BAR_X1S = 88, BAR_T3B = 89, BAR_H1 = 90,
       BAR_ALAND = 91  , BAR_HLAND = 101  , BAR_WRETRY = 117  ,
       BAR_EARLY = 125,
       BAR_MODA = 125, BAR_RETRY = 126, BAR_IN2 = 127, BAR_IN3 = 128, BAR_AB = 129, BAR_ALD = 130, BAR_T2P = 131, BAR_G2 = 132  ,
       BAR_TB3 = 134, BAR_SENT = 135, BAR_WDL = 136,
       BAR_G1 = 137, BAR_COL = 138, BAR_C = 139, BAR_TB = 140, BAR_W = 141, BAR_G1H = 142, NBAR = 143 };

__device__ __align__(1024) uint32_t g_E[2 * 128 * 5120];
__device__ __align__(1024) uint4 g_H2[16 * 10 * 1024];
__device__ __align__(1024) uint4 g_H[16 * 24 * 1024];
__device__ __align__(1024) uint4 g_WdP[8 * 24 * 640];
__device__ __align__(128) uint32_t g_mod[8 * 3840];
__device__ __align__(128) uint32_t g_cnt[17 * 32];
constexpr int C_T1 = 0, C_T2 = 4, C_WD = 1, C_MOD = 5, C_T3 = 0, C_X1 = 1, C_H0 = 4;

#define STAMP(i) do {} while (0)
#define GSTAMP(i) do {} while (0)

#define X_DELAY 2000
#define PREFETCH_BAR BAR_IN3
#define GEMV2_BAR BAR_IN2
#define GU_BAR BAR_T2P
#define MODB_BAR BAR_T2P
#define WDG_BAR BAR_IN3
#define MOD_LAG 100
#define X1_PACE 0
#define G2_AT 28
#define COL_AT 2600
#define TAB_AT 1500
#define G2_STEP 0
#define GSZ 8
#define X1_AT 21
#define T3_LAG 430
#define W_PROMO CU_TENSOR_MAP_L2_PROMOTION_L2_128B
#define PREP_BAR BAR_SENT
#define GU_D 6
#define H_LAG 600
#define G2_DEEP 1
#define GATE_T 8
#define GATE_LAG 0
#define T1_LAG 450
#define T2_LAG 270
#define X1_SPLIT 7
#define T3_CAP 850
#define T1_CAP 100000
#define T2_CAP 100000
#define MODB_LAG 0
constexpr int SPIN_LIMIT = 2000000;

__device__ __forceinline__ uint32_t pack2(float lo, float hi) {
  uint32_t r; asm("cvt.rn.bf16x2.f32 %0, %1, %2;" : "=r"(r) : "f"(hi), "f"(lo)); return r;
}
__device__ __forceinline__ float bf_lo(uint32_t w) { return __uint_as_float(w << 16); }
__device__ __forceinline__ float bf_hi(uint32_t w) { return __uint_as_float(w & 0xffff0000u); }
__device__ __forceinline__ float bf_round(float x) { return bf_lo(pack2(x, 0.f)); }

__device__ __forceinline__ uint32_t hfma2(uint32_t a, uint32_t b, uint32_t c) {
  uint32_t r; asm("fma.rn.bf16x2 %0, %1, %2, %3;" : "=r"(r) : "r"(a), "r"(b), "r"(c)); return r;
}
__device__ __forceinline__ uint32_t hadd2(uint32_t a, uint32_t b) { uint32_t r; asm("add.rn.bf16x2 %0, %1, %2;" : "=r"(r) : "r"(a), "r"(b)); return r; }
__device__ __forceinline__ uint32_t hmul2(uint32_t a, uint32_t b) { uint32_t r; asm("mul.rn.bf16x2 %0, %1, %2;" : "=r"(r) : "r"(a), "r"(b)); return r; }
__device__ __forceinline__ void mma_acc(float (&c)[4], uint32_t a0, uint32_t a1, uint32_t a2, uint32_t a3, uint32_t b0, uint32_t b1) {
  asm("mma.sync.aligned.m16n8k16.row.col.f32.bf16.bf16.f32 {%0,%1,%2,%3},{%4,%5,%6,%7},{%8,%9},{%0,%1,%2,%3};"
      : "+f"(c[0]), "+f"(c[1]), "+f"(c[2]), "+f"(c[3]) : "r"(a0), "r"(a1), "r"(a2), "r"(a3), "r"(b0), "r"(b1));
}
__device__ __forceinline__ void mma_new(float (&c)[4], uint32_t a0, uint32_t a1, uint32_t a2, uint32_t a3, uint32_t b0, uint32_t b1) {
  asm("mma.sync.aligned.m16n8k16.row.col.f32.bf16.bf16.f32 {%0,%1,%2,%3},{%4,%5,%6,%7},{%8,%9},{%10,%10,%10,%10};"
      : "=f"(c[0]), "=f"(c[1]), "=f"(c[2]), "=f"(c[3]) : "r"(a0), "r"(a1), "r"(a2), "r"(a3), "r"(b0), "r"(b1), "f"(0.f));
}
__device__ __forceinline__ void ldsm4t(uint32_t& r0, uint32_t& r1, uint32_t& r2, uint32_t& r3, uint32_t addr) {
  asm volatile("ldmatrix.sync.aligned.m8n8.x4.trans.shared.b16 {%0,%1,%2,%3}, [%4];"
               : "=r"(r0), "=r"(r1), "=r"(r2), "=r"(r3) : "r"(addr) : "memory");
}
__device__ __forceinline__ void ldsm4(uint32_t& r0, uint32_t& r1, uint32_t& r2, uint32_t& r3, uint32_t addr) {
  asm volatile("ldmatrix.sync.aligned.m8n8.x4.shared.b16 {%0,%1,%2,%3}, [%4];"
               : "=r"(r0), "=r"(r1), "=r"(r2), "=r"(r3) : "r"(addr) : "memory");
}
__device__ __forceinline__ void stsm4(uint32_t addr, uint32_t r0, uint32_t r1, uint32_t r2, uint32_t r3) {
  asm volatile("stmatrix.sync.aligned.m8n8.x4.shared.b16 [%0], {%1,%2,%3,%4};" :: "r"(addr), "r"(r0), "r"(r1), "r"(r2), "r"(r3) : "memory");
}
__device__ __forceinline__ uint32_t lds32(uint32_t a) { uint32_t v; asm volatile("ld.shared.u32 %0, [%1];" : "=r"(v) : "r"(a) : "memory"); return v; }
__device__ __forceinline__ uint32_t lds32v(uint32_t a) { uint32_t v; asm volatile("ld.volatile.shared.u32 %0, [%1];" : "=r"(v) : "r"(a) : "memory"); return v; }
__device__ __forceinline__ uint32_t lds16(uint32_t a) { uint32_t v; asm volatile("ld.shared.u16 %0, [%1];" : "=r"(v) : "r"(a) : "memory"); return v; }
__device__ __forceinline__ void sts32(uint32_t a, uint32_t v) { asm volatile("st.shared.u32 [%0], %1;" :: "r"(a), "r"(v) : "memory"); }
__device__ __forceinline__ uint4 lds128(uint32_t a) { uint4 v; asm volatile("ld.shared.v4.u32 {%0,%1,%2,%3}, [%4];" : "=r"(v.x), "=r"(v.y), "=r"(v.z), "=r"(v.w) : "r"(a) : "memory"); return v; }
__device__ __forceinline__ void sts128(uint32_t a, uint4 v) { asm volatile("st.shared.v4.u32 [%0], {%1,%2,%3,%4};" :: "r"(a), "r"(v.x), "r"(v.y), "r"(v.z), "r"(v.w) : "memory"); }
__device__ __forceinline__ void sts64(uint32_t a, uint32_t v0, uint32_t v1) { asm volatile("st.shared.v2.u32 [%0], {%1,%2};" :: "r"(a), "r"(v0), "r"(v1) : "memory"); }

__device__ __forceinline__ void bar_sync(int id, int n) { asm volatile("bar.sync %0, %1;" :: "r"(id), "r"(n) : "memory"); }
__device__ __forceinline__ void bar_arrive(int id, int n) { asm volatile("bar.arrive %0, %1;" :: "r"(id), "r"(n) : "memory"); }
__device__ __forceinline__ void fence_async_smem() { asm volatile("fence.proxy.async.shared::cta;" ::: "memory"); }

__device__ __forceinline__ void mbar_init(uint32_t b, int c) { asm volatile("mbarrier.init.shared.b64 [%0], %1;" :: "r"(b), "r"(c) : "memory"); }
__device__ __forceinline__ void mbar_expect(uint32_t b, uint32_t bytes) { asm volatile("mbarrier.arrive.expect_tx.shared.b64 _, [%0], %1;" :: "r"(b), "r"(bytes) : "memory"); }
__device__ __forceinline__ void mbar_arrive(uint32_t b) { asm volatile("mbarrier.arrive.shared.b64 _, [%0];" :: "r"(b) : "memory"); }
__device__ __forceinline__ void mbar_wait(uint32_t b, uint32_t ph) {
  uint32_t ok; int it = 0;
  do {
    asm volatile("{\n.reg .pred p;\nmbarrier.try_wait.parity.shared.b64 p, [%1], %2;\nselp.u32 %0, 1, 0, p;\n}" : "=r"(ok) : "r"(b), "r"(ph) : "memory");
  } while (!ok && ++it < SPIN_LIMIT);
}
__device__ __forceinline__ uint32_t mbar_test(uint32_t b, uint32_t ph) {
  uint32_t ok;
  asm volatile("{\n.reg .pred p;\nmbarrier.test_wait.parity.shared.b64 p, [%1], %2;\nselp.u32 %0, 1, 0, p;\n}" : "=r"(ok) : "r"(b), "r"(ph) : "memory");
  return ok;
}
__device__ __forceinline__ void mbar_arrive_if(uint32_t b, bool pred) {
  asm volatile("{\n.reg .pred p;\nsetp.ne.u32 p, %1, 0;\n@p mbarrier.arrive.shared.b64 _, [%0];\n}" :: "r"(b), "r"((uint32_t)pred) : "memory");
}
__device__ __forceinline__ void bulk_g2s(uint32_t dst, const void* src, uint32_t bytes, uint32_t bar) {
  asm volatile("cp.async.bulk.shared::cluster.global.mbarrier::complete_tx::bytes [%0], [%1], %2, [%3];"
               :: "r"(dst), "l"(src), "r"(bytes), "r"(bar) : "memory");
}
__device__ __forceinline__ void bulk_s2g(void* dst, uint32_t src, uint32_t bytes) {
  asm volatile("cp.async.bulk.global.shared::cta.bulk_group [%0], [%1], %2;" :: "l"(dst), "r"(src), "r"(bytes) : "memory");
}
__device__ __forceinline__ void bulk_commit() { asm volatile("cp.async.bulk.commit_group;" ::: "memory"); }
__device__ __forceinline__ void bulk_wait0() { asm volatile("cp.async.bulk.wait_group 0;" ::: "memory"); }
__device__ __forceinline__ void bulk_wait_read0() { asm volatile("cp.async.bulk.wait_group.read 0;" ::: "memory"); }
__device__ __forceinline__ void tma2d(uint32_t dst, const CUtensorMap* tm, int c0, int c1, uint32_t bar) {
  asm volatile("cp.async.bulk.tensor.2d.shared::cluster.global.mbarrier::complete_tx::bytes [%0], [%1, {%3, %4}], [%2];"
               :: "r"(dst), "l"(tm), "r"(bar), "r"(c0), "r"(c1) : "memory");
}
__device__ __forceinline__ void tma3d(uint32_t dst, const CUtensorMap* tm, int c0, int c1, int c2, uint32_t bar) {
  asm volatile("cp.async.bulk.tensor.3d.shared::cluster.global.mbarrier::complete_tx::bytes [%0], [%1, {%3, %4, %5}], [%2];"
               :: "r"(dst), "l"(tm), "r"(bar), "r"(c0), "r"(c1), "r"(c2) : "memory");
}
__device__ __forceinline__ void tma4d(uint32_t dst, const CUtensorMap* tm, int c0, uint32_t bar) {
  asm volatile("cp.async.bulk.tensor.4d.shared::cluster.global.mbarrier::complete_tx::bytes [%0], [%1, {%3, %4, %4, %4}], [%2];"
               :: "r"(dst), "l"(tm), "r"(bar), "r"(c0), "r"(0) : "memory");
}
__device__ __forceinline__ void tma5d(uint32_t dst, const CUtensorMap* tm, int c2, int c4, uint32_t bar) {
  asm volatile("cp.async.bulk.tensor.5d.shared::cluster.global.mbarrier::complete_tx::bytes [%0], [%1, {%5, %5, %3, %5, %4}], [%2];"
               :: "r"(dst), "l"(tm), "r"(bar), "r"(c2), "r"(c4), "r"(0) : "memory");
}
__device__ __forceinline__ void tma2d_store(const CUtensorMap* tm, int c0, int c1, uint32_t src) {
  asm volatile("cp.async.bulk.tensor.2d.global.shared::cta.bulk_group [%0, {%2, %3}], [%1];"
               :: "l"(tm), "r"(src), "r"(c0), "r"(c1) : "memory");
}
__device__ __forceinline__ void tma3d_prefetch(const CUtensorMap* tm, int c0, int c1) {
  asm volatile("cp.async.bulk.prefetch.tensor.3d.L2.global [%0, {%1, %2, %3}];" :: "l"(tm), "r"(c0), "r"(c1), "r"(0) : "memory");
}
__device__ __forceinline__ void l2_prefetch(const void* p, uint32_t bytes) {
  asm volatile("cp.async.bulk.prefetch.L2.global [%0], %1;" :: "l"(p), "r"(bytes) : "memory");
}
__device__ __forceinline__ uint32_t ld_relaxed(const uint32_t* p) {
  uint32_t v; asm volatile("ld.relaxed.gpu.global.u32 %0, [%1];" : "=r"(v) : "l"(p) : "memory"); return v;
}
__device__ __forceinline__ uint4 ld_relaxed4(const uint32_t* p) {
  uint4 v; asm volatile("ld.relaxed.gpu.global.v4.u32 {%0,%1,%2,%3}, [%4];" : "=r"(v.x), "=r"(v.y), "=r"(v.z), "=r"(v.w) : "l"(p) : "memory"); return v;
}
__device__ __forceinline__ void st_relaxed(uint32_t* p, uint32_t v) { asm volatile("st.relaxed.gpu.global.u32 [%0], %1;" :: "l"(p), "r"(v) : "memory"); }
__device__ __forceinline__ void red_relaxed(uint32_t* p) { asm volatile("red.relaxed.gpu.global.add.u32 [%0], 1;" :: "l"(p) : "memory"); }
__device__ __forceinline__ void red_release(uint32_t* p) { asm volatile("red.release.gpu.global.add.u32 [%0], 1;" :: "l"(p) : "memory"); }
__device__ __forceinline__ uint64_t gtime() { uint64_t t; asm volatile("mov.u64 %0, %%globaltimer;" : "=l"(t)); return t; }
__device__ __forceinline__ void hint(uint32_t* p, uint32_t own) {
  const uint64_t now = gtime();
  asm volatile("red.relaxed.gpu.global.max.u64 [%0], %1;" :: "l"(p + 2), "l"(now) : "memory");
  red_relaxed(p);
  sts32(own, (uint32_t)now);
}
__device__ __forceinline__ uint32_t poll_hint(const uint32_t* p, uint32_t target) {
  int it = 0;
  uint4 v;
  do { v = ld_relaxed4(p); } while ((int)(v.x - target) < 0 && ++it < SPIN_LIMIT);
  return v.z;
}
__device__ __forceinline__ void poll_cnt(const uint32_t* p, uint32_t target) {
  int it = 0;
  while ((int)(ld_relaxed(p) - target) < 0 && ++it < SPIN_LIMIT) {}
}
__device__ __forceinline__ uint32_t clock32() { uint32_t c; asm volatile("mov.u32 %0, %%clock;" : "=r"(c)); return c; }
__device__ __forceinline__ void spin_until(uint32_t t) { while ((int)(clock32() - t) < 0) __nanosleep(20); }
__device__ __forceinline__ bool elect() {
  uint32_t p; asm volatile("{\n.reg .pred p;\nelect.sync _|p, 0xffffffff;\nselp.u32 %0, 1, 0, p;\n}" : "=r"(p)); return p != 0;
}
__device__ __forceinline__ uint64_t mkdesc(uint32_t addr, uint32_t lbo, uint32_t sbo, uint32_t sw) {
  return (uint64_t)((addr & 0x3FFFF) >> 4) | ((uint64_t)(lbo >> 4) << 16) | ((uint64_t)(sbo >> 4) << 32) | ((uint64_t)sw << 62);
}
__device__ __forceinline__ void wg_fence() { asm volatile("wgmma.fence.sync.aligned;" ::: "memory"); }
__device__ __forceinline__ void wg_commit() { asm volatile("wgmma.commit_group.sync.aligned;" ::: "memory"); }
template <int N> __device__ __forceinline__ void wg_wait() { asm volatile("wgmma.wait_group.sync.aligned %0;" :: "n"(N) : "memory"); }
template <int N> __device__ __forceinline__ void reg_fence(float (&d)[N]) {
#pragma unroll
  for (int i = 0; i < N; i++) asm volatile("" : "+f"(d[i]) :: "memory");
}

constexpr int TAB_T1 = 10, TAB_T3 = 58, TAB_T2 = 98;
__device__ __align__(128) const uint32_t g_tab[35072] = {
0x3f803f80,0xbf803f80,0x3f803f80,0xbf803f80,0x3f803f80,0xbf803f80,0x3f803f80,0xbf803f80,0x3f803f80,0xbf803f80,0x3f803f80,0xbf803f80,0x3f803f80,0xbf803f80,0x3f803f80,0xbf803f80,
0x3f6d3f80,0xbec40000,0xbf6dbf80,0x3ec40000,0x3ec43f35,0xbf6dbf35,0xbec4bf35,0x3f6d3f35,0xbec40000,0xbf6dbf80,0x3ec40000,0x3f6d3f80,0xbf6dbf35,0xbec4bf35,0x3f6d3f35,0x3ec43f35,
0x3f353f80,0xbf350000,0x3f353f80,0xbf350000,0xbf350000,0xbf35bf80,0xbf350000,0xbf35bf80,0xbf35bf80,0x3f350000,0xbf35bf80,0x3f350000,0x3f350000,0x3f353f80,0x3f350000,0x3f353f80,
0x3ec43f80,0xbf6d0000,0xbec4bf80,0x3f6d0000,0xbf6dbf35,0x3ec4bf35,0x3f6d3f35,0xbec43f35,0x3f6d0000,0x3ec43f80,0xbf6d0000,0xbec4bf80,0xbec43f35,0xbf6dbf35,0x3ec4bf35,0x3f6d3f35,
0x3f80,0xbf800000,0x3f80,0xbf800000,0xbf80,0x3f800000,0xbf80,0x3f800000,0x3f80,0xbf800000,0x3f80,0xbf800000,0xbf80,0x3f800000,0xbf80,0x3f800000,
0xbec43f80,0xbf6d0000,0x3ec4bf80,0x3f6d0000,0x3f6dbf35,0x3ec43f35,0xbf6d3f35,0xbec4bf35,0xbf6d0000,0x3ec4bf80,0x3f6d0000,0xbec43f80,0x3ec43f35,0xbf6d3f35,0xbec4bf35,0x3f6dbf35,
0xbf353f80,0xbf350000,0xbf353f80,0xbf350000,0x3f350000,0xbf353f80,0x3f350000,0xbf353f80,0x3f35bf80,0x3f350000,0x3f35bf80,0x3f350000,0xbf350000,0x3f35bf80,0xbf350000,0x3f35bf80,
0xbf6d3f80,0xbec40000,0x3f6dbf80,0x3ec40000,0xbec43f35,0xbf6d3f35,0x3ec4bf35,0x3f6dbf35,0x3ec40000,0xbf6d3f80,0xbec40000,0x3f6dbf80,0x3f6dbf35,0xbec43f35,0xbf6d3f35,0x3ec4bf35,
0x3f803f80,0x3f803f80,0xbf803f80,0xbf803f80,0x3f803f80,0x3f803f80,0xbf803f80,0xbf803f80,0x3f803f80,0x3f803f80,0xbf803f80,0xbf803f80,0x3f803f80,0x3f803f80,0xbf803f80,0xbf803f80,
0x3f80,0x3f80,0x3f80,0x3f80,0xbf80,0xbf80,0xbf80,0xbf80,0x3f80,0x3f80,0x3f80,0x3f80,0xbf80,0xbf80,0xbf80,0xbf80,
0x3f6d3f80,0xbf6dbf80,0xbf6d3f80,0x3f6dbf80,0x3ec43f35,0xbec4bf35,0xbec43f35,0x3ec4bf35,0xbec40000,0x3ec40000,0x3ec40000,0xbec40000,0xbf6dbf35,0x3f6d3f35,0x3f6dbf35,0xbf6d3f35,
0xbec43f80,0x3ec4bf80,0x3ec43f80,0xbec4bf80,0x3f6dbf35,0xbf6d3f35,0xbf6dbf35,0x3f6d3f35,0xbf6d0000,0x3f6d0000,0x3f6d0000,0xbf6d0000,0x3ec43f35,0xbec4bf35,0xbec43f35,0x3ec4bf35,
0x3f353f80,0x3f353f80,0xbf353f80,0xbf353f80,0xbf350000,0xbf350000,0x3f350000,0x3f350000,0xbf35bf80,0xbf35bf80,0x3f35bf80,0x3f35bf80,0x3f350000,0x3f350000,0xbf350000,0xbf350000,
0xbf353f80,0xbf353f80,0x3f353f80,0x3f353f80,0x3f350000,0x3f350000,0xbf350000,0xbf350000,0x3f35bf80,0x3f35bf80,0xbf35bf80,0xbf35bf80,0xbf350000,0xbf350000,0x3f350000,0x3f350000,
0x3ec43f80,0xbec4bf80,0xbec43f80,0x3ec4bf80,0xbf6dbf35,0x3f6d3f35,0x3f6dbf35,0xbf6d3f35,0x3f6d0000,0xbf6d0000,0xbf6d0000,0x3f6d0000,0xbec43f35,0x3ec4bf35,0x3ec43f35,0xbec4bf35,
0xbf6d3f80,0x3f6dbf80,0x3f6d3f80,0xbf6dbf80,0xbec43f35,0x3ec4bf35,0x3ec43f35,0xbec4bf35,0x3ec40000,0xbec40000,0xbec40000,0x3ec40000,0x3f6dbf35,0xbf6d3f35,0xbf6dbf35,0x3f6d3f35,
0,0,0,0,0,0,0,0,0,0,0,0,0,0,0,0,
0x3f800000,0x3f800000,0xbf800000,0xbf800000,0xbf800000,0xbf800000,0x3f800000,0x3f800000,0x3f800000,0x3f800000,0xbf800000,0xbf800000,0xbf800000,0xbf800000,0x3f800000,0x3f800000,
0x3ec40000,0xbec40000,0xbec40000,0x3ec40000,0x3f6d3f35,0xbf6dbf35,0xbf6d3f35,0x3f6dbf35,0x3f6d3f80,0xbf6dbf80,0xbf6d3f80,0x3f6dbf80,0x3ec43f35,0xbec4bf35,0xbec43f35,0x3ec4bf35,
0x3f6d0000,0xbf6d0000,0xbf6d0000,0x3f6d0000,0xbec4bf35,0x3ec43f35,0x3ec4bf35,0xbec43f35,0xbec43f80,0x3ec4bf80,0x3ec43f80,0xbec4bf80,0x3f6dbf35,0xbf6d3f35,0xbf6dbf35,0x3f6d3f35,
0x3f350000,0x3f350000,0xbf350000,0xbf350000,0x3f353f80,0x3f353f80,0xbf353f80,0xbf353f80,0xbf350000,0xbf350000,0x3f350000,0x3f350000,0xbf35bf80,0xbf35bf80,0x3f35bf80,0x3f35bf80,
0x3f350000,0x3f350000,0xbf350000,0xbf350000,0x3f35bf80,0x3f35bf80,0xbf35bf80,0xbf35bf80,0xbf350000,0xbf350000,0x3f350000,0x3f350000,0xbf353f80,0xbf353f80,0x3f353f80,0x3f353f80,
0x3f6d0000,0xbf6d0000,0xbf6d0000,0x3f6d0000,0xbec43f35,0x3ec4bf35,0x3ec43f35,0xbec4bf35,0xbec4bf80,0x3ec43f80,0x3ec4bf80,0xbec43f80,0x3f6d3f35,0xbf6dbf35,0xbf6d3f35,0x3f6dbf35,
0x3ec40000,0xbec40000,0xbec40000,0x3ec40000,0x3f6dbf35,0xbf6d3f35,0xbf6dbf35,0x3f6d3f35,0x3f6dbf80,0xbf6d3f80,0xbf6dbf80,0x3f6d3f80,0x3ec4bf35,0xbec43f35,0xbec4bf35,0x3ec43f35,
0x3f803f80,0,0,0x3f803f80,0x3f803f80,0,0,0x3f803f80,0x3f803f80,0,0,0x3f803f80,0x3f803f80,0,0,0x3f803f80,
0x3f353f80,0x3f350000,0xbf350000,0x3f353f80,0xbf350000,0x3f353f80,0xbf35bf80,0xbf350000,0xbf35bf80,0xbf350000,0x3f350000,0xbf35bf80,0x3f350000,0xbf35bf80,0x3f353f80,0x3f350000,
0x3f80,0x3f800000,0xbf800000,0x3f80,0xbf80,0xbf800000,0x3f800000,0xbf80,0x3f80,0x3f800000,0xbf800000,0x3f80,0xbf80,0xbf800000,0x3f800000,0xbf80,
0xbf353f80,0x3f350000,0xbf350000,0xbf353f80,0x3f350000,0x3f35bf80,0xbf353f80,0x3f350000,0x3f35bf80,0xbf350000,0x3f350000,0x3f35bf80,0xbf350000,0xbf353f80,0x3f35bf80,0xbf350000,
0xbf803f80,0,0,0xbf803f80,0xbf803f80,0,0,0xbf803f80,0xbf803f80,0,0,0xbf803f80,0xbf803f80,0,0,0xbf803f80,
0xbf353f80,0xbf350000,0x3f350000,0xbf353f80,0x3f350000,0xbf353f80,0x3f35bf80,0x3f350000,0x3f35bf80,0x3f350000,0xbf350000,0x3f35bf80,0xbf350000,0x3f35bf80,0xbf353f80,0xbf350000,
0x3f80,0xbf800000,0x3f800000,0x3f80,0xbf80,0x3f800000,0xbf800000,0xbf80,0x3f80,0xbf800000,0x3f800000,0x3f80,0xbf80,0x3f800000,0xbf800000,0xbf80,
0x3f353f80,0xbf350000,0x3f350000,0x3f353f80,0xbf350000,0xbf35bf80,0x3f353f80,0xbf350000,0xbf35bf80,0x3f350000,0xbf350000,0xbf35bf80,0x3f350000,0x3f353f80,0xbf35bf80,0x3f350000,
0x3f803f80,0,0,0x3f803f80,0x3f803f80,0,0,0x3f803f80,0x3f803f80,0,0,0x3f803f80,0x3f803f80,0,0,0x3f803f80,
0xbf803f80,0,0,0xbf803f80,0xbf803f80,0,0,0xbf803f80,0xbf803f80,0,0,0xbf803f80,0xbf803f80,0,0,0xbf803f80,
0x3f353f80,0x3f350000,0xbf350000,0x3f353f80,0xbf350000,0x3f353f80,0xbf35bf80,0xbf350000,0xbf35bf80,0xbf350000,0x3f350000,0xbf35bf80,0x3f350000,0xbf35bf80,0x3f353f80,0x3f350000,
0xbf353f80,0xbf350000,0x3f350000,0xbf353f80,0x3f350000,0xbf353f80,0x3f35bf80,0x3f350000,0x3f35bf80,0x3f350000,0xbf350000,0x3f35bf80,0xbf350000,0x3f35bf80,0xbf353f80,0xbf350000,
0x3f80,0x3f800000,0xbf800000,0x3f80,0xbf80,0xbf800000,0x3f800000,0xbf80,0x3f80,0x3f800000,0xbf800000,0x3f80,0xbf80,0xbf800000,0x3f800000,0xbf80,
0x3f80,0xbf800000,0x3f800000,0x3f80,0xbf80,0x3f800000,0xbf800000,0xbf80,0x3f80,0xbf800000,0x3f800000,0x3f80,0xbf80,0x3f800000,0xbf800000,0xbf80,
0xbf353f80,0x3f350000,0xbf350000,0xbf353f80,0x3f350000,0x3f35bf80,0xbf353f80,0x3f350000,0x3f35bf80,0xbf350000,0x3f350000,0x3f35bf80,0xbf350000,0xbf353f80,0x3f35bf80,0xbf350000,
0x3f353f80,0xbf350000,0x3f350000,0x3f353f80,0xbf350000,0xbf35bf80,0x3f353f80,0xbf350000,0xbf35bf80,0x3f350000,0xbf350000,0xbf35bf80,0x3f350000,0x3f353f80,0xbf35bf80,0x3f350000,
0x3f80,0x3f80,0x3f80,0x3f80,0x3f80,0xbf80,0x3f80,0xbf80,0x3f80,0x3f80,0x3f80,0x3f80,0x3f80,0xbf80,0x3f80,0xbf80,
0x3f80,0x3f80,0xbf800000,0xbf800000,0xbec43f6d,0x3ec4bf6d,0xbf6dbec4,0x3f6d3ec4,0xbf353f35,0xbf353f35,0xbf35bf35,0xbf35bf35,0xbf6d3ec4,0x3f6dbec4,0xbec4bf6d,0x3ec43f6d,
0x3f80,0x3f80,0xbf80,0xbf80,0xbf353f35,0x3f35bf35,0x3f35bf35,0xbf353f35,0xbf800000,0xbf800000,0x3f800000,0x3f800000,0xbf35bf35,0x3f353f35,0x3f353f35,0xbf35bf35,
0x3f80,0x3f80,0x3f800000,0x3f800000,0xbf6d3ec4,0x3f6dbec4,0x3ec43f6d,0xbec4bf6d,0xbf35bf35,0xbf35bf35,0xbf353f35,0xbf353f35,0x3ec4bf6d,0xbec43f6d,0xbf6dbec4,0x3f6d3ec4,
0x3f80,0x3f80,0x3f80,0x3f80,0xbf800000,0x3f800000,0xbf800000,0x3f800000,0xbf80,0xbf80,0xbf80,0xbf80,0x3f800000,0xbf800000,0x3f800000,0xbf800000,
0x3f80,0x3f80,0xbf800000,0xbf800000,0xbf6dbec4,0x3f6d3ec4,0x3ec4bf6d,0xbec43f6d,0x3f35bf35,0x3f35bf35,0x3f353f35,0x3f353f35,0x3ec43f6d,0xbec4bf6d,0xbf6d3ec4,0x3f6dbec4,
0x3f80,0x3f80,0xbf80,0xbf80,0xbf35bf35,0x3f353f35,0x3f353f35,0xbf35bf35,0x3f800000,0x3f800000,0xbf800000,0xbf800000,0xbf353f35,0x3f35bf35,0x3f35bf35,0xbf353f35,
0x3f80,0x3f80,0x3f800000,0x3f800000,0xbec4bf6d,0x3ec43f6d,0xbf6d3ec4,0x3f6dbec4,0x3f353f35,0x3f353f35,0x3f35bf35,0x3f35bf35,0xbf6dbec4,0x3f6d3ec4,0xbec43f6d,0x3ec4bf6d,
0x3f80,0x3f80,0x3f80,0x3f80,0x3f80,0xbf80,0x3f80,0xbf80,0x3f80,0x3f80,0x3f80,0x3f80,0x3f80,0xbf80,0x3f80,0xbf80,
0xbf80,0xbf80,0x3f800000,0x3f800000,0x3ec4bf6d,0xbec43f6d,0x3f6d3ec4,0xbf6dbec4,0x3f35bf35,0x3f35bf35,0x3f353f35,0x3f353f35,0x3f6dbec4,0xbf6d3ec4,0x3ec43f6d,0xbec4bf6d,
0x3f80,0x3f80,0xbf80,0xbf80,0xbf353f35,0x3f35bf35,0x3f35bf35,0xbf353f35,0xbf800000,0xbf800000,0x3f800000,0x3f800000,0xbf35bf35,0x3f353f35,0x3f353f35,0xbf35bf35,
0xbf80,0xbf80,0xbf800000,0xbf800000,0x3f6dbec4,0xbf6d3ec4,0xbec4bf6d,0x3ec43f6d,0x3f353f35,0x3f353f35,0x3f35bf35,0x3f35bf35,0xbec43f6d,0x3ec4bf6d,0x3f6d3ec4,0xbf6dbec4,
0x3f80,0x3f80,0x3f80,0x3f80,0xbf800000,0x3f800000,0xbf800000,0x3f800000,0xbf80,0xbf80,0xbf80,0xbf80,0x3f800000,0xbf800000,0x3f800000,0xbf800000,
0xbf80,0xbf80,0x3f800000,0x3f800000,0x3f6d3ec4,0xbf6dbec4,0xbec43f6d,0x3ec4bf6d,0xbf353f35,0xbf353f35,0xbf35bf35,0xbf35bf35,0xbec4bf6d,0x3ec43f6d,0x3f6dbec4,0xbf6d3ec4,
0x3f80,0x3f80,0xbf80,0xbf80,0xbf35bf35,0x3f353f35,0x3f353f35,0xbf35bf35,0x3f800000,0x3f800000,0xbf800000,0xbf800000,0xbf353f35,0x3f35bf35,0x3f35bf35,0xbf353f35,
0xbf80,0xbf80,0xbf800000,0xbf800000,0x3ec43f6d,0xbec4bf6d,0x3f6dbec4,0xbf6d3ec4,0xbf35bf35,0xbf35bf35,0xbf353f35,0xbf353f35,0x3f6d3ec4,0xbf6dbec4,0x3ec4bf6d,0xbec43f6d,
0x3f800000,0x3f800000,0x3f800000,0x3f800000,0x3f800000,0xbf800000,0x3f800000,0xbf800000,0x3f800000,0x3f800000,0x3f800000,0x3f800000,0x3f800000,0xbf800000,0x3f800000,0xbf800000,
0x3f800000,0x3f800000,0x3f80,0x3f80,0x3f6d3ec4,0xbf6dbec4,0xbec43f6d,0x3ec4bf6d,0x3f353f35,0x3f353f35,0xbf353f35,0xbf353f35,0x3ec43f6d,0xbec4bf6d,0xbf6d3ec4,0x3f6dbec4,
0x3f800000,0x3f800000,0xbf800000,0xbf800000,0x3f353f35,0xbf35bf35,0xbf35bf35,0x3f353f35,0x3f80,0x3f80,0xbf80,0xbf80,0xbf353f35,0x3f35bf35,0x3f35bf35,0xbf353f35,
0x3f800000,0x3f800000,0xbf80,0xbf80,0x3ec43f6d,0xbec4bf6d,0x3f6dbec4,0xbf6d3ec4,0xbf353f35,0xbf353f35,0x3f353f35,0x3f353f35,0xbf6dbec4,0x3f6d3ec4,0xbec43f6d,0x3ec4bf6d,
0x3f800000,0x3f800000,0x3f800000,0x3f800000,0x3f80,0xbf80,0x3f80,0xbf80,0xbf800000,0xbf800000,0xbf800000,0xbf800000,0xbf80,0x3f80,0xbf80,0x3f80,
0x3f800000,0x3f800000,0x3f80,0x3f80,0xbec43f6d,0x3ec4bf6d,0xbf6dbec4,0x3f6d3ec4,0xbf35bf35,0xbf35bf35,0x3f35bf35,0x3f35bf35,0x3f6dbec4,0xbf6d3ec4,0x3ec43f6d,0xbec4bf6d,
0x3f800000,0x3f800000,0xbf800000,0xbf800000,0xbf353f35,0x3f35bf35,0x3f35bf35,0xbf353f35,0xbf80,0xbf80,0x3f80,0x3f80,0x3f353f35,0xbf35bf35,0xbf35bf35,0x3f353f35,
0x3f800000,0x3f800000,0xbf80,0xbf80,0xbf6d3ec4,0x3f6dbec4,0x3ec43f6d,0xbec4bf6d,0x3f35bf35,0x3f35bf35,0xbf35bf35,0xbf35bf35,0xbec43f6d,0x3ec4bf6d,0x3f6d3ec4,0xbf6dbec4,
0x3f800000,0x3f800000,0x3f800000,0x3f800000,0x3f800000,0xbf800000,0x3f800000,0xbf800000,0x3f800000,0x3f800000,0x3f800000,0x3f800000,0x3f800000,0xbf800000,0x3f800000,0xbf800000,
0xbf800000,0xbf800000,0xbf80,0xbf80,0xbf6dbec4,0x3f6d3ec4,0x3ec4bf6d,0xbec43f6d,0xbf35bf35,0xbf35bf35,0x3f35bf35,0x3f35bf35,0xbec4bf6d,0x3ec43f6d,0x3f6dbec4,0xbf6d3ec4,
0x3f800000,0x3f800000,0xbf800000,0xbf800000,0x3f353f35,0xbf35bf35,0xbf35bf35,0x3f353f35,0x3f80,0x3f80,0xbf80,0xbf80,0xbf353f35,0x3f35bf35,0x3f35bf35,0xbf353f35,
0xbf800000,0xbf800000,0x3f80,0x3f80,0xbec4bf6d,0x3ec43f6d,0xbf6d3ec4,0x3f6dbec4,0x3f35bf35,0x3f35bf35,0xbf35bf35,0xbf35bf35,0x3f6d3ec4,0xbf6dbec4,0x3ec4bf6d,0xbec43f6d,
0x3f800000,0x3f800000,0x3f800000,0x3f800000,0x3f80,0xbf80,0x3f80,0xbf80,0xbf800000,0xbf800000,0xbf800000,0xbf800000,0xbf80,0x3f80,0xbf80,0x3f80,
0xbf800000,0xbf800000,0xbf80,0xbf80,0x3ec4bf6d,0xbec43f6d,0x3f6d3ec4,0xbf6dbec4,0x3f353f35,0x3f353f35,0xbf353f35,0xbf353f35,0xbf6d3ec4,0x3f6dbec4,0xbec4bf6d,0x3ec43f6d,
0x3f800000,0x3f800000,0xbf800000,0xbf800000,0xbf353f35,0x3f35bf35,0x3f35bf35,0xbf353f35,0xbf80,0xbf80,0x3f80,0x3f80,0x3f353f35,0xbf35bf35,0xbf35bf35,0x3f353f35,
0xbf800000,0xbf800000,0x3f80,0x3f80,0x3f6dbec4,0xbf6d3ec4,0xbec4bf6d,0x3ec43f6d,0xbf353f35,0xbf353f35,0x3f353f35,0x3f353f35,0x3ec4bf6d,0xbec43f6d,0xbf6dbec4,0x3f6d3ec4,
0x3f803f80,0x3f803f80,0x4000,0x4000,0x4000,0xc000,0x4000,0xc000,0x4000,0x4000,0x4000,0x4000,0x4000,0xc000,0x4000,0xc000,
0xbf803f80,0xbf803f80,0xc0000000,0xc0000000,0xbf443fed,0x3f44bfed,0xbfedbf44,0x3fed3f44,0xbfb53fb5,0xbfb53fb5,0xbfb5bfb5,0xbfb5bfb5,0xbfed3f44,0x3fedbf44,0xbf44bfed,0x3f443fed,
0x3f803f80,0x3f803f80,0xc000,0xc000,0xbfb53fb5,0x3fb5bfb5,0x3fb5bfb5,0xbfb53fb5,0xc0000000,0xc0000000,0x40000000,0x40000000,0xbfb5bfb5,0x3fb53fb5,0x3fb53fb5,0xbfb5bfb5,
0xbf803f80,0xbf803f80,0x40000000,0x40000000,0xbfed3f44,0x3fedbf44,0x3f443fed,0xbf44bfed,0xbfb5bfb5,0xbfb5bfb5,0xbfb53fb5,0xbfb53fb5,0x3f44bfed,0xbf443fed,0xbfedbf44,0x3fed3f44,
0x3f803f80,0x3f803f80,0x4000,0x4000,0xc0000000,0x40000000,0xc0000000,0x40000000,0xc000,0xc000,0xc000,0xc000,0x40000000,0xc0000000,0x40000000,0xc0000000,
0xbf803f80,0xbf803f80,0xc0000000,0xc0000000,0xbfedbf44,0x3fed3f44,0x3f44bfed,0xbf443fed,0x3fb5bfb5,0x3fb5bfb5,0x3fb53fb5,0x3fb53fb5,0x3f443fed,0xbf44bfed,0xbfed3f44,0x3fedbf44,
0x3f803f80,0x3f803f80,0xc000,0xc000,0xbfb5bfb5,0x3fb53fb5,0x3fb53fb5,0xbfb5bfb5,0x40000000,0x40000000,0xc0000000,0xc0000000,0xbfb53fb5,0x3fb5bfb5,0x3fb5bfb5,0xbfb53fb5,
0xbf803f80,0xbf803f80,0x40000000,0x40000000,0xbf44bfed,0x3f443fed,0xbfed3f44,0x3fedbf44,0x3fb53fb5,0x3fb53fb5,0x3fb5bfb5,0x3fb5bfb5,0xbfedbf44,0x3fed3f44,0xbf443fed,0x3f44bfed,
0x3f80,0x3f80,0x3f80,0x3f80,0x3f80,0xbf80,0x3f80,0xbf80,0x3f80,0x3f80,0x3f80,0x3f80,0x3f80,0xbf80,0x3f80,0xbf80,
0x3f80,0,0xbf80,0,0x3f35,0xbf35,0xbf35,0x3f35,0,0xbf80,0,0x3f80,0xbf35,0xbf35,0x3f35,0x3f35,
0x3f80,0,0x3f80,0,0,0xbf80,0,0xbf80,0xbf80,0,0xbf80,0,0,0x3f80,0,0x3f80,
0x3f80,0,0xbf80,0,0xbf35,0xbf35,0x3f35,0x3f35,0,0x3f80,0,0xbf80,0x3f35,0xbf35,0xbf35,0x3f35,
0x3f800000,0,0,0xbf800000,0x3f6d0000,0xbec40000,0xbec40000,0xbf6d0000,0x3f350000,0xbf350000,0xbf350000,0xbf350000,0x3ec40000,0xbf6d0000,0xbf6d0000,0xbec40000,
0x3f800000,0,0,0x3f800000,0x3ec40000,0xbf6d0000,0x3f6d0000,0x3ec40000,0xbf350000,0xbf350000,0x3f350000,0xbf350000,0xbf6d0000,0x3ec40000,0xbec40000,0xbf6d0000,
0x3f800000,0,0,0xbf800000,0xbec40000,0xbf6d0000,0xbf6d0000,0x3ec40000,0xbf350000,0x3f350000,0x3f350000,0x3f350000,0x3f6d0000,0x3ec40000,0x3ec40000,0xbf6d0000,
0x3f800000,0,0,0x3f800000,0xbf6d0000,0xbec40000,0x3ec40000,0xbf6d0000,0x3f350000,0x3f350000,0xbf350000,0x3f350000,0xbec40000,0xbf6d0000,0x3f6d0000,0xbec40000,
0x3f80,0xbf80,0x3f80,0xbf80,0x3f80,0x3f80,0x3f80,0x3f80,0x3f80,0xbf80,0x3f80,0xbf80,0x3f80,0x3f80,0x3f80,0x3f80,
0x3f7d,0xbe20,0xbf7d,0x3e20,0x3f16,0xbf4f,0xbf16,0x3f4f,0xbe20,0xbf7d,0x3e20,0x3f7d,0xbf4f,0xbf16,0x3f4f,0x3f16,
0x3f73,0xbe9e,0x3f73,0xbe9e,0xbe9e,0xbf73,0xbe9e,0xbf73,0xbf73,0x3e9e,0xbf73,0x3e9e,0x3e9e,0x3f73,0x3e9e,0x3f73,
0x3f64,0xbee8,0xbf64,0x3ee8,0xbf73,0xbe9e,0x3f73,0x3e9e,0x3ee8,0x3f64,0xbee8,0xbf64,0x3e9e,0xbf73,0xbe9e,0x3f73,
0x3f7f0000,0xbda10000,0xbda10000,0xbf7f0000,0x3f640000,0xbee80000,0xbee80000,0xbf640000,0x3f260000,0xbf430000,0xbf430000,0xbf260000,0x3e9e0000,0xbf730000,0xbf730000,0xbe9e0000,
0x3f790000,0xbe6f0000,0x3e6f0000,0x3f790000,0x3e200000,0xbf7d0000,0x3f7d0000,0x3e200000,0xbf5a0000,0xbf060000,0x3f060000,0xbf5a0000,0xbf4f0000,0x3f160000,0xbf160000,0xbf4f0000,
0x3f6d0000,0xbec40000,0xbec40000,0xbf6d0000,0xbf350000,0xbf350000,0xbf350000,0x3f350000,0xbec40000,0x3f6d0000,0x3f6d0000,0x3ec40000,0x3f800000,0,0,0xbf800000,
0x3f5a0000,0xbf060000,0x3f060000,0x3f5a0000,0xbf7d0000,0x3e200000,0xbe200000,0xbf7d0000,0x3f790000,0x3e6f0000,0xbe6f0000,0x3f790000,0xbf4f0000,0xbf160000,0x3f160000,0xbf4f0000,
0x3f80,0x3f80,0x3f80,0x3f80,0x3f80,0xbf80,0x3f80,0xbf80,0x3f80,0x3f80,0x3f80,0x3f80,0x3f80,0xbf80,0x3f80,0xbf80,
0x3f73,0xbe9e,0xbf73,0x3e9e,0x3ee8,0xbf64,0xbee8,0x3f64,0xbe9e,0xbf73,0x3e9e,0x3f73,0xbf64,0xbee8,0x3f64,0x3ee8,
0x3f4f,0xbf16,0x3f4f,0xbf16,0xbf16,0xbf4f,0xbf16,0xbf4f,0xbf4f,0x3f16,0xbf4f,0x3f16,0x3f16,0x3f4f,0x3f16,0x3f4f,
0x3f16,0xbf4f,0xbf16,0x3f4f,0xbf7d,0x3e20,0x3f7d,0xbe20,0x3f4f,0x3f16,0xbf4f,0xbf16,0xbe20,0xbf7d,0x3e20,0x3f7d,
0x3f7d0000,0xbe200000,0xbe200000,0xbf7d0000,0x3f5a0000,0xbf060000,0xbf060000,0xbf5a0000,0x3f160000,0xbf4f0000,0xbf4f0000,0xbf160000,0x3e6f0000,0xbf790000,0xbf790000,0xbe6f0000,
0x3f640000,0xbee80000,0x3ee80000,0x3f640000,0xbda10000,0xbf7f0000,0x3f7f0000,0xbda10000,0xbf730000,0xbe9e0000,0x3e9e0000,0xbf730000,0xbf260000,0x3f430000,0xbf430000,0xbf260000,
0x3f350000,0xbf350000,0xbf350000,0xbf350000,0xbf6d0000,0xbec40000,0xbec40000,0x3f6d0000,0,0x3f800000,0x3f800000,0,0x3f6d0000,0xbec40000,0xbec40000,0xbf6d0000,
0x3ee80000,0xbf640000,0x3f640000,0x3ee80000,0xbf430000,0x3f260000,0xbf260000,0xbf430000,0x3f730000,0xbe9e0000,0x3e9e0000,0x3f730000,0xbf7f0000,0xbda10000,0x3da10000,0xbf7f0000,
0x3f80,0xbf80,0x3f80,0xbf80,0x3f80,0x3f80,0x3f80,0x3f80,0x3f80,0xbf80,0x3f80,0xbf80,0x3f80,0x3f80,0x3f80,0x3f80,
0x3f64,0xbee8,0xbf64,0x3ee8,0x3e9e,0xbf73,0xbe9e,0x3f73,0xbee8,0xbf64,0x3ee8,0x3f64,0xbf73,0xbe9e,0x3f73,0x3e9e,
0x3f16,0xbf4f,0x3f16,0xbf4f,0xbf4f,0xbf16,0xbf4f,0xbf16,0xbf16,0x3f4f,0xbf16,0x3f4f,0x3f4f,0x3f16,0x3f4f,0x3f16,
0x3e20,0xbf7d,0xbe20,0x3f7d,0xbf4f,0x3f16,0x3f4f,0xbf16,0x3f7d,0x3e20,0xbf7d,0xbe20,0xbf16,0xbf4f,0x3f16,0x3f4f,
0x3f790000,0xbe6f0000,0xbe6f0000,0xbf790000,0x3f4f0000,0xbf160000,0xbf160000,0xbf4f0000,0x3f060000,0xbf5a0000,0xbf5a0000,0xbf060000,0x3e200000,0xbf7d0000,0xbf7d0000,0xbe200000,
0x3f430000,0xbf260000,0x3f260000,0x3f430000,0xbe9e0000,0xbf730000,0x3f730000,0xbe9e0000,0xbf7f0000,0xbda10000,0x3da10000,0xbf7f0000,0xbee80000,0x3f640000,0xbf640000,0xbee80000,
0x3ec40000,0xbf6d0000,0xbf6d0000,0xbec40000,0xbf800000,0,0,0x3f800000,0x3ec40000,0x3f6d0000,0x3f6d0000,0xbec40000,0x3f350000,0xbf350000,0xbf350000,0xbf350000,
0xbda10000,0xbf7f0000,0x3f7f0000,0xbda10000,0xbe9e0000,0x3f730000,0xbf730000,0xbe9e0000,0x3f260000,0xbf430000,0x3f430000,0x3f260000,0xbf640000,0x3ee80000,0xbee80000,0xbf640000,
0x3f80,0x3f80,0x3f80,0x3f80,0x3f80,0xbf80,0x3f80,0xbf80,0x3f80,0x3f80,0x3f80,0x3f80,0x3f80,0xbf80,0x3f80,0xbf80,
0x3f4f,0xbf16,0xbf4f,0x3f16,0x3e20,0xbf7d,0xbe20,0x3f7d,0xbf16,0xbf4f,0x3f16,0x3f4f,0xbf7d,0xbe20,0x3f7d,0x3e20,
0x3e9e,0xbf73,0x3e9e,0xbf73,0xbf73,0xbe9e,0xbf73,0xbe9e,0xbe9e,0x3f73,0xbe9e,0x3f73,0x3f73,0x3e9e,0x3f73,0x3e9e,
0xbe9e,0xbf73,0x3e9e,0x3f73,0xbee8,0x3f64,0x3ee8,0xbf64,0x3f73,0xbe9e,0xbf73,0x3e9e,0xbf64,0xbee8,0x3f64,0x3ee8,
0x3f730000,0xbe9e0000,0xbe9e0000,0xbf730000,0x3f430000,0xbf260000,0xbf260000,0xbf430000,0x3ee80000,0xbf640000,0xbf640000,0xbee80000,0x3da10000,0xbf7f0000,0xbf7f0000,0xbda10000,
0x3f160000,0xbf4f0000,0x3f4f0000,0x3f160000,0xbf060000,0xbf5a0000,0x3f5a0000,0xbf060000,0xbf7d0000,0x3e200000,0xbe200000,0xbf7d0000,0xbe6f0000,0x3f790000,0xbf790000,0xbe6f0000,
0,0xbf800000,0xbf800000,0,0xbf6d0000,0x3ec40000,0x3ec40000,0x3f6d0000,0x3f350000,0x3f350000,0x3f350000,0xbf350000,0x3ec40000,0xbf6d0000,0xbf6d0000,0xbec40000,
0xbf160000,0xbf4f0000,0x3f4f0000,0xbf160000,0x3e6f0000,0x3f790000,0xbf790000,0x3e6f0000,0x3e200000,0xbf7d0000,0x3f7d0000,0x3e200000,0xbf060000,0x3f5a0000,0xbf5a0000,0xbf060000,
0,0x1e20,0x3c40,0x28900a70,0xa0,0x1ec0,0x3ce0,0x29300b10,0x140,0x1f60,0x3d80,0x29d00bb0,0x1e0,0x2000,0x3e20,0x2a700c50,
0x44,0x1e64,0x3c84,0x149c3c1c,0xe4,0x1f04,0x3d24,0x153c3cbc,0x184,0x1fa4,0x3dc4,0x15dc3d5c,0x224,0x2044,0x3e64,0x167c3dfc,
0x88,0x2808,0x4628,0x14583278,0x128,0x28a8,0x46c8,0x14f83318,0x1c8,0x2948,0x4768,0x159833b8,0x268,0x29e8,0x4808,0x16383458,
0xa2c,0x284c,0x466c,0x14143234,0xacc,0x28ec,0x470c,0x14b432d4,0xb6c,0x298c,0x47ac,0x15543374,0xc0c,0x2a2c,0x484c,0x15f43414,
0x20,0x1e40,0x3c60,0x1e1c3c3c,0xc0,0x1ee0,0x3d00,0x1ebc3cdc,0x160,0x1f80,0x3da0,0x1f5c3d7c,0x200,0x2020,0x3e40,0x1ffc3e1c,
0x64,0x1e84,0x4604,0x14783298,0x104,0x1f24,0x46a4,0x15183338,0x1a4,0x1fc4,0x4744,0x15b833d8,0x244,0x2064,0x47e4,0x16583478,
0xa08,0x2828,0x4648,0x14343254,0xaa8,0x28c8,0x46e8,0x14d432f4,0xb48,0x2968,0x4788,0x15743394,0xbe8,0x2a08,0x4828,0x16143434,
0xa4c,0x286c,0x468c,0xa903210,0xaec,0x290c,0x472c,0xb3032b0,0xb8c,0x29ac,0x47cc,0xbd03350,0xc2c,0x2a4c,0x486c,0xc7033f0,
0x3f80,0x3f800000,0x3e483f7b,0x3f7bbe48,0x3d493f80,0x3f80bd49,0x3e793f78,0x3f78be79,0x3dc93f7f,0x3f7fbdc9,0x3e953f75,0x3f75be95,0x3e163f7d,0x3f7dbe16,0x3eac3f71,0x3f71beac,
0x3f80,0x3f800000,0xbe48bf7b,0xbf7b3e48,0x3f3e3f2c,0x3f2cbf3e,0xbf5cbf04,0xbf043f5c,0x3f7fbdc9,0xbdc9bf7f,0xbf753e95,0x3e953f75,0x3f18bf4e,0xbf4ebf18,0xbedb3f67,0x3f673edb,
0x3f80,0x3f800000,0x3e483f7b,0x3f7bbe48,0x3f80bd49,0xbd49bf80,0x3f78be79,0xbe79bf78,0xbdc9bf7f,0xbf7f3dc9,0xbe95bf75,0xbf753e95,0xbf7d3e16,0x3e163f7d,0xbf713eac,0x3eac3f71,
0x3f80,0x3f800000,0xbe48bf7b,0xbf7b3e48,0x3f2cbf3e,0xbf3ebf2c,0xbf043f5c,0x3f5c3f04,0xbf7f3dc9,0x3dc93f7f,0x3f75be95,0xbe95bf75,0x3f4e3f18,0x3f18bf4e,0xbf67bedb,0xbedb3f67,
0x3f80,0x3f800000,0x3e483f7b,0x3f7bbe48,0xbd49bf80,0xbf803d49,0xbe79bf78,0xbf783e79,0x3dc93f7f,0x3f7fbdc9,0x3e953f75,0x3f75be95,0xbe16bf7d,0xbf7d3e16,0xbeacbf71,0xbf713eac,
0x3f80,0x3f800000,0xbe48bf7b,0xbf7b3e48,0xbf3ebf2c,0xbf2c3f3e,0x3f5c3f04,0x3f04bf5c,0x3f7fbdc9,0xbdc9bf7f,0xbf753e95,0x3e953f75,0xbf183f4e,0x3f4e3f18,0x3edbbf67,0xbf67bedb,
0x3f80,0x3f800000,0x3e483f7b,0x3f7bbe48,0xbf803d49,0x3d493f80,0xbf783e79,0x3e793f78,0xbdc9bf7f,0xbf7f3dc9,0xbe95bf75,0xbf753e95,0x3f7dbe16,0xbe16bf7d,0x3f71beac,0xbeacbf71,
0x3f80,0x3f800000,0xbe48bf7b,0xbf7b3e48,0xbf2c3f3e,0x3f3e3f2c,0x3f04bf5c,0xbf5cbf04,0xbf7f3dc9,0x3dc93f7f,0x3f75be95,0xbe95bf75,0xbf4ebf18,0xbf183f4e,0x3f673edb,0x3edbbf67,
0x3c213f80,0x3f80bc21,0x3e523f7b,0x3f7bbe52,0x3d713f80,0x3f80bd71,0x3e813f78,0x3f78be81,0x3ddd3f7f,0x3f7fbddd,0x3e993f74,0x3f74be99,0x3e203f7d,0x3f7dbe20,0x3eb13f70,0x3f70beb1,
0x3e2a3f7c,0x3f7cbe2a,0xbeb6bf6f,0xbf6f3eb6,0x3f583f0a,0x3f0abf58,0xbf6ebebb,0xbebb3f6e,0x3f77be86,0xbe86bf77,0xbf653ee4,0x3ee43f65,0x3ee8bf64,0xbf64bee8,0xbe8b3f76,0x3f763e8b,
0x3ea33f73,0x3f73bea3,0x3eff3f5e,0x3f5ebeff,0x3f6ebebb,0xbebbbf6e,0x3f58bf0a,0xbf0abf58,0xbed2bf6a,0xbf6a3ed2,0xbf14bf51,0xbf513f14,0xbf643ee8,0x3ee83f64,0xbf493f1e,0x3f1e3f49,
0x3eed3f63,0x3f63beed,0xbf20bf47,0xbf473f20,0x3e81bf78,0xbf78be81,0xbd713f80,0x3f803d71,0xbf563f0c,0x3f0c3f56,0x3f37bf33,0xbf33bf37,0x3f7d3e20,0x3e20bf7d,0xbf803d21,0x3d213f80,
0x3f183f4e,0x3f4ebf18,0x3f3e3f2c,0x3f2cbf3e,0xbf22bf46,0xbf463f22,0xbf46bf22,0xbf223f46,0x3f2c3f3e,0x3f3ebf2c,0x3f4e3f18,0x3f18bf4e,0xbf35bf35,0xbf353f35,0xbf55bf0e,0xbf0e3f55,
0x3f373f33,0x3f33bf37,0xbf56bf0c,0xbf0c3f56,0xbf803d71,0x3d713f80,0x3f78be81,0xbe81bf78,0x3f20bf47,0xbf47bf20,0xbeed3f63,0x3f633eed,0x3e203f7d,0x3f7dbe20,0xbeb1bf70,0xbf703eb1,
0x3f513f14,0x3f14bf51,0x3f6a3ed2,0x3ed2bf6a,0xbf0a3f58,0x3f583f0a,0xbebb3f6e,0x3f6e3ebb,0xbf5ebeff,0xbeff3f5e,0xbf73bea3,0xbea33f73,0x3ee8bf64,0xbf64bee8,0x3e8bbf76,0xbf76be8b,
0x3f653ee4,0x3ee4bf65,0xbf77be86,0xbe863f77,0x3ebb3f6e,0x3f6ebebb,0xbf0abf58,0xbf583f0a,0xbeb63f6f,0x3f6f3eb6,0x3e2abf7c,0xbf7cbe2a,0xbf643ee8,0x3ee83f64,0x3f49bf1e,0xbf1ebf49,
0x3ca13f80,0x3f80bca1,0x3e5b3f7a,0x3f7abe5b,0x3d8d3f7f,0x3f7fbd8d,0x3e863f77,0x3f77be86,0x3df13f7e,0x3f7ebdf1,0x3e9e3f73,0x3f73be9e,0x3e2a3f7c,0x3f7cbe2a,0x3eb63f6f,0x3f6fbeb6,
0x3ea83f72,0x3f72bea8,0xbf01bf5d,0xbf5d3f01,0x3f6c3ec9,0x3ec9bf6c,0xbf7bbe52,0xbe523f7b,0x3f68bed6,0xbed6bf68,0xbf4f3f16,0x3f163f4f,0x3e99bf74,0xbf74be99,0xbddd3f7f,0x3f7f3ddd,
0x3f1b3f4c,0x3f4cbf1b,0x3f3f3f2a,0x3f2abf3f,0x3f44bf24,0xbf24bf44,0x3f20bf47,0xbf47bf20,0xbf2ebf3c,0xbf3c3f2e,0xbf4fbf16,0xbf163f4f,0xbf333f37,0x3f373f33,0xbf0c3f56,0x3f563f0c,
0x3f523f12,0x3f12bf52,0xbf6bbecd,0xbecd3f6b,0xbe65bf7a,0xbf7a3e65,0x3ed23f6a,0x3f6abed2,0xbefa3f5f,0x3f5f3efa,0x3e9ebf73,0xbf73be9e,0x3f73bea3,0xbea3bf73,0xbf5e3eff,0x3eff3f5e,
0x3f753e95,0x3e95bf75,0x3f7f3dc9,0x3dc9bf7f,0xbf78be79,0xbe793f78,0xbf80bd49,0xbd493f80,0x3f7b3e48,0x3e48bf7b,0x3f800000,0xbf80,0xbf7dbe16,0xbe163f7d,0xbf803d49,0x3d493f80,
0x3f80bca1,0xbca1bf80,0xbf7a3e5b,0x3e5b3f7a,0xbf283f41,0x3f413f28,0x3effbf5e,0xbf5ebeff,0xbdf1bf7e,0xbf7e3df1,0x3e9e3f73,0x3f73be9e,0x3f513f14,0x3f14bf51,0xbf6abed2,0xbed23f6a,
0x3f72bea8,0xbea8bf72,0x3f5dbf01,0xbf01bf5d,0x3ebf3f6d,0x3f6dbebf,0x3f0c3f56,0x3f56bf0c,0xbf683ed6,0x3ed63f68,0xbf4f3f16,0x3f163f4f,0xbeedbf63,0xbf633eed,0xbf20bf47,0xbf473f20,
0x3f4cbf1b,0xbf1bbf4c,0xbf2a3f3f,0x3f3f3f2a,0x3f7f3db5,0x3db5bf7f,0xbf7f3ddd,0x3ddd3f7f,0x3f2e3f3c,0x3f3cbf2e,0xbf4fbf16,0xbf163f4f,0x3c213f80,0x3f80bc21,0xbe52bf7b,0xbf7b3e52,
0x3cf13f80,0x3f80bcf1,0x3e653f7a,0x3f7abe65,0x3da13f7f,0x3f7fbda1,0x3e8b3f76,0x3f76be8b,0x3e023f7e,0x3f7ebe02,0x3ea33f73,0x3f73bea3,0x3e343f7c,0x3f7cbe34,0x3ebb3f6e,0x3f6ebebb,
0x3ef63f61,0x3f61bef6,0xbf24bf44,0xbf443f24,0x3f793e6f,0x3e6fbf79,0xbf80bd21,0xbd213f80,0x3f53bf10,0xbf10bf53,0xbf333f37,0x3f373f33,0x3e0cbf7e,0xbf7ebe0c,0x3d713f80,0x3f80bd71,
0x3f533f10,0x3f10bf53,0x3f6c3ec9,0x3ec9bf6c,0x3f06bf5a,0xbf5abf06,0x3eb1bf70,0xbf70beb1,0xbf61bef6,0xbef63f61,0xbf74be99,0xbe993f74,0xbedf3f66,0x3f663edf,0xbe813f78,0x3f783e81,
0x3f7e3e02,0x3e02bf7e,0xbf7f3d8d,0x3d8d3f7f,0xbf26bf43,0xbf433f26,0x3f493f1e,0x3f1ebf49,0xbcf13f80,0x3f803cf1,0xbe2abf7c,0xbf7c3e2a,0x3f31bf39,0xbf39bf31,0xbf0a3f58,0x3f583f0a,
0x3f71beac,0xbeacbf71,0x3f5cbf04,0xbf04bf5c,0xbf6d3ec4,0x3ec43f6d,0xbf553f0e,0x3f0e3f55,0x3f67bedb,0xbedbbf67,0x3f4ebf18,0xbf18bf4e,0xbf623ef1,0x3ef13f62,0xbf463f22,0x3f223f46,
0x3f30bf3a,0xbf3abf30,0xbf083f59,0x3f593f08,0x3da13f7f,0x3f7fbda1,0xbe8bbf76,0xbf763e8b,0xbf4bbf1d,0xbf1d3f4b,0x3f653ee4,0x3ee4bf65,0x3f7cbe34,0xbe34bf7c,0xbf6e3ebb,0x3ebb3f6e,
0x3e90bf76,0xbf76be90,0x3db5bf7f,0xbf7fbdb5,0x3f793e6f,0x3e6fbf79,0x3f803d21,0x3d21bf80,0xbe3e3f7c,0x3f7c3e3e,0x3c213f80,0x3f80bc21,0xbf7ebe0c,0xbe0c3f7e,0xbf803d71,0x3d713f80,
0xbe3ebf7c,0xbf7c3e3e,0x3ebf3f6d,0x3f6dbebf,0x3f06bf5a,0xbf5abf06,0xbeb13f70,0x3f703eb1,0x3f76be90,0xbe90bf76,0xbf633eed,0x3eed3f63,0x3f663edf,0x3edfbf66,0xbf78be81,0xbe813f78,
0x3d213f80,0x3f80bd21,0x3e6f3f79,0x3f79be6f,0x3db53f7f,0x3f7fbdb5,0x3e903f76,0x3f76be90,0x3e0c3f7e,0x3f7ebe0c,0x3ea83f72,0x3f72bea8,0x3e3e3f7c,0x3f7cbe3e,0x3ebf3f6d,0x3f6dbebf,
0x3f1e3f49,0x3f49bf1e,0xbf43bf26,0xbf263f43,0x3f7f3d8d,0x3d8dbf7f,0xbf7e3e02,0x3e023f7e,0x3f39bf31,0xbf31bf39,0xbf123f52,0x3f523f12,0xbcf1bf80,0xbf803cf1,0x3e653f7a,0x3f7abe65,
0x3f763e8b,0x3e8bbf76,0x3f7f3da1,0x3da1bf7f,0x3e65bf7a,0xbf7abe65,0x3cf1bf80,0xbf80bcf1,0xbf7cbe34,0xbe343f7c,0xbf803ca1,0x3ca13f80,0xbe023f7e,0x3f7e3e02,0x3d8d3f7f,0x3f7fbd8d,
0x3f70beb1,0xbeb1bf70,0xbf5a3f06,0x3f063f5a,0xbf6dbebf,0xbebf3f6d,0x3f7c3e3e,0x3e3ebf7c,0x3edf3f66,0x3f66bedf,0xbf1bbf4c,0xbf4c3f1b,0x3e90bf76,0xbf76be90,0xbdb53f7f,0x3f7f3db5,
0x3f0ebf55,0xbf55bf0e,0x3ec4bf6d,0xbf6dbec4,0xbf043f5c,0x3f5c3f04,0xbeac3f71,0x3f713eac,0x3ef1bf62,0xbf62bef1,0x3e95bf75,0xbf75be95,0xbedb3f67,0x3f673edb,0xbe793f78,0x3f783e79,
0xbd21bf80,0xbf803d21,0x3e6f3f79,0x3f79be6f,0x3f443f24,0x3f24bf44,0xbf61bef6,0xbef63f61,0xbf7e3e0c,0x3e0c3f7e,0x3f72bea8,0xbea8bf72,0x3f10bf53,0xbf53bf10,0xbec93f6c,0x3f6c3ec9,
0xbf1ebf49,0xbf493f1e,0xbf43bf26,0xbf263f43,0x3f41bf28,0xbf28bf41,0x3f1dbf4b,0xbf4bbf1d,0x3f313f39,0x3f39bf31,0x3f523f12,0x3f12bf52,0xbf303f3a,0x3f3a3f30,0xbf083f59,0x3f593f08,
0xbf76be8b,0xbe8b3f76,0x3f7f3da1,0x3da1bf7f,0xbf08bf59,0xbf593f08,0x3f303f3a,0x3f3abf30,0x3e34bf7c,0xbf7cbe34,0x3ca13f80,0x3f80bca1,0x3f4bbf1d,0xbf1dbf4b,0xbf283f41,0x3f413f28,
0x4,0x1e24,0x3c44,0x1e003c20,0xa4,0x1ec4,0x3ce4,0x1ea03cc0,0x144,0x1f64,0x3d84,0x1f403d60,0x1e4,0x2004,0x3e24,0x1fe03e00,
0x40,0x1e60,0x3c80,0x14643284,0xe0,0x1f00,0x3d20,0x15043324,0x180,0x1fa0,0x3dc0,0x15a433c4,0x220,0x2040,0x3e60,0x16443464,
0x8c,0x280c,0x462c,0x14283248,0x12c,0x28ac,0x46cc,0x14c832e8,0x1cc,0x294c,0x476c,0x15683388,0x26c,0x29ec,0x480c,0x16083428,
0xa28,0x2848,0x4668,0xa8c320c,0xac8,0x28e8,0x4708,0xb2c32ac,0xb68,0x2988,0x47a8,0xbcc334c,0xc08,0x2a28,0x4848,0xc6c33ec,
0xa74,0x2894,0x4690,0xa502870,0xb14,0x2934,0x4730,0xaf02910,0xbb4,0x29d4,0x47d0,0xb9029b0,0xc54,0x2a74,0x4870,0xc302a50,
0x1410,0x3230,0x4654,0xa142834,0x14b0,0x32d0,0x46f4,0xab428d4,0x1550,0x3370,0x4794,0xb542974,0x15f0,0x3410,0x4834,0xbf42a14,
0x145c,0x327c,0x4618,0x781e98,0x14fc,0x331c,0x46b8,0x1181f38,0x159c,0x33bc,0x4758,0x1b81fd8,0x163c,0x345c,0x47f8,0x2582078,
0x1498,0x3c18,0x3c7c,0x3c1e5c,0x1538,0x3cb8,0x3d1c,0xdc1efc,0x15d8,0x3d58,0x3dbc,0x17c1f9c,0x1678,0x3df8,0x3e5c,0x21c203c,
0x3f80,0x3f800000,0x3ec43f6d,0x3f6dbec4,0x3dc93f7f,0x3f7fbdc9,0x3ef13f62,0x3f62bef1,0x3e483f7b,0x3f7bbe48,0x3f0e3f55,0x3f55bf0e,0x3e953f75,0x3f75be95,0x3f223f46,0x3f46bf22,
0x3f80,0x3f800000,0xbec4bf6d,0xbf6d3ec4,0x3f463f22,0x3f22bf46,0xbf75be95,0xbe953f75,0x3f7bbe48,0xbe48bf7b,0xbf553f0e,0x3f0e3f55,0x3ef1bf62,0xbf62bef1,0xbdc93f7f,0x3f7f3dc9,
0x3f80,0x3f800000,0x3ec43f6d,0x3f6dbec4,0x3f7fbdc9,0xbdc9bf7f,0x3f62bef1,0xbef1bf62,0xbe48bf7b,0xbf7b3e48,0xbf0ebf55,0xbf553f0e,0xbf753e95,0x3e953f75,0xbf463f22,0x3f223f46,
0x3f80,0x3f800000,0xbec4bf6d,0xbf6d3ec4,0x3f22bf46,0xbf46bf22,0xbe953f75,0x3f753e95,0xbf7b3e48,0x3e483f7b,0x3f55bf0e,0xbf0ebf55,0x3f623ef1,0x3ef1bf62,0xbf7fbdc9,0xbdc93f7f,
0x3f80,0x3f800000,0x3ec43f6d,0x3f6dbec4,0xbdc9bf7f,0xbf7f3dc9,0xbef1bf62,0xbf623ef1,0x3e483f7b,0x3f7bbe48,0x3f0e3f55,0x3f55bf0e,0xbe95bf75,0xbf753e95,0xbf22bf46,0xbf463f22,
0x3f80,0x3f800000,0xbec4bf6d,0xbf6d3ec4,0xbf46bf22,0xbf223f46,0x3f753e95,0x3e95bf75,0x3f7bbe48,0xbe48bf7b,0xbf553f0e,0x3f0e3f55,0xbef13f62,0x3f623ef1,0x3dc9bf7f,0xbf7fbdc9,
0x3f80,0x3f800000,0x3ec43f6d,0x3f6dbec4,0xbf7f3dc9,0x3dc93f7f,0xbf623ef1,0x3ef13f62,0xbe48bf7b,0xbf7b3e48,0xbf0ebf55,0xbf553f0e,0x3f75be95,0xbe95bf75,0x3f46bf22,0xbf22bf46,
0x3f80,0x3f800000,0xbec4bf6d,0xbf6d3ec4,0xbf223f46,0x3f463f22,0x3e95bf75,0xbf75be95,0xbf7b3e48,0x3e483f7b,0x3f55bf0e,0xbf0ebf55,0xbf62bef1,0xbef13f62,0x3f7f3dc9,0x3dc9bf7f,
0x3ca13f80,0x3f80bca1,0x3ecd3f6b,0x3f6bbecd,0x3df13f7e,0x3f7ebdf1,0x3efa3f5f,0x3f5fbefa,0x3e5b3f7a,0x3f7abe5b,0x3f123f52,0x3f52bf12,0x3e9e3f73,0x3f73be9e,0x3f263f43,0x3f43bf26,
0x3e343f7c,0x3f7cbe34,0xbf0abf58,0xbf583f0a,0x3f5f3efa,0x3efabf5f,0xbf7ebdf1,0xbdf13f7e,0x3f6ebebb,0xbebbbf6e,0xbf393f31,0x3f313f39,0x3e9ebf73,0xbf73be9e,0x3da13f7f,0x3f7fbda1,
0x3ea83f72,0x3f72bea8,0x3f2a3f3f,0x3f3fbf2a,0x3f68bed6,0xbed6bf68,0x3f2ebf3c,0xbf3cbf2e,0xbf01bf5d,0xbf5d3f01,0xbf4cbf1b,0xbf1b3f4c,0xbf4f3f16,0x3f163f4f,0xbf063f5a,0x3f5a3f06,
0x3ef13f62,0x3f62bef1,0xbf46bf22,0xbf223f46,0x3e48bf7b,0xbf7bbe48,0x3e483f7b,0x3f7bbe48,0xbf463f22,0x3f223f46,0x3ef1bf62,0xbf62bef1,0x3f800000,0xbf80,0xbf6d3ec4,0x3ec43f6d,
0x3f1b3f4c,0x3f4cbf1b,0x3f5d3f01,0x3f01bf5d,0xbf2ebf3c,0xbf3c3f2e,0xbf68bed6,0xbed63f68,0x3f3f3f2a,0x3f2abf3f,0x3f723ea8,0x3ea8bf72,0xbf4fbf16,0xbf163f4f,0xbf79be6f,0xbe6f3f79,
0x3f393f31,0x3f31bf39,0xbf6ebebb,0xbebb3f6e,0xbf7e3df1,0x3df13f7e,0x3f5fbefa,0xbefabf5f,0x3f0abf58,0xbf58bf0a,0xbe343f7c,0x3f7c3e34,0x3e9e3f73,0x3f73be9e,0xbf26bf43,0xbf433f26,
0x3f523f12,0x3f12bf52,0x3f7a3e5b,0x3e5bbf7a,0xbefa3f5f,0x3f5f3efa,0xbdf13f7e,0x3f7e3df1,0xbf6bbecd,0xbecd3f6b,0xbf80bca1,0xbca13f80,0x3e9ebf73,0xbf73be9e,0xbda1bf7f,0xbf7f3da1,
0x3f663edf,0x3edfbf66,0xbf80bd71,0xbd713f80,0x3ed63f68,0x3f68bed6,0xbf3cbf2e,0xbf2e3f3c,0xbe813f78,0x3f783e81,0xbe0cbf7e,0xbf7e3e0c,0xbf4f3f16,0x3f163f4f,0x3f06bf5a,0xbf5abf06,
0x3d213f80,0x3f80bd21,0x3ed63f68,0x3f68bed6,0x3e0c3f7e,0x3f7ebe0c,0x3f013f5d,0x3f5dbf01,0x3e6f3f79,0x3f79be6f,0x3f163f4f,0x3f4fbf16,0x3ea83f72,0x3f72bea8,0x3f2a3f3f,0x3f3fbf2a,
0x3eb13f70,0x3f70beb1,0xbf2ebf3c,0xbf3c3f2e,0x3f723ea8,0x3ea8bf72,0xbf803d71,0x3d713f80,0x3f5abf06,0xbf06bf5a,0xbf163f4f,0x3f4f3f16,0x3e0cbf7e,0xbf7ebe0c,0x3e813f78,0x3f78be81,
0x3f1e3f49,0x3f49bf1e,0x3f5f3efa,0x3efabf5f,0x3f39bf31,0xbf31bf39,0x3ecdbf6b,0xbf6bbecd,0xbf43bf26,0xbf263f43,0xbf73be9e,0xbe9e3f73,0xbf123f52,0x3f523f12,0xbe5b3f7a,0x3f7a3e5b,
0x3f553f0e,0x3f0ebf55,0xbf7bbe48,0xbe483f7b,0xbe95bf75,0xbf753e95,0x3f223f46,0x3f46bf22,0xbec43f6d,0x3f6d3ec4,0xbf80,0xbf800000,0x3f62bef1,0xbef1bf62,0xbf223f46,0x3f463f22,
0x3f763e8b,0x3e8bbf76,0x3f7ebdf1,0xbdf1bf7e,0xbf7cbe34,0xbe343f7c,0xbf7a3e5b,0x3e5b3f7a,0x3f7f3da1,0x3da1bf7f,0x3f73be9e,0xbe9ebf73,0xbf803ca1,0x3ca13f80,0xbf6b3ecd,0x3ecd3f6b,
0x3f80bd21,0xbd21bf80,0xbf683ed6,0x3ed63f68,0xbf1b3f4c,0x3f4c3f1b,0x3e81bf78,0xbf78be81,0xbe6fbf79,0xbf793e6f,0x3f163f4f,0x3f4fbf16,0x3f663edf,0x3edfbf66,0xbf80bd71,0xbd713f80,
0x3f70beb1,0xbeb1bf70,0x3f3cbf2e,0xbf2ebf3c,0x3edf3f66,0x3f66bedf,0x3f3f3f2a,0x3f2abf3f,0xbf5a3f06,0x3f063f5a,0xbf163f4f,0x3f4f3f16,0xbf1bbf4c,0xbf4c3f1b,0xbf5dbf01,0xbf013f5d,
0x3f49bf1e,0xbf1ebf49,0xbefa3f5f,0x3f5f3efa,0x3f803ca1,0x3ca1bf80,0xbf6e3ebb,0x3ebb3f6e,0x3f433f26,0x3f26bf43,0xbf73be9e,0xbe9e3f73,0x3e343f7c,0x3f7cbe34,0xbf0abf58,0xbf583f0a,
0x3d713f80,0x3f80bd71,0x3edf3f66,0x3f66bedf,0x3e203f7d,0x3f7dbe20,0x3f063f5a,0x3f5abf06,0x3e813f78,0x3f78be81,0x3f1b3f4c,0x3f4cbf1b,0x3eb13f70,0x3f70beb1,0x3f2e3f3c,0x3f3cbf2e,
0x3f013f5d,0x3f5dbf01,0xbf4cbf1b,0xbf1b3f4c,0x3f7d3e20,0x3e20bf7d,0xbf793e6f,0x3e6f3f79,0x3f3fbf2a,0xbf2abf3f,0xbedf3f66,0x3f663edf,0xbd21bf80,0xbf803d21,0x3ed63f68,0x3f68bed6,
0x3f583f0a,0x3f0abf58,0x3f7c3e34,0x3e34bf7c,0x3ee8bf64,0xbf64bee8,0x3da1bf7f,0xbf7fbda1,0xbf6ebebb,0xbebb3f6e,0xbf803ca1,0x3ca13f80,0xbe8b3f76,0x3f763e8b,0x3df13f7e,0x3f7ebdf1,
0x3f7f3dc9,0x3dc9bf7f,0xbf753e95,0x3e953f75,0xbf35bf35,0xbf353f35,0x3f6d3ec4,0x3ec4bf6d,0x3dc93f7f,0x3f7fbdc9,0xbef1bf62,0xbf623ef1,0x3f0ebf55,0xbf55bf0e,0xbe483f7b,0x3f7b3e48,
0x3f6ebebb,0xbebbbf6e,0x3f39bf31,0xbf31bf39,0xbf643ee8,0x3ee83f64,0xbf263f43,0x3f433f26,0x3f58bf0a,0xbf0abf58,0x3f12bf52,0xbf52bf12,0xbf493f1e,0x3f1e3f49,0xbefa3f5f,0x3f5f3efa,
0x3f2abf3f,0xbf3fbf2a,0xbea83f72,0x3f723ea8,0x3e203f7d,0x3f7dbe20,0xbf06bf5a,0xbf5a3f06,0xbf5dbf01,0xbf013f5d,0x3f7e3e0c,0x3e0cbf7e,0x3f70beb1,0xbeb1bf70,0xbf3c3f2e,0x3f2e3f3c,
0x3e81bf78,0xbf78be81,0xbe0cbf7e,0xbf7e3e0c,0x3f7d3e20,0x3e20bf7d,0x3f79be6f,0xbe6fbf79,0xbd713f80,0x3f803d71,0x3ea83f72,0x3f72bea8,0xbf803d21,0x3d213f80,0xbf683ed6,0x3ed63f68,
0xbe5bbf7a,0xbf7a3e5b,0x3f123f52,0x3f52bf12,0x3ee8bf64,0xbf64bee8,0xbda13f7f,0x3f7f3da1,0x3f6bbecd,0xbecdbf6b,0xbf313f39,0x3f393f31,0x3f763e8b,0x3e8bbf76,0xbf7e3df1,0x3df13f7e,
0x3da13f7f,0x3f7fbda1,0x3ee83f64,0x3f64bee8,0x3e343f7c,0x3f7cbe34,0x3f0a3f58,0x3f58bf0a,0x3e8b3f76,0x3f76be8b,0x3f1e3f49,0x3f49bf1e,0x3ebb3f6e,0x3f6ebebb,0x3f313f39,0x3f39bf31,
0x3f263f43,0x3f43bf26,0xbf64bee8,0xbee83f64,0x3f80bca1,0xbca1bf80,0xbf6b3ecd,0x3ecd3f6b,0x3f1ebf49,0xbf49bf1e,0xbe8b3f76,0x3f763e8b,0xbe5bbf7a,0xbf7a3e5b,0x3f123f52,0x3f52bf12,
0x3f793e6f,0x3e6fbf79,0x3f7dbe20,0xbe20bf7d,0x3e0cbf7e,0xbf7ebe0c,0xbe81bf78,0xbf783e81,0xbf80bd21,0xbd213f80,0xbf703eb1,0x3eb13f70,0x3d713f80,0x3f80bd71,0x3edf3f66,0x3f66bedf,
0x3f6dbec4,0xbec4bf6d,0xbf353f35,0x3f353f35,0xbf75be95,0xbe953f75,0x3f7fbdc9,0xbdc9bf7f,0x3f0e3f55,0x3f55bf0e,0xbf55bf0e,0xbf0e3f55,0x3dc9bf7f,0xbf7fbdc9,0x3e953f75,0x3f75be95,
0x3f06bf5a,0xbf5abf06,0x3e20bf7d,0xbf7dbe20,0xbedf3f66,0x3f663edf,0xbd713f80,0x3f803d71,0x3eb1bf70,0xbf70beb1,0xbd21bf80,0xbf803d21,0xbe813f78,0x3f783e81,0x3e0c3f7e,0x3f7ebe0c,
0xbda1bf7f,0xbf7f3da1,0x3ee83f64,0x3f64bee8,0x3f523f12,0x3f12bf52,0xbf7abe5b,0xbe5b3f7a,0xbf763e8b,0x3e8b3f76,0x3f49bf1e,0xbf1ebf49,0x3ecdbf6b,0xbf6bbecd,0xbca13f80,0x3f803ca1,
0xbf26bf43,0xbf433f26,0xbf64bee8,0xbee83f64,0x3f31bf39,0xbf39bf31,0x3ebbbf6e,0xbf6ebebb,0x3f493f1e,0x3f1ebf49,0x3f763e8b,0x3e8bbf76,0xbf0a3f58,0x3f583f0a,0xbe343f7c,0x3f7c3e34,
0xbf79be6f,0xbe6f3f79,0x3f7dbe20,0xbe20bf7d,0xbf1bbf4c,0xbf4c3f1b,0x3f5d3f01,0x3f01bf5d,0x3d21bf80,0xbf80bd21,0x3eb13f70,0x3f70beb1,0x3f2abf3f,0xbf3fbf2a,0xbea83f72,0x3f723ea8,
0x8,0x1e28,0x3c48,0x1e043c24,0xa8,0x1ec8,0x3ce8,0x1ea43cc4,0x148,0x1f68,0x3d88,0x1f443d64,0x1e8,0x2008,0x3e28,0x1fe43e04,
0x4c,0x1e6c,0x3c8c,0x14603280,0xec,0x1f0c,0x3d2c,0x15003320,0x18c,0x1fac,0x3dcc,0x15a033c0,0x22c,0x204c,0x3e6c,0x16403460,
0x80,0x2800,0x4620,0x142c324c,0x120,0x28a0,0x46c0,0x14cc32ec,0x1c0,0x2940,0x4760,0x156c338c,0x260,0x29e0,0x4800,0x160c342c,
0xa24,0x2844,0x4664,0xa883208,0xac4,0x28e4,0x4704,0xb2832a8,0xb64,0x2984,0x47a4,0xbc83348,0xc04,0x2a24,0x4844,0xc6833e8,
0xa78,0x2898,0x4694,0xa542874,0xb18,0x2938,0x4734,0xaf42914,0xbb8,0x29d8,0x47d4,0xb9429b4,0xc58,0x2a78,0x4874,0xc342a54,
0x141c,0x323c,0x4650,0xa102830,0x14bc,0x32dc,0x46f0,0xab028d0,0x155c,0x337c,0x4790,0xb502970,0x15fc,0x341c,0x4830,0xbf02a10,
0x1450,0x3270,0x461c,0x7c1e9c,0x14f0,0x3310,0x46bc,0x11c1f3c,0x1590,0x33b0,0x475c,0x1bc1fdc,0x1630,0x3450,0x47fc,0x25c207c,
0x1494,0x3c14,0x3c78,0x381e58,0x1534,0x3cb4,0x3d18,0xd81ef8,0x15d4,0x3d54,0x3db8,0x1781f98,0x1674,0x3df4,0x3e58,0x2182038,
0x3f80,0x3f800000,0x3f0e3f55,0x3f55bf0e,0x3e163f7d,0x3f7dbe16,0x3f2c3f3e,0x3f3ebf2c,0x3e953f75,0x3f75be95,0x3f463f22,0x3f22bf46,0x3edb3f67,0x3f67bedb,0x3f5c3f04,0x3f04bf5c,
0x3f80,0x3f800000,0xbf0ebf55,0xbf553f0e,0x3f4e3f18,0x3f18bf4e,0xbf80bd49,0xbd493f80,0x3f75be95,0xbe95bf75,0xbf223f46,0x3f463f22,0x3eacbf71,0xbf71beac,0x3e793f78,0x3f78be79,
0x3f80,0x3f800000,0x3f0e3f55,0x3f55bf0e,0x3f7dbe16,0xbe16bf7d,0x3f3ebf2c,0xbf2cbf3e,0xbe95bf75,0xbf753e95,0xbf46bf22,0xbf223f46,0xbf673edb,0x3edb3f67,0xbf043f5c,0x3f5c3f04,
0x3f80,0x3f800000,0xbf0ebf55,0xbf553f0e,0x3f18bf4e,0xbf4ebf18,0xbd493f80,0x3f803d49,0xbf753e95,0x3e953f75,0x3f22bf46,0xbf46bf22,0x3f713eac,0x3eacbf71,0xbf783e79,0x3e793f78,
0x3f80,0x3f800000,0x3f0e3f55,0x3f55bf0e,0xbe16bf7d,0xbf7d3e16,0xbf2cbf3e,0xbf3e3f2c,0x3e953f75,0x3f75be95,0x3f463f22,0x3f22bf46,0xbedbbf67,0xbf673edb,0xbf5cbf04,0xbf043f5c,
0x3f80,0x3f800000,0xbf0ebf55,0xbf553f0e,0xbf4ebf18,0xbf183f4e,0x3f803d49,0x3d49bf80,0x3f75be95,0xbe95bf75,0xbf223f46,0x3f463f22,0xbeac3f71,0x3f713eac,0xbe79bf78,0xbf783e79,
0x3f80,0x3f800000,0x3f0e3f55,0x3f55bf0e,0xbf7d3e16,0x3e163f7d,0xbf3e3f2c,0x3f2c3f3e,0xbe95bf75,0xbf753e95,0xbf46bf22,0xbf223f46,0x3f67bedb,0xbedbbf67,0x3f04bf5c,0xbf5cbf04,
0x3f80,0x3f800000,0xbf0ebf55,0xbf553f0e,0xbf183f4e,0x3f4e3f18,0x3d49bf80,0xbf80bd49,0xbf753e95,0x3e953f75,0x3f22bf46,0xbf46bf22,0xbf71beac,0xbeac3f71,0x3f78be79,0xbe79bf78,
0x3cf13f80,0x3f80bcf1,0x3f143f51,0x3f51bf14,0x3e343f7c,0x3f7cbe34,0x3f313f39,0x3f39bf31,0x3ea33f73,0x3f73bea3,0x3f4b3f1d,0x3f1dbf4b,0x3ee83f64,0x3f64bee8,0x3f5f3efa,0x3efabf5f,
0x3e3e3f7c,0x3f7cbe3e,0xbf33bf37,0xbf373f33,0x3f663edf,0x3edfbf66,0xbf7e3e0c,0x3e0c3f7e,0x3f63beed,0xbeedbf63,0xbef63f61,0x3f613ef6,0x3e20bf7d,0xbf7dbe20,0x3ed63f68,0x3f68bed6,
0x3eac3f71,0x3f71beac,0x3f4e3f18,0x3f18bf4e,0x3f62bef1,0xbef1bf62,0x3ef1bf62,0xbf62bef1,0xbf18bf4e,0xbf4e3f18,0xbf71beac,0xbeac3f71,0xbf353f35,0x3f353f35,0xbe483f7b,0x3f7b3e48,
0x3ef63f61,0x3f61bef6,0xbf63beed,0xbeed3f63,0x3e0cbf7e,0xbf7ebe0c,0x3edf3f66,0x3f66bedf,0xbf333f37,0x3f373f33,0x3e3ebf7c,0xbf7cbe3e,0x3f7dbe20,0xbe20bf7d,0xbf3c3f2e,0x3f2e3f3c,
0x3f1d3f4b,0x3f4bbf1d,0x3f733ea3,0x3ea3bf73,0xbf39bf31,0xbf313f39,0xbf7cbe34,0xbe343f7c,0x3f513f14,0x3f14bf51,0x3f803cf1,0x3cf1bf80,0xbf64bee8,0xbee83f64,0xbf7e3df1,0x3df13f7e,
0x3f3a3f30,0x3f30bf3a,0xbf7cbe2a,0xbe2a3f7c,0xbf7c3e34,0x3e343f7c,0x3f39bf31,0xbf31bf39,0x3ee4bf65,0xbf65bee4,0x3e023f7e,0x3f7ebe02,0x3ee83f64,0x3f64bee8,0xbf5fbefa,0xbefa3f5f,
0x3f533f10,0x3f10bf53,0x3f803c21,0x3c21bf80,0xbedf3f66,0x3f663edf,0x3e0c3f7e,0x3f7ebe0c,0xbf74be99,0xbe993f74,0xbf763e90,0x3e903f76,0x3e20bf7d,0xbf7dbe20,0xbed6bf68,0xbf683ed6,
0x3f673edb,0x3edbbf67,0xbf7d3e16,0x3e163f7d,0x3ef13f62,0x3f62bef1,0xbf62bef1,0xbef13f62,0xbe163f7d,0x3f7d3e16,0xbedbbf67,0xbf673edb,0xbf353f35,0x3f353f35,0x3e48bf7b,0xbf7bbe48,
0x3d713f80,0x3f80bd71,0x3f1b3f4c,0x3f4cbf1b,0x3e523f7b,0x3f7bbe52,0x3f373f33,0x3f33bf37,0x3eb13f70,0x3f70beb1,0x3f4f3f16,0x3f16bf4f,0x3ef63f61,0x3f61bef6,0x3f633eed,0x3eedbf63,
0x3ebb3f6e,0x3f6ebebb,0xbf52bf12,0xbf123f52,0x3f773e86,0x3e86bf77,0xbf733ea3,0x3ea33f73,0x3f49bf1e,0xbf1ebf49,0xbe9e3f73,0x3f733e9e,0xbcf1bf80,0xbf803cf1,0x3f143f51,0x3f51bf14,
0x3f223f46,0x3f46bf22,0x3f753e95,0x3e95bf75,0x3f2cbf3e,0xbf3ebf2c,0x3e16bf7d,0xbf7dbe16,0xbf55bf0e,0xbf0e3f55,0xbf800000,0x3f80,0xbedb3f67,0x3f673edb,0x3e163f7d,0x3f7dbe16,
0x3f583f0a,0x3f0abf58,0xbf803ca1,0x3ca13f80,0xbeb6bf6f,0xbf6f3eb6,0x3f513f14,0x3f14bf51,0xbe8b3f76,0x3f763e8b,0xbe9ebf73,0xbf733e9e,0x3f4bbf1d,0xbf1dbf4b,0xbea33f73,0x3f733ea3,
0x3f783e81,0x3e81bf78,0x3f72bea8,0xbea8bf72,0xbf7fbddd,0xbddd3f7f,0xbf633eed,0x3eed3f63,0x3f80bd21,0xbd21bf80,0x3f4fbf16,0xbf16bf4f,0xbf7c3e3e,0x3e3e3f7c,0xbf373f33,0x3f333f37,
0x3f80bd71,0xbd71bf80,0xbf4c3f1b,0x3f1b3f4c,0xbf0c3f56,0x3f563f0c,0xbc21bf80,0xbf803c21,0xbeb1bf70,0xbf703eb1,0x3f4f3f16,0x3f16bf4f,0x3f763e90,0x3e90bf76,0xbf743e99,0x3e993f74,
0x3f6ebebb,0xbebbbf6e,0x3f12bf52,0xbf52bf12,0x3eff3f5e,0x3f5ebeff,0x3f653ee4,0x3ee4bf65,0xbf493f1e,0x3f1e3f49,0xbe9e3f73,0x3f733e9e,0xbf3abf30,0xbf303f3a,0xbf7cbe2a,0xbe2a3f7c,
0x3f46bf22,0xbf22bf46,0xbe953f75,0x3f753e95,0x3f80bd49,0xbd49bf80,0xbf4e3f18,0x3f183f4e,0x3f553f0e,0x3f0ebf55,0xbf800000,0x3f80,0x3eac3f71,0x3f71beac,0xbf4ebf18,0xbf183f4e,
0x3db53f7f,0x3f7fbdb5,0x3f203f47,0x3f47bf20,0x3e6f3f79,0x3f79be6f,0x3f3c3f2e,0x3f2ebf3c,0x3ebf3f6d,0x3f6dbebf,0x3f533f10,0x3f10bf53,0x3f013f5d,0x3f5dbf01,0x3f663edf,0x3edfbf66,
0x3f083f59,0x3f59bf08,0xbf6abed2,0xbed23f6a,0x3f7f3da1,0x3da1bf7f,0xbf5f3efa,0x3efa3f5f,0x3f28bf41,0xbf41bf28,0xbe023f7e,0x3f7e3e02,0xbe5bbf7a,0xbf7a3e5b,0x3f393f31,0x3f31bf39,
0x3f5c3f04,0x3f04bf5c,0x3f80bd49,0xbd49bf80,0x3ec4bf6d,0xbf6dbec4,0xbe48bf7b,0xbf7b3e48,0xbf78be79,0xbe793f78,0xbf713eac,0x3eac3f71,0xbdc93f7f,0x3f7f3dc9,0x3ef13f62,0x3f62bef1,
0x3f7f3d8d,0x3d8dbf7f,0xbf5e3eff,0x3eff3f5e,0xbf43bf26,0xbf263f43,0x3f7e3df1,0x3df1bf7e,0x3e653f7a,0x3f7abe65,0xbf3abf30,0xbf303f3a,0x3ecdbf6b,0xbf6bbecd,0x3e343f7c,0x3f7cbe34,
0x3f6cbec9,0xbec9bf6c,0x3f0cbf56,0xbf56bf0c,0xbf5a3f06,0x3f063f5a,0xbed63f68,0x3f683ed6,0x3f44bf24,0xbf24bf44,0x3e90bf76,0xbf76be90,0xbf2a3f3f,0x3f3f3f2a,0xbe0c3f7e,0x3f7e3e0c,
0x3f24bf44,0xbf44bf24,0xbddd3f7f,0x3f7f3ddd,0x3e6f3f79,0x3f79be6f,0xbf3cbf2e,0xbf2e3f3c,0xbf6cbec9,0xbec93f6c,0x3f7cbe3e,0xbe3ebf7c,0x3f5dbf01,0xbf01bf5d,0xbedf3f66,0x3f663edf,
0x3e65bf7a,0xbf7abe65,0xbeb6bf6f,0xbf6f3eb6,0x3f7f3da1,0x3da1bf7f,0x3f5fbefa,0xbefabf5f,0x3d8d3f7f,0x3f7fbd8d,0x3f1d3f4b,0x3f4bbf1d,0xbf7a3e5b,0x3e5b3f7a,0xbf313f39,0x3f393f31,
0xbe79bf78,0xbf783e79,0x3f3e3f2c,0x3f2cbf3e,0x3ec4bf6d,0xbf6dbec4,0x3e483f7b,0x3f7bbe48,0x3f5cbf04,0xbf04bf5c,0xbedb3f67,0x3f673edb,0x3f7f3dc9,0x3dc9bf7f,0xbf623ef1,0x3ef13f62,
0x3df13f7e,0x3f7ebdf1,0x3f263f43,0x3f43bf26,0x3e863f77,0x3f77be86,0x3f413f28,0x3f28bf41,0x3ecd3f6b,0x3f6bbecd,0x3f583f0a,0x3f0abf58,0x3f083f59,0x3f59bf08,0x3f6a3ed2,0x3ed2bf6a,
0x3f2e3f3c,0x3f3cbf2e,0xbf79be6f,0xbe6f3f79,0x3f7fbddd,0xbdddbf7f,0xbf443f24,0x3f243f44,0x3f01bf5d,0xbf5dbf01,0x3d713f80,0x3f80bd71,0xbec9bf6c,0xbf6c3ec9,0x3f563f0c,0x3f0cbf56,
0x3f7b3e48,0x3e48bf7b,0x3f6dbec4,0xbec4bf6d,0x3d49bf80,0xbf80bd49,0xbf04bf5c,0xbf5c3f04,0xbf7f3dc9,0x3dc93f7f,0xbf463f22,0x3f223f46,0x3e793f78,0x3f78be79,0x3f3e3f2c,0x3f2cbf3e,
0x3f68bed6,0xbed6bf68,0xbf063f5a,0x3f5a3f06,0xbf7bbe52,0xbe523f7b,0x3f6dbebf,0xbebfbf6d,0x3f2a3f3f,0x3f3fbf2a,0xbf78be81,0xbe813f78,0xbdb5bf7f,0xbf7f3db5,0x3f203f47,0x3f47bf20,
0x3efabf5f,0xbf5fbefa,0xbda1bf7f,0xbf7f3da1,0xbeb63f6f,0x3f6f3eb6,0x3e653f7a,0x3f7abe65,0x3e5bbf7a,0xbf7abe5b,0xbebbbf6e,0xbf6e3ebb,0xbd8d3f7f,0x3f7f3d8d,0x3eff3f5e,0x3f5ebeff,
0xbdf1bf7e,0xbf7e3df1,0x3f263f43,0x3f43bf26,0x3f5e3eff,0x3effbf5e,0xbf7f3d8d,0x3d8d3f7f,0xbf6b3ecd,0x3ecd3f6b,0x3f0abf58,0xbf58bf0a,0x3e65bf7a,0xbf7abe65,0x3eb63f6f,0x3f6fbeb6,
0xbf2ebf3c,0xbf3c3f2e,0xbf79be6f,0xbe6f3f79,0x3f20bf47,0xbf47bf20,0x3db5bf7f,0xbf7fbdb5,0x3f5d3f01,0x3f01bf5d,0x3f80bd71,0xbd71bf80,0xbebf3f6d,0x3f6d3ebf,0x3e523f7b,0x3f7bbe52,
0xbf7bbe48,0xbe483f7b,0x3f6dbec4,0xbec4bf6d,0xbf2cbf3e,0xbf3e3f2c,0x3f783e79,0x3e79bf78,0xbdc9bf7f,0xbf7f3dc9,0x3f223f46,0x3f46bf22,0x3f04bf5c,0xbf5cbf04,0x3d493f80,0x3f80bd49,
0xc,0x1e2c,0x3c4c,0x1e083c28,0xac,0x1ecc,0x3cec,0x1ea83cc8,0x14c,0x1f6c,0x3d8c,0x1f483d68,0x1ec,0x200c,0x3e2c,0x1fe83e08,
0x48,0x1e68,0x3c88,0x146c328c,0xe8,0x1f08,0x3d28,0x150c332c,0x188,0x1fa8,0x3dc8,0x15ac33cc,0x228,0x2048,0x3e68,0x164c346c,
0x84,0x2804,0x4624,0x14203240,0x124,0x28a4,0x46c4,0x14c032e0,0x1c4,0x2944,0x4764,0x15603380,0x264,0x29e4,0x4804,0x16003420,
0xa20,0x2840,0x4660,0xa843204,0xac0,0x28e0,0x4700,0xb2432a4,0xb60,0x2980,0x47a0,0xbc43344,0xc00,0x2a20,0x4840,0xc6433e4,
0xa7c,0x289c,0x4698,0xa582878,0xb1c,0x293c,0x4738,0xaf82918,0xbbc,0x29dc,0x47d8,0xb9829b8,0xc5c,0x2a7c,0x4878,0xc382a58,
0x1418,0x3238,0x465c,0xa1c283c,0x14b8,0x32d8,0x46fc,0xabc28dc,0x1558,0x3378,0x479c,0xb5c297c,0x15f8,0x3418,0x483c,0xbfc2a1c,
0x1454,0x3274,0x4610,0x701e90,0x14f4,0x3314,0x46b0,0x1101f30,0x1594,0x33b4,0x4750,0x1b01fd0,0x1634,0x3454,0x47f0,0x2502070,
0x1490,0x3c10,0x3c74,0x341e54,0x1530,0x3cb0,0x3d14,0xd41ef4,0x15d0,0x3d50,0x3db4,0x1741f94,0x1670,0x3df0,0x3e54,0x2142034,
0x3f80,0x3f800000,0x3f353f35,0x3f35bf35,0x3e483f7b,0x3f7bbe48,0x3f553f0e,0x3f0ebf55,0x3ec43f6d,0x3f6dbec4,0x3f6d3ec4,0x3ec4bf6d,0x3f0e3f55,0x3f55bf0e,0x3f7b3e48,0x3e48bf7b,
0x3f80,0x3f800000,0xbf35bf35,0xbf353f35,0x3f553f0e,0x3f0ebf55,0xbf7b3e48,0x3e483f7b,0x3f6dbec4,0xbec4bf6d,0xbec43f6d,0x3f6d3ec4,0x3e48bf7b,0xbf7bbe48,0x3f0e3f55,0x3f55bf0e,
0x3f80,0x3f800000,0x3f353f35,0x3f35bf35,0x3f7bbe48,0xbe48bf7b,0x3f0ebf55,0xbf55bf0e,0xbec4bf6d,0xbf6d3ec4,0xbf6dbec4,0xbec43f6d,0xbf553f0e,0x3f0e3f55,0xbe483f7b,0x3f7b3e48,
0x3f80,0x3f800000,0xbf35bf35,0xbf353f35,0x3f0ebf55,0xbf55bf0e,0x3e483f7b,0x3f7bbe48,0xbf6d3ec4,0x3ec43f6d,0x3ec4bf6d,0xbf6dbec4,0x3f7b3e48,0x3e48bf7b,0xbf553f0e,0x3f0e3f55,
0x3f80,0x3f800000,0x3f353f35,0x3f35bf35,0xbe48bf7b,0xbf7b3e48,0xbf55bf0e,0xbf0e3f55,0x3ec43f6d,0x3f6dbec4,0x3f6d3ec4,0x3ec4bf6d,0xbf0ebf55,0xbf553f0e,0xbf7bbe48,0xbe483f7b,
0x3f80,0x3f800000,0xbf35bf35,0xbf353f35,0xbf55bf0e,0xbf0e3f55,0x3f7bbe48,0xbe48bf7b,0x3f6dbec4,0xbec4bf6d,0xbec43f6d,0x3f6d3ec4,0xbe483f7b,0x3f7b3e48,0xbf0ebf55,0xbf553f0e,
0x3f80,0x3f800000,0x3f353f35,0x3f35bf35,0xbf7b3e48,0x3e483f7b,0xbf0e3f55,0x3f553f0e,0xbec4bf6d,0xbf6d3ec4,0xbf6dbec4,0xbec43f6d,0x3f55bf0e,0xbf0ebf55,0x3e48bf7b,0xbf7bbe48,
0x3f80,0x3f800000,0xbf35bf35,0xbf353f35,0xbf0e3f55,0x3f553f0e,0xbe48bf7b,0xbf7b3e48,0xbf6d3ec4,0x3ec43f6d,0x3ec4bf6d,0xbf6dbec4,0xbf7bbe48,0xbe483f7b,0x3f55bf0e,0xbf0ebf55,
0x3d213f80,0x3f80bd21,0x3f3c3f2e,0x3f2ebf3c,0x3e6f3f79,0x3f79be6f,0x3f5a3f06,0x3f06bf5a,0x3ed63f68,0x3f68bed6,0x3f703eb1,0x3eb1bf70,0x3f163f4f,0x3f4fbf16,0x3f7d3e20,0x3e20bf7d,
0x3e483f7b,0x3f7bbe48,0xbf55bf0e,0xbf0e3f55,0x3f6d3ec4,0x3ec4bf6d,0xbf6d3ec4,0x3ec43f6d,0x3f55bf0e,0xbf0ebf55,0xbe483f7b,0x3f7b3e48,0xbf80,0xbf800000,0x3f353f35,0x3f35bf35,
0x3eb13f70,0x3f70beb1,0x3f683ed6,0x3ed6bf68,0x3f5abf06,0xbf06bf5a,0x3e6fbf79,0xbf79be6f,0xbf2ebf3c,0xbf3c3f2e,0xbf80bd21,0xbd213f80,0xbf163f4f,0x3f4f3f16,0x3e203f7d,0x3f7dbe20,
0x3efa3f5f,0x3f5fbefa,0xbf76be8b,0xbe8b3f76,0x3da1bf7f,0xbf7fbda1,0x3f263f43,0x3f43bf26,0xbf1e3f49,0x3f493f1e,0xbdf1bf7e,0xbf7e3df1,0x3f73be9e,0xbe9ebf73,0xbee83f64,0x3f643ee8,
0x3f1e3f49,0x3f49bf1e,0x3f7e3df1,0x3df1bf7e,0xbf43bf26,0xbf263f43,0xbf7f3da1,0x3da13f7f,0x3f5f3efa,0x3efabf5f,0x3f76be8b,0xbe8bbf76,0xbf73be9e,0xbe9e3f73,0xbf643ee8,0x3ee83f64,
0x3f3c3f2e,0x3f2ebf3c,0xbf803d21,0x3d213f80,0xbf793e6f,0x3e6f3f79,0x3f06bf5a,0xbf5abf06,0x3eb1bf70,0xbf70beb1,0x3ed63f68,0x3f68bed6,0x3f163f4f,0x3f4fbf16,0xbf7dbe20,0xbe203f7d,
0x3f553f0e,0x3f0ebf55,0x3f7bbe48,0xbe48bf7b,0xbec43f6d,0x3f6d3ec4,0x3ec43f6d,0x3f6dbec4,0xbf7bbe48,0xbe483f7b,0xbf553f0e,0x3f0e3f55,0xbf80,0xbf800000,0xbf35bf35,0xbf353f35,
0x3f683ed6,0x3ed6bf68,0xbf703eb1,0x3eb13f70,0x3f063f5a,0x3f5abf06,0xbf79be6f,0xbe6f3f79,0xbd213f80,0x3f803d21,0xbf2ebf3c,0xbf3c3f2e,0xbf163f4f,0x3f4f3f16,0xbe20bf7d,0xbf7d3e20,
0x3da13f7f,0x3f7fbda1,0x3f433f26,0x3f26bf43,0x3e8b3f76,0x3f76be8b,0x3f5f3efa,0x3efabf5f,0x3ee83f64,0x3f64bee8,0x3f733e9e,0x3e9ebf73,0x3f1e3f49,0x3f49bf1e,0x3f7e3df1,0x3df1bf7e,
0x3ec43f6d,0x3f6dbec4,0xbf6dbec4,0xbec43f6d,0x3f7b3e48,0x3e48bf7b,0xbf553f0e,0x3f0e3f55,0x3f35bf35,0xbf35bf35,0x3f80,0x3f800000,0xbe48bf7b,0xbf7b3e48,0x3f553f0e,0x3f0ebf55,
0x3f263f43,0x3f43bf26,0x3f7f3da1,0x3da1bf7f,0x3f1ebf49,0xbf49bf1e,0xbdf1bf7e,0xbf7e3df1,0xbf64bee8,0xbee83f64,0xbf733e9e,0x3e9e3f73,0xbe8b3f76,0x3f763e8b,0x3efa3f5f,0x3f5fbefa,
0x3f5a3f06,0x3f06bf5a,0xbf793e6f,0x3e6f3f79,0xbed6bf68,0xbf683ed6,0x3f703eb1,0x3eb1bf70,0xbe203f7d,0x3f7d3e20,0xbf16bf4f,0xbf4f3f16,0x3f2ebf3c,0xbf3cbf2e,0x3d213f80,0x3f80bd21,
0x3f793e6f,0x3e6fbf79,0x3f5abf06,0xbf06bf5a,0xbf80bd21,0xbd213f80,0xbf3c3f2e,0x3f2e3f3c,0x3f7dbe20,0xbe20bf7d,0x3f16bf4f,0xbf4fbf16,0xbf703eb1,0x3eb13f70,0xbed63f68,0x3f683ed6,
0x3f7fbda1,0xbda1bf7f,0xbf263f43,0x3f433f26,0xbefa3f5f,0x3f5f3efa,0xbe8bbf76,0xbf763e8b,0xbee8bf64,0xbf643ee8,0x3f733e9e,0x3e9ebf73,0x3f7e3df1,0x3df1bf7e,0xbf493f1e,0x3f1e3f49,
0x3f6dbec4,0xbec4bf6d,0x3ec4bf6d,0xbf6dbec4,0x3f0e3f55,0x3f55bf0e,0x3f7b3e48,0x3e48bf7b,0xbf353f35,0x3f353f35,0x3f80,0x3f800000,0xbf55bf0e,0xbf0e3f55,0xbf7b3e48,0x3e483f7b,
0x3f43bf26,0xbf26bf43,0xbda13f7f,0x3f7f3da1,0x3f7ebdf1,0xbdf1bf7e,0xbf1e3f49,0x3f493f1e,0x3f643ee8,0x3ee8bf64,0xbf733e9e,0x3e9e3f73,0x3efa3f5f,0x3f5fbefa,0xbf76be8b,0xbe8b3f76,
0x3df13f7e,0x3f7ebdf1,0x3f493f1e,0x3f1ebf49,0x3e9e3f73,0x3f73be9e,0x3f643ee8,0x3ee8bf64,0x3efa3f5f,0x3f5fbefa,0x3f763e8b,0x3e8bbf76,0x3f263f43,0x3f43bf26,0x3f7f3da1,0x3da1bf7f,
0x3f0e3f55,0x3f55bf0e,0xbf7bbe48,0xbe483f7b,0x3f800000,0xbf80,0xbf353f35,0x3f353f35,0x3f0ebf55,0xbf55bf0e,0x3e483f7b,0x3f7bbe48,0xbec4bf6d,0xbf6d3ec4,0x3f6d3ec4,0x3ec4bf6d,
0x3f5f3efa,0x3efabf5f,0x3f76be8b,0xbe8bbf76,0x3e9ebf73,0xbf73be9e,0xbee8bf64,0xbf643ee8,0xbf7ebdf1,0xbdf13f7e,0xbf493f1e,0x3f1e3f49,0x3da13f7f,0x3f7fbda1,0x3f433f26,0x3f26bf43,
0x3f803d21,0x3d21bf80,0xbf3c3f2e,0x3f2e3f3c,0xbf4fbf16,0xbf163f4f,0x3f7dbe20,0xbe20bf7d,0x3eb13f70,0x3f70beb1,0xbf68bed6,0xbed63f68,0x3e6fbf79,0xbf79be6f,0x3f063f5a,0x3f5abf06,
0x3f68bed6,0xbed6bf68,0x3eb1bf70,0xbf70beb1,0xbf4f3f16,0x3f163f4f,0xbe203f7d,0x3f7d3e20,0x3f2ebf3c,0xbf3cbf2e,0xbd21bf80,0xbf803d21,0xbf063f5a,0x3f5a3f06,0x3e6f3f79,0x3f79be6f,
0x3f1ebf49,0xbf49bf1e,0x3df13f7e,0x3f7ebdf1,0x3e9e3f73,0x3f73be9e,0xbf64bee8,0xbee83f64,0xbf76be8b,0xbe8b3f76,0x3f5fbefa,0xbefabf5f,0x3f43bf26,0xbf26bf43,0xbda13f7f,0x3f7f3da1,
0x3e48bf7b,0xbf7bbe48,0xbf0ebf55,0xbf553f0e,0x3f800000,0xbf80,0x3f35bf35,0xbf35bf35,0x3e483f7b,0x3f7bbe48,0x3f553f0e,0x3f0ebf55,0xbf6d3ec4,0x3ec43f6d,0xbec43f6d,0x3f6d3ec4,
0xbe8bbf76,0xbf763e8b,0x3f5f3efa,0x3efabf5f,0x3e9ebf73,0xbf73be9e,0x3ee83f64,0x3f64bee8,0x3f49bf1e,0xbf1ebf49,0xbdf13f7e,0x3f7e3df1,0x3f7fbda1,0xbda1bf7f,0xbf263f43,0x3f433f26,
0x3e203f7d,0x3f7dbe20,0x3f4f3f16,0x3f16bf4f,0x3eb13f70,0x3f70beb1,0x3f683ed6,0x3ed6bf68,0x3f063f5a,0x3f5abf06,0x3f793e6f,0x3e6fbf79,0x3f2e3f3c,0x3f3cbf2e,0x3f803d21,0x3d21bf80,
0x3f353f35,0x3f35bf35,0xbf800000,0x3f80,0x3f7bbe48,0xbe48bf7b,0xbf0e3f55,0x3f553f0e,0x3ec4bf6d,0xbf6dbec4,0x3ec43f6d,0x3f6dbec4,0xbf0ebf55,0xbf553f0e,0x3f7b3e48,0x3e48bf7b,
0x3f7d3e20,0x3e20bf7d,0x3f4fbf16,0xbf16bf4f,0xbd21bf80,0xbf803d21,0xbf3cbf2e,0xbf2e3f3c,0xbf793e6f,0x3e6f3f79,0xbf063f5a,0x3f5a3f06,0x3ed63f68,0x3f68bed6,0x3f703eb1,0x3eb1bf70,
0x3f64bee8,0xbee8bf64,0xbe9e3f73,0x3f733e9e,0xbf7ebdf1,0xbdf13f7e,0x3f49bf1e,0xbf1ebf49,0x3f433f26,0x3f26bf43,0xbf7f3da1,0x3da13f7f,0xbe8bbf76,0xbf763e8b,0x3f5f3efa,0x3efabf5f,
0x3ee8bf64,0xbf64bee8,0xbe9ebf73,0xbf733e9e,0xbe8b3f76,0x3f763e8b,0x3efa3f5f,0x3f5fbefa,0x3da1bf7f,0xbf7fbda1,0xbf26bf43,0xbf433f26,0x3df13f7e,0x3f7ebdf1,0x3f493f1e,0x3f1ebf49,
0xbe20bf7d,0xbf7d3e20,0x3f4f3f16,0x3f16bf4f,0x3f683ed6,0x3ed6bf68,0xbf703eb1,0x3eb13f70,0xbf5a3f06,0x3f063f5a,0x3e6fbf79,0xbf79be6f,0x3d21bf80,0xbf80bd21,0x3f2e3f3c,0x3f3cbf2e,
0xbf35bf35,0xbf353f35,0xbf800000,0x3f80,0x3f0ebf55,0xbf55bf0e,0xbe48bf7b,0xbf7b3e48,0x3f6d3ec4,0x3ec4bf6d,0x3f6dbec4,0xbec4bf6d,0xbe483f7b,0x3f7b3e48,0x3f0e3f55,0x3f55bf0e,
0xbf7dbe20,0xbe203f7d,0x3f4fbf16,0xbf16bf4f,0xbf3cbf2e,0xbf2e3f3c,0x3f80bd21,0xbd21bf80,0xbe6fbf79,0xbf793e6f,0x3f5a3f06,0x3f06bf5a,0x3eb1bf70,0xbf70beb1,0x3ed63f68,0x3f68bed6,
0x10,0x1e30,0x3c50,0x1e0c3c2c,0xb0,0x1ed0,0x3cf0,0x1eac3ccc,0x150,0x1f70,0x3d90,0x1f4c3d6c,0x1f0,0x2010,0x3e30,0x1fec3e0c,
0x54,0x1e74,0x3c94,0x14683288,0xf4,0x1f14,0x3d34,0x15083328,0x194,0x1fb4,0x3dd4,0x15a833c8,0x234,0x2054,0x3e74,0x16483468,
0x98,0x2818,0x4638,0x14243244,0x138,0x28b8,0x46d8,0x14c432e4,0x1d8,0x2958,0x4778,0x15643384,0x278,0x29f8,0x4818,0x16043424,
0xa3c,0x285c,0x467c,0xa803200,0xadc,0x28fc,0x471c,0xb2032a0,0xb7c,0x299c,0x47bc,0xbc03340,0xc1c,0x2a3c,0x485c,0xc6033e0,
0xa60,0x2880,0x469c,0xa5c287c,0xb00,0x2920,0x473c,0xafc291c,0xba0,0x29c0,0x47dc,0xb9c29bc,0xc40,0x2a60,0x487c,0xc3c2a5c,
0x1404,0x3224,0x4658,0xa182838,0x14a4,0x32c4,0x46f8,0xab828d8,0x1544,0x3364,0x4798,0xb582978,0x15e4,0x3404,0x4838,0xbf82a18,
0x1448,0x3268,0x4614,0x741e94,0x14e8,0x3308,0x46b4,0x1141f34,0x1588,0x33a8,0x4754,0x1b41fd4,0x1628,0x3448,0x47f4,0x2542074,
0x148c,0x3c0c,0x3c70,0x301e50,0x152c,0x3cac,0x3d10,0xd01ef0,0x15cc,0x3d4c,0x3db0,0x1701f90,0x166c,0x3dec,0x3e50,0x2102030,
0x3f80,0x3f800000,0x3f553f0e,0x3f0ebf55,0x3e793f78,0x3f78be79,0x3f713eac,0x3eacbf71,0x3ef13f62,0x3f62bef1,0x3f7f3dc9,0x3dc9bf7f,0x3f2c3f3e,0x3f3ebf2c,0x3f7dbe16,0xbe16bf7d,
0x3f80,0x3f800000,0xbf55bf0e,0xbf0e3f55,0x3f5c3f04,0x3f04bf5c,0xbf673edb,0x3edb3f67,0x3f62bef1,0xbef1bf62,0xbdc93f7f,0x3f7f3dc9,0x3d49bf80,0xbf80bd49,0x3f4e3f18,0x3f18bf4e,
0x3f80,0x3f800000,0x3f553f0e,0x3f0ebf55,0x3f78be79,0xbe79bf78,0x3eacbf71,0xbf71beac,0xbef1bf62,0xbf623ef1,0xbf7fbdc9,0xbdc93f7f,0xbf3e3f2c,0x3f2c3f3e,0x3e163f7d,0x3f7dbe16,
0x3f80,0x3f800000,0xbf55bf0e,0xbf0e3f55,0x3f04bf5c,0xbf5cbf04,0x3edb3f67,0x3f67bedb,0xbf623ef1,0x3ef13f62,0x3dc9bf7f,0xbf7fbdc9,0x3f803d49,0x3d49bf80,0xbf183f4e,0x3f4e3f18,
0x3f80,0x3f800000,0x3f553f0e,0x3f0ebf55,0xbe79bf78,0xbf783e79,0xbf71beac,0xbeac3f71,0x3ef13f62,0x3f62bef1,0x3f7f3dc9,0x3dc9bf7f,0xbf2cbf3e,0xbf3e3f2c,0xbf7d3e16,0x3e163f7d,
0x3f80,0x3f800000,0xbf55bf0e,0xbf0e3f55,0xbf5cbf04,0xbf043f5c,0x3f67bedb,0xbedbbf67,0x3f62bef1,0xbef1bf62,0xbdc93f7f,0x3f7f3dc9,0xbd493f80,0x3f803d49,0xbf4ebf18,0xbf183f4e,
0x3f80,0x3f800000,0x3f553f0e,0x3f0ebf55,0xbf783e79,0x3e793f78,0xbeac3f71,0x3f713eac,0xbef1bf62,0xbf623ef1,0xbf7fbdc9,0xbdc93f7f,0x3f3ebf2c,0xbf2cbf3e,0xbe16bf7d,0xbf7d3e16,
0x3f80,0x3f800000,0xbf55bf0e,0xbf0e3f55,0xbf043f5c,0x3f5c3f04,0xbedbbf67,0xbf673edb,0xbf623ef1,0x3ef13f62,0x3dc9bf7f,0xbf7fbdc9,0xbf80bd49,0xbd493f80,0x3f18bf4e,0xbf4ebf18,
0x3d493f80,0x3f80bd49,0x3f5c3f04,0x3f04bf5c,0x3e953f75,0x3f75be95,0x3f753e95,0x3e95bf75,0x3f043f5c,0x3f5cbf04,0x3f803d49,0x3d49bf80,0x3f353f35,0x3f35bf35,0x3f7bbe48,0xbe48bf7b,
0x3e523f7b,0x3f7bbe52,0xbf6dbebf,0xbebf3f6d,0x3f723ea8,0x3ea8bf72,0xbf4c3f1b,0x3f1b3f4c,0x3f44bf24,0xbf24bf44,0x3ddd3f7f,0x3f7fbddd,0xbe20bf7d,0xbf7d3e20,0x3f683ed6,0x3ed6bf68,
0x3eb63f6f,0x3f6fbeb6,0x3f7a3e65,0x3e65bf7a,0x3f52bf12,0xbf12bf52,0xbca1bf80,0xbf803ca1,0xbf41bf28,0xbf283f41,0xbf773e86,0x3e863f77,0xbee83f64,0x3f643ee8,0x3efa3f5f,0x3f5fbefa,
0x3eff3f5e,0x3f5ebeff,0xbf7fbd8d,0xbd8d3f7f,0x3ca1bf80,0xbf80bca1,0x3f523f12,0x3f12bf52,0xbf083f59,0x3f593f08,0xbed2bf6a,0xbf6a3ed2,0x3f64bee8,0xbee8bf64,0xbdf13f7e,0x3f7e3df1,
0x3f203f47,0x3f47bf20,0x3f7fbdb5,0xbdb5bf7f,0xbf4cbf1b,0xbf1b3f4c,0xbf723ea8,0x3ea83f72,0x3f6c3ec9,0x3ec9bf6c,0x3f56bf0c,0xbf0cbf56,0xbf7dbe20,0xbe203f7d,0xbf2e3f3c,0x3f3c3f2e,
0x3f3e3f2c,0x3f2cbf3e,0xbf783e79,0x3e793f78,0xbf753e95,0x3e953f75,0x3e95bf75,0xbf75be95,0x3e79bf78,0xbf78be79,0x3f2c3f3e,0x3f3ebf2c,0x3f353f35,0x3f35bf35,0xbf7b3e48,0x3e483f7b,
0x3f563f0c,0x3f0cbf56,0x3f6cbec9,0xbec9bf6c,0xbea83f72,0x3f723ea8,0x3f1b3f4c,0x3f4cbf1b,0xbf7fbdb5,0xbdb53f7f,0xbf203f47,0x3f473f20,0xbe20bf7d,0xbf7d3e20,0xbf68bed6,0xbed63f68,
0x3f6a3ed2,0x3ed2bf6a,0xbf593f08,0x3f083f59,0x3f123f52,0x3f52bf12,0xbf803ca1,0x3ca13f80,0x3d8d3f7f,0x3f7fbd8d,0xbf5ebeff,0xbeff3f5e,0xbee83f64,0x3f643ee8,0xbefabf5f,0xbf5f3efa,
0x3dc93f7f,0x3f7fbdc9,0x3f623ef1,0x3ef1bf62,0x3eac3f71,0x3f71beac,0x3f783e79,0x3e79bf78,0x3f0e3f55,0x3f55bf0e,0x3f800000,0xbf80,0x3f3e3f2c,0x3f2cbf3e,0x3f78be79,0xbe79bf78,
0x3ecd3f6b,0x3f6bbecd,0xbf7cbe34,0xbe343f7c,0x3f7e3e02,0x3e02bf7e,0xbf283f41,0x3f413f28,0x3f1ebf49,0xbf49bf1e,0x3e9e3f73,0x3f73be9e,0xbeb6bf6f,0xbf6f3eb6,0x3f7a3e65,0x3e65bf7a,
0x3f2a3f3f,0x3f3fbf2a,0x3f7ebe0c,0xbe0cbf7e,0x3f10bf53,0xbf53bf10,0xbebfbf6d,0xbf6d3ebf,0xbf70beb1,0xbeb13f70,0xbf4f3f16,0x3f163f4f,0xbddd3f7f,0x3f7f3ddd,0x3f443f24,0x3f24bf44,
0x3f5d3f01,0x3f01bf5d,0xbf663edf,0x3edf3f66,0xbef6bf61,0xbf613ef6,0x3f7f3db5,0x3db5bf7f,0xbd213f80,0x3f803d21,0xbf4fbf16,0xbf163f4f,0x3f0cbf56,0xbf56bf0c,0x3ec93f6c,0x3f6cbec9,
0x3f7a3e5b,0x3e5bbf7a,0x3f39bf31,0xbf31bf39,0xbf803cf1,0x3cf13f80,0xbf083f59,0x3f593f08,0x3f76be8b,0xbe8bbf76,0x3e9ebf73,0xbf73be9e,0xbf5e3eff,0x3eff3f5e,0xbd8d3f7f,0x3f7f3d8d,
0x3f7fbdc9,0xbdc9bf7f,0xbef13f62,0x3f623ef1,0xbedb3f67,0x3f673edb,0xbf04bf5c,0xbf5c3f04,0xbf0ebf55,0xbf553f0e,0x3f800000,0xbf80,0x3f80bd49,0xbd49bf80,0xbf043f5c,0x3f5c3f04,
0x3f6bbecd,0xbecdbf6b,0x3e34bf7c,0xbf7cbe34,0x3f1d3f4b,0x3f4bbf1d,0x3f7fbd8d,0xbd8dbf7f,0xbf1e3f49,0x3f493f1e,0x3e9e3f73,0x3f73be9e,0xbf6abed2,0xbed23f6a,0xbf593f08,0x3f083f59,
0x3f3fbf2a,0xbf2abf3f,0x3e0c3f7e,0x3f7ebe0c,0x3f7cbe3e,0xbe3ebf7c,0xbec93f6c,0x3f6c3ec9,0x3f703eb1,0x3eb1bf70,0xbf4f3f16,0x3f163f4f,0x3f203f47,0x3f47bf20,0xbf7f3db5,0x3db53f7f,
0x3e163f7d,0x3f7dbe16,0x3f673edb,0x3edbbf67,0x3ec43f6d,0x3f6dbec4,0x3f7b3e48,0x3e48bf7b,0x3f183f4e,0x3f4ebf18,0x3f80bd49,0xbd49bf80,0x3f463f22,0x3f22bf46,0x3f75be95,0xbe95bf75,
0x3f143f51,0x3f51bf14,0xbf803cf1,0x3cf13f80,0x3f7fbda1,0xbda1bf7f,0xbefa3f5f,0x3f5f3efa,0x3ee4bf65,0xbf65bee4,0x3eff3f5e,0x3f5ebeff,0xbf0abf58,0xbf583f0a,0x3f803ca1,0x3ca1bf80,
0x3f633eed,0x3eedbf63,0x3f61bef6,0xbef6bf61,0x3e6fbf79,0xbf79be6f,0xbf2ebf3c,0xbf3c3f2e,0xbf803c21,0x3c213f80,0xbf0c3f56,0x3f563f0c,0x3e813f78,0x3f78be81,0x3f723ea8,0x3ea8bf72,
0x3f803c21,0x3c21bf80,0xbf103f53,0x3f533f10,0xbf5abf06,0xbf063f5a,0x3f68bed6,0xbed6bf68,0x3eed3f63,0x3f63beed,0xbf7fbddd,0xbddd3f7f,0x3d71bf80,0xbf80bd71,0x3f4c3f1b,0x3f1bbf4c,
0x3f65bee4,0xbee4bf65,0x3e02bf7e,0xbf7ebe02,0xbf433f26,0x3f263f43,0x3df13f7e,0x3f7ebdf1,0x3f14bf51,0xbf51bf14,0xbeb6bf6f,0xbf6f3eb6,0xbebb3f6e,0x3f6e3ebb,0x3f123f52,0x3f52bf12,
0x3f18bf4e,0xbf4ebf18,0x3eac3f71,0x3f71beac,0x3ec43f6d,0x3f6dbec4,0xbf7bbe48,0xbe483f7b,0xbf7dbe16,0xbe163f7d,0x3f2cbf3e,0xbf3ebf2c,0x3f22bf46,0xbf46bf22,0x3e953f75,0x3f75be95,
0x3e2abf7c,0xbf7cbe2a,0xbf3abf30,0xbf303f3a,0x3f7fbda1,0xbda1bf7f,0x3efabf5f,0xbf5fbefa,0x3ea33f73,0x3f73bea3,0x3f773e86,0x3e86bf77,0xbf583f0a,0x3f0a3f58,0xbca13f80,0x3f803ca1,
0xbe99bf74,0xbf743e99,0x3f763e90,0x3e90bf76,0x3e6fbf79,0xbf79be6f,0x3f2e3f3c,0x3f3cbf2e,0x3f33bf37,0xbf37bf33,0x3e523f7b,0x3f7bbe52,0x3f78be81,0xbe81bf78,0xbea83f72,0x3f723ea8,
0x3e483f7b,0x3f7bbe48,0x3f6d3ec4,0x3ec4bf6d,0x3edb3f67,0x3f67bedb,0x3f7d3e16,0x3e16bf7d,0x3f223f46,0x3f46bf22,0x3f7fbdc9,0xbdc9bf7f,0x3f4e3f18,0x3f18bf4e,0x3f71beac,0xbeacbf71,
0x3f3c3f2e,0x3f2ebf3c,0xbf793e6f,0x3e6f3f79,0x3f76be90,0xbe90bf76,0xbe993f74,0x3f743e99,0x3e81bf78,0xbf78be81,0x3f2a3f3f,0x3f3fbf2a,0xbf33bf37,0xbf373f33,0x3f7cbe3e,0xbe3ebf7c,
0x3f7e3df1,0x3df1bf7e,0x3f26bf43,0xbf43bf26,0xbe02bf7e,0xbf7e3e02,0xbf65bee4,0xbee43f65,0xbf6e3ebb,0x3ebb3f6e,0xbe5b3f7a,0x3f7a3e5b,0x3f143f51,0x3f51bf14,0x3f80bcf1,0xbcf1bf80,
0x3f5fbefa,0xbefabf5f,0xbda13f7f,0x3f7f3da1,0xbf80bcf1,0xbcf13f80,0x3f14bf51,0xbf51bf14,0x3f583f0a,0x3f0abf58,0xbf6b3ecd,0x3ecd3f6b,0xbee4bf65,0xbf653ee4,0x3f7e3e02,0x3e02bf7e,
0x3ed6bf68,0xbf68bed6,0xbf06bf5a,0xbf5a3f06,0xbe3e3f7c,0x3f7c3e3e,0x3f373f33,0x3f33bf37,0xbd71bf80,0xbf803d71,0xbf5dbf01,0xbf013f5d,0x3e993f74,0x3f74be99,0x3f763e90,0x3e90bf76,
0xbe48bf7b,0xbf7b3e48,0x3f6d3ec4,0x3ec4bf6d,0x3f713eac,0x3eacbf71,0xbf4e3f18,0x3f183f4e,0xbf463f22,0x3f223f46,0xbdc9bf7f,0xbf7f3dc9,0xbe16bf7d,0xbf7d3e16,0x3f673edb,0x3edbbf67,
0xbf3cbf2e,0xbf2e3f3c,0xbf793e6f,0x3e6f3f79,0x3ef6bf61,0xbf61bef6,0xbeedbf63,0xbf633eed,0x3f783e81,0x3e81bf78,0x3f3fbf2a,0xbf2abf3f,0xbc213f80,0x3f803c21,0x3f533f10,0x3f10bf53,
0xbf7ebdf1,0xbdf13f7e,0x3f26bf43,0xbf43bf26,0xbf4bbf1d,0xbf1d3f4b,0x3f73bea3,0xbea3bf73,0xbebbbf6e,0xbf6e3ebb,0x3f7a3e5b,0x3e5bbf7a,0x3e2abf7c,0xbf7cbe2a,0x3f3a3f30,0x3f30bf3a,
0x14,0x1e34,0x3c54,0x1e103c30,0xb4,0x1ed4,0x3cf4,0x1eb03cd0,0x154,0x1f74,0x3d94,0x1f503d70,0x1f4,0x2014,0x3e34,0x1ff03e10,
0x50,0x1e70,0x3c90,0x14743294,0xf0,0x1f10,0x3d30,0x15143334,0x190,0x1fb0,0x3dd0,0x15b433d4,0x230,0x2050,0x3e70,0x16543474,
0x9c,0x281c,0x463c,0x14383258,0x13c,0x28bc,0x46dc,0x14d832f8,0x1dc,0x295c,0x477c,0x15783398,0x27c,0x29fc,0x481c,0x16183438,
0xa38,0x2858,0x4678,0xa9c321c,0xad8,0x28f8,0x4718,0xb3c32bc,0xb78,0x2998,0x47b8,0xbdc335c,0xc18,0x2a38,0x4858,0xc7c33fc,
0xa64,0x2884,0x4680,0xa402860,0xb04,0x2924,0x4720,0xae02900,0xba4,0x29c4,0x47c0,0xb8029a0,0xc44,0x2a64,0x4860,0xc202a40,
0x1400,0x3220,0x4644,0xa042824,0x14a0,0x32c0,0x46e4,0xaa428c4,0x1540,0x3360,0x4784,0xb442964,0x15e0,0x3400,0x4824,0xbe42a04,
0x144c,0x326c,0x4608,0x681e88,0x14ec,0x330c,0x46a8,0x1081f28,0x158c,0x33ac,0x4748,0x1a81fc8,0x162c,0x344c,0x47e8,0x2482068,
0x1488,0x3c08,0x3c6c,0x2c1e4c,0x1528,0x3ca8,0x3d0c,0xcc1eec,0x15c8,0x3d48,0x3dac,0x16c1f8c,0x1668,0x3de8,0x3e4c,0x20c202c,
0x3f80,0x3f800000,0x3f6d3ec4,0x3ec4bf6d,0x3e953f75,0x3f75be95,0x3f7f3dc9,0x3dc9bf7f,0x3f0e3f55,0x3f55bf0e,0x3f7bbe48,0xbe48bf7b,0x3f463f22,0x3f22bf46,0x3f62bef1,0xbef1bf62,
0x3f80,0x3f800000,0xbf6dbec4,0xbec43f6d,0x3f623ef1,0x3ef1bf62,0xbf463f22,0x3f223f46,0x3f55bf0e,0xbf0ebf55,0x3e483f7b,0x3f7bbe48,0xbdc9bf7f,0xbf7f3dc9,0x3f753e95,0x3e95bf75,
0x3f80,0x3f800000,0x3f6d3ec4,0x3ec4bf6d,0x3f75be95,0xbe95bf75,0x3dc9bf7f,0xbf7fbdc9,0xbf0ebf55,0xbf553f0e,0xbf7b3e48,0x3e483f7b,0xbf223f46,0x3f463f22,0x3ef13f62,0x3f62bef1,
0x3f80,0x3f800000,0xbf6dbec4,0xbec43f6d,0x3ef1bf62,0xbf62bef1,0x3f223f46,0x3f46bf22,0xbf553f0e,0x3f0e3f55,0xbe48bf7b,0xbf7b3e48,0x3f7fbdc9,0xbdc9bf7f,0xbe953f75,0x3f753e95,
0x3f80,0x3f800000,0x3f6d3ec4,0x3ec4bf6d,0xbe95bf75,0xbf753e95,0xbf7fbdc9,0xbdc93f7f,0x3f0e3f55,0x3f55bf0e,0x3f7bbe48,0xbe48bf7b,0xbf46bf22,0xbf223f46,0xbf623ef1,0x3ef13f62,
0x3f80,0x3f800000,0xbf6dbec4,0xbec43f6d,0xbf62bef1,0xbef13f62,0x3f46bf22,0xbf22bf46,0x3f55bf0e,0xbf0ebf55,0x3e483f7b,0x3f7bbe48,0x3dc93f7f,0x3f7fbdc9,0xbf75be95,0xbe953f75,
0x3f80,0x3f800000,0x3f6d3ec4,0x3ec4bf6d,0xbf753e95,0x3e953f75,0xbdc93f7f,0x3f7f3dc9,0xbf0ebf55,0xbf553f0e,0xbf7b3e48,0x3e483f7b,0x3f22bf46,0xbf46bf22,0xbef1bf62,0xbf623ef1,
0x3f80,0x3f800000,0xbf6dbec4,0xbec43f6d,0xbef13f62,0x3f623ef1,0xbf22bf46,0xbf463f22,0xbf553f0e,0x3f0e3f55,0xbe48bf7b,0xbf7b3e48,0xbf7f3dc9,0x3dc93f7f,0x3e95bf75,0xbf75be95,
0x3d713f80,0x3f80bd71,0x3f723ea8,0x3ea8bf72,0x3eb13f70,0x3f70beb1,0x3f803d21,0x3d21bf80,0x3f1b3f4c,0x3f4cbf1b,0x3f78be81,0xbe81bf78,0x3f4f3f16,0x3f16bf4f,0x3f5abf06,0xbf06bf5a,
0x3e5b3f7a,0x3f7abe5b,0xbf7cbe34,0xbe343f7c,0x3f763e8b,0x3e8bbf76,0xbf1e3f49,0x3f493f1e,0x3f31bf39,0xbf39bf31,0x3ecd3f6b,0x3f6bbecd,0xbe9ebf73,0xbf733e9e,0x3f7f3da1,0x3da1bf7f,
0x3ebb3f6e,0x3f6ebebb,0x3f803ca1,0x3ca1bf80,0x3f49bf1e,0xbf1ebf49,0xbe8bbf76,0xbf763e8b,0xbf52bf12,0xbf123f52,0xbf583f0a,0x3f0a3f58,0xbe9e3f73,0x3f733e9e,0x3f433f26,0x3f26bf43,
0x3f013f5d,0x3f5dbf01,0xbf7e3e0c,0x3e0c3f7e,0xbd21bf80,0xbf803d21,0x3f703eb1,0x3eb1bf70,0xbedf3f66,0x3f663edf,0xbf2abf3f,0xbf3f3f2a,0x3f4fbf16,0xbf16bf4f,0x3e6f3f79,0x3f79be6f,
0x3f223f46,0x3f46bf22,0x3f75be95,0xbe95bf75,0xbf55bf0e,0xbf0e3f55,0xbf553f0e,0x3f0e3f55,0x3f753e95,0x3e95bf75,0x3f22bf46,0xbf46bf22,0xbf800000,0x3f80,0xbec43f6d,0x3f6d3ec4,
0x3f3f3f2a,0x3f2abf3f,0xbf663edf,0x3edf3f66,0xbf703eb1,0x3eb13f70,0x3d21bf80,0xbf80bd21,0x3e0cbf7e,0xbf7ebe0c,0x3f5d3f01,0x3f01bf5d,0x3f4f3f16,0x3f16bf4f,0xbf5a3f06,0x3f063f5a,
0x3f583f0a,0x3f0abf58,0x3f52bf12,0xbf12bf52,0xbe8b3f76,0x3f763e8b,0x3f493f1e,0x3f1ebf49,0xbf803ca1,0x3ca13f80,0xbebb3f6e,0x3f6e3ebb,0xbe9ebf73,0xbf733e9e,0xbf7fbda1,0xbda13f7f,
0x3f6b3ecd,0x3ecdbf6b,0xbf393f31,0x3f313f39,0x3f1e3f49,0x3f49bf1e,0xbf763e8b,0x3e8b3f76,0x3e343f7c,0x3f7cbe34,0xbf7abe5b,0xbe5b3f7a,0xbe9e3f73,0x3f733e9e,0xbf43bf26,0xbf263f43,
0x3df13f7e,0x3f7ebdf1,0x3f763e8b,0x3e8bbf76,0x3ecd3f6b,0x3f6bbecd,0x3f80bca1,0xbca1bf80,0x3f263f43,0x3f43bf26,0x3f73be9e,0xbe9ebf73,0x3f583f0a,0x3f0abf58,0x3f52bf12,0xbf12bf52,
0x3ed63f68,0x3f68bed6,0xbf803d21,0x3d213f80,0x3f803d71,0x3d71bf80,0xbedf3f66,0x3f663edf,0x3f06bf5a,0xbf5abf06,0x3f163f4f,0x3f4fbf16,0xbf01bf5d,0xbf5d3f01,0x3f7ebe0c,0xbe0cbf7e,
0x3f2e3f3c,0x3f3cbf2e,0x3f70beb1,0xbeb1bf70,0x3f01bf5d,0xbf5dbf01,0xbf1bbf4c,0xbf4c3f1b,0xbf79be6f,0xbe6f3f79,0xbf163f4f,0x3f4f3f16,0x3d713f80,0x3f80bd71,0x3f723ea8,0x3ea8bf72,
0x3f5f3efa,0x3efabf5f,0xbf493f1e,0x3f1e3f49,0xbf0abf58,0xbf583f0a,0x3f7cbe34,0xbe34bf7c,0x3da13f7f,0x3f7fbda1,0xbf73be9e,0xbe9e3f73,0x3ecdbf6b,0xbf6bbecd,0x3f313f39,0x3f39bf31,
0x3f7b3e48,0x3e48bf7b,0x3f0ebf55,0xbf55bf0e,0xbf7f3dc9,0x3dc93f7f,0xbe953f75,0x3f753e95,0x3f6dbec4,0xbec4bf6d,0xbf80,0xbf800000,0xbf463f22,0x3f223f46,0x3e953f75,0x3f75be95,
0x3f7ebdf1,0xbdf1bf7e,0xbe8b3f76,0x3f763e8b,0xbebb3f6e,0x3f6e3ebb,0xbf39bf31,0xbf313f39,0xbf26bf43,0xbf433f26,0x3f73be9e,0xbe9ebf73,0x3f7abe5b,0xbe5bbf7a,0xbe343f7c,0x3f7c3e34,
0x3f68bed6,0xbed6bf68,0xbd21bf80,0xbf803d21,0x3f2a3f3f,0x3f3fbf2a,0x3f72bea8,0xbea8bf72,0xbf063f5a,0x3f5a3f06,0x3f163f4f,0x3f4fbf16,0xbf78be81,0xbe813f78,0xbf1b3f4c,0x3f4c3f1b,
0x3f3cbf2e,0xbf2ebf3c,0x3eb13f70,0x3f70beb1,0x3f78be81,0xbe81bf78,0xbe0c3f7e,0x3f7e3e0c,0x3f793e6f,0x3e6fbf79,0xbf163f4f,0x3f4f3f16,0x3f3f3f2a,0x3f2abf3f,0xbf663edf,0x3edf3f66,
0x3e343f7c,0x3f7cbe34,0x3f7a3e5b,0x3e5bbf7a,0x3ee83f64,0x3f64bee8,0x3f7fbda1,0xbda1bf7f,0x3f313f39,0x3f39bf31,0x3f6ebebb,0xbebbbf6e,0x3f5f3efa,0x3efabf5f,0x3f49bf1e,0xbf1ebf49,
0x3f1b3f4c,0x3f4cbf1b,0xbf783e81,0x3e813f78,0x3f7dbe20,0xbe20bf7d,0xbe6f3f79,0x3f793e6f,0x3ea8bf72,0xbf72bea8,0x3f3f3f2a,0x3f2abf3f,0xbf2ebf3c,0xbf3c3f2e,0x3f70beb1,0xbeb1bf70,
0x3f663edf,0x3edfbf66,0x3f3fbf2a,0xbf2abf3f,0x3e20bf7d,0xbf7dbe20,0xbf5abf06,0xbf063f5a,0xbf7e3e0c,0x3e0c3f7e,0xbe813f78,0x3f783e81,0x3ed63f68,0x3f68bed6,0x3f80bd21,0xbd21bf80,
0x3f80bca1,0xbca1bf80,0xbebb3f6e,0x3f6e3ebb,0xbf64bee8,0xbee83f64,0x3f43bf26,0xbf26bf43,0x3f123f52,0x3f52bf12,0xbf7a3e5b,0x3e5b3f7a,0xbdf1bf7e,0xbf7e3df1,0x3f763e8b,0x3e8bbf76,
0x3f62bef1,0xbef1bf62,0xbdc9bf7f,0xbf7f3dc9,0xbf353f35,0x3f353f35,0x3ec43f6d,0x3f6dbec4,0x3ef1bf62,0xbf62bef1,0xbf22bf46,0xbf463f22,0xbe483f7b,0x3f7b3e48,0x3f553f0e,0x3f0ebf55,
0x3f12bf52,0xbf52bf12,0x3f0a3f58,0x3f58bf0a,0x3ee83f64,0x3f64bee8,0xbf7f3da1,0x3da13f7f,0xbf80bca1,0xbca13f80,0x3ecdbf6b,0xbf6bbecd,0x3efabf5f,0xbf5fbefa,0x3f1e3f49,0x3f49bf1e,
0x3e0cbf7e,0xbf7ebe0c,0xbf5dbf01,0xbf013f5d,0x3f7dbe20,0xbe20bf7d,0x3e6fbf79,0xbf79be6f,0x3edf3f66,0x3f66bedf,0x3f80bd71,0xbd71bf80,0xbf3c3f2e,0x3f2e3f3c,0x3eb13f70,0x3f70beb1,
0xbea8bf72,0xbf723ea8,0x3f803d71,0x3d71bf80,0x3e20bf7d,0xbf7dbe20,0x3f5a3f06,0x3f06bf5a,0x3f1bbf4c,0xbf4cbf1b,0x3f013f5d,0x3f5dbf01,0x3f68bed6,0xbed6bf68,0x3d213f80,0x3f80bd21,
0x3e6f3f79,0x3f79be6f,0x3f7d3e20,0x3e20bf7d,0x3f013f5d,0x3f5dbf01,0x3f7ebe0c,0xbe0cbf7e,0x3f3c3f2e,0x3f2ebf3c,0x3f68bed6,0xbed6bf68,0x3f663edf,0x3edfbf66,0x3f3fbf2a,0xbf2abf3f,
0x3f433f26,0x3f26bf43,0xbf643ee8,0x3ee83f64,0x3f6ebebb,0xbebbbf6e,0xbca13f80,0x3f803ca1,0x3df1bf7e,0xbf7ebdf1,0x3f5f3efa,0x3efabf5f,0xbf52bf12,0xbf123f52,0x3f58bf0a,0xbf0abf58,
0x3f7f3da1,0x3da1bf7f,0x3ee8bf64,0xbf64bee8,0xbe5bbf7a,0xbf7a3e5b,0xbf7cbe34,0xbe343f7c,0xbf5f3efa,0x3efa3f5f,0x3df13f7e,0x3f7ebdf1,0x3f393f31,0x3f31bf39,0x3f6bbecd,0xbecdbf6b,
0x3f5abf06,0xbf06bf5a,0x3e203f7d,0x3f7dbe20,0xbf803d71,0x3d713f80,0x3ea8bf72,0xbf72bea8,0x3f683ed6,0x3ed6bf68,0xbf3c3f2e,0x3f2e3f3c,0xbf1bbf4c,0xbf4c3f1b,0x3f78be81,0xbe81bf78,
0x3ec4bf6d,0xbf6dbec4,0xbf35bf35,0xbf353f35,0xbdc93f7f,0x3f7f3dc9,0x3f623ef1,0x3ef1bf62,0xbe48bf7b,0xbf7b3e48,0xbf7bbe48,0xbe483f7b,0x3ef13f62,0x3f62bef1,0x3f7fbdc9,0xbdc9bf7f,
0xbe6fbf79,0xbf793e6f,0x3f7d3e20,0x3e20bf7d,0x3f783e81,0x3e81bf78,0xbf1b3f4c,0x3f4c3f1b,0xbf2e3f3c,0x3f3c3f2e,0xbed6bf68,0xbf683ed6,0xbea8bf72,0xbf723ea8,0x3f803d71,0x3d71bf80,
0xbf43bf26,0xbf263f43,0xbf643ee8,0x3ee83f64,0x3ecdbf6b,0xbf6bbecd,0xbf31bf39,0xbf393f31,0x3f7e3df1,0x3df1bf7e,0x3efabf5f,0xbf5fbefa,0x3e343f7c,0x3f7cbe34,0x3f7a3e5b,0x3e5bbf7a,
0xbf7fbda1,0xbda13f7f,0x3ee8bf64,0xbf64bee8,0xbf58bf0a,0xbf0a3f58,0x3f52bf12,0xbf12bf52,0xbefabf5f,0xbf5f3efa,0x3f7ebdf1,0xbdf1bf7e,0xbca1bf80,0xbf803ca1,0x3f6e3ebb,0x3ebbbf6e,
0x18,0x1e38,0x3c58,0x1e143c34,0xb8,0x1ed8,0x3cf8,0x1eb43cd4,0x158,0x1f78,0x3d98,0x1f543d74,0x1f8,0x2018,0x3e38,0x1ff43e14,
0x5c,0x1e7c,0x3c9c,0x14703290,0xfc,0x1f1c,0x3d3c,0x15103330,0x19c,0x1fbc,0x3ddc,0x15b033d0,0x23c,0x205c,0x3e7c,0x16503470,
0x90,0x2810,0x4630,0x143c325c,0x130,0x28b0,0x46d0,0x14dc32fc,0x1d0,0x2950,0x4770,0x157c339c,0x270,0x29f0,0x4810,0x161c343c,
0xa34,0x2854,0x4674,0xa983218,0xad4,0x28f4,0x4714,0xb3832b8,0xb74,0x2994,0x47b4,0xbd83358,0xc14,0x2a34,0x4854,0xc7833f8,
0xa68,0x2888,0x4684,0xa442864,0xb08,0x2928,0x4724,0xae42904,0xba8,0x29c8,0x47c4,0xb8429a4,0xc48,0x2a68,0x4864,0xc242a44,
0x140c,0x322c,0x4640,0xa002820,0x14ac,0x32cc,0x46e0,0xaa028c0,0x154c,0x336c,0x4780,0xb402960,0x15ec,0x340c,0x4820,0xbe02a00,
0x1440,0x3260,0x460c,0x6c1e8c,0x14e0,0x3300,0x46ac,0x10c1f2c,0x1580,0x33a0,0x474c,0x1ac1fcc,0x1620,0x3440,0x47ec,0x24c206c,
0x1484,0x3c04,0x3c68,0x281e48,0x1524,0x3ca4,0x3d08,0xc81ee8,0x15c4,0x3d44,0x3da8,0x1681f88,0x1664,0x3de4,0x3e48,0x2082028,
0x3f80,0x3f800000,0x3f7b3e48,0x3e48bf7b,0x3eac3f71,0x3f71beac,0x3f7dbe16,0xbe16bf7d,0x3f223f46,0x3f46bf22,0x3f62bef1,0xbef1bf62,0x3f5c3f04,0x3f04bf5c,0x3f2cbf3e,0xbf3ebf2c,
0x3f80,0x3f800000,0xbf7bbe48,0xbe483f7b,0x3f673edb,0x3edbbf67,0xbf183f4e,0x3f4e3f18,0x3f46bf22,0xbf22bf46,0x3ef13f62,0x3f62bef1,0xbe79bf78,0xbf783e79,0x3f80bd49,0xbd49bf80,
0x3f80,0x3f800000,0x3f7b3e48,0x3e48bf7b,0x3f71beac,0xbeacbf71,0xbe16bf7d,0xbf7d3e16,0xbf22bf46,0xbf463f22,0xbf623ef1,0x3ef13f62,0xbf043f5c,0x3f5c3f04,0x3f3e3f2c,0x3f2cbf3e,
0x3f80,0x3f800000,0xbf7bbe48,0xbe483f7b,0x3edbbf67,0xbf67bedb,0x3f4e3f18,0x3f18bf4e,0xbf463f22,0x3f223f46,0xbef1bf62,0xbf623ef1,0x3f78be79,0xbe79bf78,0x3d493f80,0x3f80bd49,
0x3f80,0x3f800000,0x3f7b3e48,0x3e48bf7b,0xbeacbf71,0xbf713eac,0xbf7d3e16,0x3e163f7d,0x3f223f46,0x3f46bf22,0x3f62bef1,0xbef1bf62,0xbf5cbf04,0xbf043f5c,0xbf2c3f3e,0x3f3e3f2c,
0x3f80,0x3f800000,0xbf7bbe48,0xbe483f7b,0xbf67bedb,0xbedb3f67,0x3f18bf4e,0xbf4ebf18,0x3f46bf22,0xbf22bf46,0x3ef13f62,0x3f62bef1,0x3e793f78,0x3f78be79,0xbf803d49,0x3d493f80,
0x3f80,0x3f800000,0x3f7b3e48,0x3e48bf7b,0xbf713eac,0x3eac3f71,0x3e163f7d,0x3f7dbe16,0xbf22bf46,0xbf463f22,0xbf623ef1,0x3ef13f62,0x3f04bf5c,0xbf5cbf04,0xbf3ebf2c,0xbf2c3f3e,
0x3f80,0x3f800000,0xbf7bbe48,0xbe483f7b,0xbedb3f67,0x3f673edb,0xbf4ebf18,0xbf183f4e,0xbf463f22,0x3f223f46,0xbef1bf62,0xbf623ef1,0xbf783e79,0x3e793f78,0xbd49bf80,0xbf803d49,
0x3d8d3f7f,0x3f7fbd8d,0x3f7e3e02,0x3e02bf7e,0x3ecd3f6b,0x3f6bbecd,0x3f7abe5b,0xbe5bbf7a,0x3f303f3a,0x3f3abf30,0x3f59bf08,0xbf08bf59,0x3f643ee8,0x3ee8bf64,0x3f1ebf49,0xbf49bf1e,
0x3e653f7a,0x3f7abe65,0xbf803cf1,0x3cf13f80,0x3f7a3e5b,0x3e5bbf7a,0xbecd3f6b,0x3f6b3ecd,0x3f1dbf4b,0xbf4bbf1d,0x3f283f41,0x3f41bf28,0xbee8bf64,0xbf643ee8,0x3f76be8b,0xbe8bbf76,
0x3ebf3f6d,0x3f6dbebf,0x3f7cbe3e,0xbe3ebf7c,0x3f3fbf2a,0xbf2abf3f,0xbf01bf5d,0xbf5d3f01,0xbf61bef6,0xbef63f61,0xbf243f44,0x3f443f24,0xbe203f7d,0x3f7d3e20,0x3f703eb1,0x3eb1bf70,
0x3f043f5c,0x3f5cbf04,0xbf713eac,0x3eac3f71,0xbdc9bf7f,0xbf7f3dc9,0x3f7f3dc9,0x3dc9bf7f,0xbeac3f71,0x3f713eac,0xbf5cbf04,0xbf043f5c,0x3f35bf35,0xbf35bf35,0x3f0e3f55,0x3f55bf0e,
0x3f243f44,0x3f44bf24,0x3f61bef6,0xbef6bf61,0xbf5dbf01,0xbf013f5d,0xbf2a3f3f,0x3f3f3f2a,0x3f7c3e3e,0x3e3ebf7c,0x3ebfbf6d,0xbf6dbebf,0xbf7d3e20,0x3e203f7d,0xbd213f80,0x3f803d21,
0x3f413f28,0x3f28bf41,0xbf4b3f1d,0x3f1d3f4b,0xbf6b3ecd,0x3ecd3f6b,0xbe5bbf7a,0xbf7a3e5b,0x3cf1bf80,0xbf80bcf1,0x3f7a3e65,0x3e65bf7a,0x3f643ee8,0x3ee8bf64,0xbf1e3f49,0x3f493f1e,
0x3f593f08,0x3f08bf59,0x3f30bf3a,0xbf3abf30,0xbe5b3f7a,0x3f7a3e5b,0x3f6b3ecd,0x3ecdbf6b,0xbf7e3e02,0x3e023f7e,0xbd8d3f7f,0x3f7f3d8d,0xbee8bf64,0xbf643ee8,0xbf763e8b,0x3e8b3f76,
0x3f6c3ec9,0x3ec9bf6c,0xbf103f53,0x3f533f10,0x3f2a3f3f,0x3f3fbf2a,0xbf5d3f01,0x3f013f5d,0x3e903f76,0x3f76be90,0xbf7f3db5,0x3db53f7f,0xbe203f7d,0x3f7d3e20,0xbf70beb1,0xbeb13f70,
0x3e0c3f7e,0x3f7ebe0c,0x3f803d71,0x3d71bf80,0x3eed3f63,0x3f63beed,0x3f76be90,0xbe90bf76,0x3f3c3f2e,0x3f2ebf3c,0x3f4fbf16,0xbf16bf4f,0x3f6c3ec9,0x3ec9bf6c,0x3f10bf53,0xbf53bf10,
0x3edf3f66,0x3f66bedf,0xbf783e81,0x3e813f78,0x3f80bc21,0xbc21bf80,0xbe3e3f7c,0x3f7c3e3e,0x3ed6bf68,0xbf68bed6,0x3f4f3f16,0x3f16bf4f,0xbf24bf44,0xbf443f24,0x3f61bef6,0xbef6bf61,
0x3f313f39,0x3f39bf31,0x3f58bf0a,0xbf0abf58,0x3ee4bf65,0xbf65bee4,0xbf4bbf1d,0xbf1d3f4b,0xbf7ebdf1,0xbdf13f7e,0xbe9e3f73,0x3f733e9e,0x3e653f7a,0x3f7abe65,0x3f80bcf1,0xbcf1bf80,
0x3f623ef1,0x3ef1bf62,0xbf223f46,0x3f463f22,0xbf18bf4e,0xbf4e3f18,0x3f67bedb,0xbedbbf67,0x3e483f7b,0x3f7bbe48,0xbf800000,0x3f80,0x3e79bf78,0xbf78be79,0x3f673edb,0x3edbbf67,
0x3f7c3e34,0x3e34bf7c,0x3ebbbf6e,0xbf6ebebb,0xbf7c3e2a,0x3e2a3f7c,0xbcf13f80,0x3f803cf1,0x3f5fbefa,0xbefabf5f,0xbe9ebf73,0xbf733e9e,0xbf283f41,0x3f413f28,0x3f1d3f4b,0x3f4bbf1d,
0x3f7ebe0c,0xbe0cbf7e,0xbd713f80,0x3f803d71,0xbe993f74,0x3f743e99,0xbf61bef6,0xbef63f61,0xbf3cbf2e,0xbf2e3f3c,0x3f4fbf16,0xbf16bf4f,0x3f6dbebf,0xbebfbf6d,0x3e3e3f7c,0x3f7cbe3e,
0x3f66bedf,0xbedfbf66,0xbe81bf78,0xbf783e81,0x3f373f33,0x3f33bf37,0x3f53bf10,0xbf10bf53,0xbed63f68,0x3f683ed6,0x3f4f3f16,0x3f16bf4f,0xbf7fbdb5,0xbdb53f7f,0xbe903f76,0x3f763e90,
0x3f39bf31,0xbf31bf39,0x3f0a3f58,0x3f58bf0a,0x3f73bea3,0xbea3bf73,0x3e023f7e,0x3f7ebe02,0x3f7e3df1,0x3df1bf7e,0xbe9e3f73,0x3f733e9e,0x3f593f08,0x3f08bf59,0xbf303f3a,0x3f3a3f30,
0x3e523f7b,0x3f7bbe52,0x3f80bc21,0xbc21bf80,0x3f063f5a,0x3f5abf06,0x3f70beb1,0xbeb1bf70,0x3f473f20,0x3f20bf47,0x3f44bf24,0xbf24bf44,0x3f723ea8,0x3ea8bf72,0x3f01bf5d,0xbf5dbf01,
0x3f203f47,0x3f47bf20,0xbf633eed,0x3eed3f63,0x3f79be6f,0xbe6fbf79,0x3d213f80,0x3f80bd21,0x3e52bf7b,0xbf7bbe52,0x3f6c3ec9,0x3ec9bf6c,0xbf4cbf1b,0xbf1b3f4c,0x3f3fbf2a,0xbf2abf3f,
0x3f6a3ed2,0x3ed2bf6a,0x3f14bf51,0xbf51bf14,0x3da1bf7f,0xbf7fbda1,0xbf76be8b,0xbe8b3f76,0xbf773e86,0x3e863f77,0x3d8d3f7f,0x3f7fbd8d,0x3f123f52,0x3f52bf12,0x3f6bbecd,0xbecdbf6b,
0x3f80bd49,0xbd49bf80,0xbe163f7d,0x3f7d3e16,0xbf6dbec4,0xbec43f6d,0x3f0ebf55,0xbf55bf0e,0x3f2c3f3e,0x3f3ebf2c,0xbf5c3f04,0x3f043f5c,0xbe95bf75,0xbf753e95,0x3f7fbdc9,0xbdc9bf7f,
0x3f5ebeff,0xbeffbf5e,0xbea3bf73,0xbf733ea3,0xbf263f43,0x3f433f26,0x3f1e3f49,0x3f49bf1e,0x3eb6bf6f,0xbf6fbeb6,0xbf59bf08,0xbf083f59,0xbca13f80,0x3f803ca1,0x3f7a3e5b,0x3e5bbf7a,
0x3f0cbf56,0xbf56bf0c,0x3f373f33,0x3f33bf37,0x3f063f5a,0x3f5abf06,0xbf703eb1,0x3eb13f70,0xbf7f3ddd,0x3ddd3f7f,0x3db5bf7f,0xbf7fbdb5,0x3ea8bf72,0xbf72bea8,0x3f5d3f01,0x3f01bf5d,
0x3dddbf7f,0xbf7fbddd,0xbf74be99,0xbe993f74,0x3f79be6f,0xbe6fbf79,0xbd21bf80,0xbf803d21,0x3f0c3f56,0x3f56bf0c,0x3f6dbebf,0xbebfbf6d,0xbf1b3f4c,0x3f4c3f1b,0x3f2a3f3f,0x3f3fbf2a,
0xbeb6bf6f,0xbf6f3eb6,0x3f7cbe2a,0xbe2abf7c,0x3da1bf7f,0xbf7fbda1,0x3f763e8b,0x3e8bbf76,0x3effbf5e,0xbf5ebeff,0x3f413f28,0x3f28bf41,0x3f52bf12,0xbf12bf52,0x3ecd3f6b,0x3f6bbecd,
0x3e8b3f76,0x3f76be8b,0x3f7fbda1,0xbda1bf7f,0x3f143f51,0x3f51bf14,0x3f6abed2,0xbed2bf6a,0x3f523f12,0x3f12bf52,0x3f39bf31,0xbf31bf39,0x3f773e86,0x3e86bf77,0x3ee4bf65,0xbf65bee4,
0x3f493f1e,0x3f1ebf49,0xbf433f26,0x3f263f43,0x3f65bee4,0xbee4bf65,0x3e863f77,0x3f77be86,0xbca1bf80,0xbf803ca1,0x3f7c3e34,0x3e34bf7c,0xbf6abed2,0xbed23f6a,0x3f14bf51,0xbf51bf14,
0x3f803d21,0x3d21bf80,0x3e6fbf79,0xbf79be6f,0xbe99bf74,0xbf743e99,0xbf7f3ddd,0x3ddd3f7f,0xbf4c3f1b,0x3f1b3f4c,0x3edf3f66,0x3f66bedf,0x3f563f0c,0x3f0cbf56,0x3f33bf37,0xbf37bf33,
0x3f55bf0e,0xbf0ebf55,0x3ec43f6d,0x3f6dbec4,0xbf7d3e16,0x3e163f7d,0x3d49bf80,0xbf80bd49,0x3f753e95,0x3e95bf75,0xbef13f62,0x3f623ef1,0xbf3ebf2c,0xbf2c3f3e,0x3f4ebf18,0xbf18bf4e,
0x3eb1bf70,0xbf70beb1,0xbf5abf06,0xbf063f5a,0xbc213f80,0x3f803c21,0x3f7b3e52,0x3e52bf7b,0xbea8bf72,0xbf723ea8,0xbf7e3e0c,0x3e0c3f7e,0x3f203f47,0x3f47bf20,0x3f63beed,0xbeedbf63,
0xbe8bbf76,0xbf763e8b,0x3f7fbda1,0xbda1bf7f,0x3f7c3e2a,0x3e2abf7c,0xbeb63f6f,0x3f6f3eb6,0xbf123f52,0x3f523f12,0xbf31bf39,0xbf393f31,0xbeffbf5e,0xbf5e3eff,0x3f73bea3,0xbea3bf73,
0xbf49bf1e,0xbf1e3f49,0xbf433f26,0x3f263f43,0x3ea3bf73,0xbf73bea3,0xbf5ebeff,0xbeff3f5e,0x3f80bca1,0xbca1bf80,0x3e34bf7c,0xbf7cbe34,0x3eb63f6f,0x3f6fbeb6,0x3f7cbe2a,0xbe2abf7c,
0xbf80bd21,0xbd213f80,0x3e6fbf79,0xbf79be6f,0xbf63beed,0xbeed3f63,0x3f20bf47,0xbf47bf20,0xbf1bbf4c,0xbf4c3f1b,0x3f66bedf,0xbedfbf66,0xbe52bf7b,0xbf7b3e52,0x3f80bc21,0xbc21bf80,
0x1c,0x1e3c,0x3c5c,0x1e183c38,0xbc,0x1edc,0x3cfc,0x1eb83cd8,0x15c,0x1f7c,0x3d9c,0x1f583d78,0x1fc,0x201c,0x3e3c,0x1ff83e18,
0x58,0x1e78,0x3c98,0x147c329c,0xf8,0x1f18,0x3d38,0x151c333c,0x198,0x1fb8,0x3dd8,0x15bc33dc,0x238,0x2058,0x3e78,0x165c347c,
0x94,0x2814,0x4634,0x14303250,0x134,0x28b4,0x46d4,0x14d032f0,0x1d4,0x2954,0x4774,0x15703390,0x274,0x29f4,0x4814,0x16103430,
0xa30,0x2850,0x4670,0xa943214,0xad0,0x28f0,0x4710,0xb3432b4,0xb70,0x2990,0x47b0,0xbd43354,0xc10,0x2a30,0x4850,0xc7433f4,
0xa6c,0x288c,0x4688,0xa482868,0xb0c,0x292c,0x4728,0xae82908,0xbac,0x29cc,0x47c8,0xb8829a8,0xc4c,0x2a6c,0x4868,0xc282a48,
0x1408,0x3228,0x464c,0xa0c282c,0x14a8,0x32c8,0x46ec,0xaac28cc,0x1548,0x3368,0x478c,0xb4c296c,0x15e8,0x3408,0x482c,0xbec2a0c,
0x1444,0x3264,0x4600,0x601e80,0x14e4,0x3304,0x46a0,0x1001f20,0x1584,0x33a4,0x4740,0x1a01fc0,0x1624,0x3444,0x47e0,0x2402060,
0x1480,0x3c00,0x3c64,0x241e44,0x1520,0x3ca0,0x3d04,0xc41ee4,0x15c0,0x3d40,0x3da4,0x1641f84,0x1660,0x3de0,0x3e44,0x2042024,
0x40003f80,0x3f80,0xc0003f80,0x3f80,0x40004000,0,0xc0004000,0,0,0,0,0,0,0,0,0,
0,0,0,0,0,0,0,0,0x40004000,0,0,0x4000c000,0x40004000,0,0,0x4000c000,
0x3fb53f80,0xbfb5bf80,0xbfb53f80,0x3fb5bf80,0xbfb50000,0xbfb5c000,0x3fb50000,0x3fb5c000,0,0,0,0,0,0,0,0,
0,0,0,0,0,0,0,0,0x3f443fed,0xbfedbf44,0x3fedbf44,0x3f44bfed,0xbfedbf44,0xbf44bfed,0x3f44bfed,0xbfed3f44,
0x3f80,0xc0003f80,0x3f80,0x40003f80,0xc000,0x40000000,0xc000,0xc0000000,0,0,0,0,0,0,0,0,
0,0,0,0,0,0,0,0,0xbfb53fb5,0xbfb5bfb5,0x3fb5bfb5,0xbfb5bfb5,0x3fb5bfb5,0x3fb53fb5,0xbfb53fb5,0x3fb53fb5,
0xbfb53f80,0xbfb5bf80,0x3fb53f80,0x3fb5bf80,0x3fb50000,0xbfb54000,0xbfb50000,0x3fb54000,0,0,0,0,0,0,0,0,
0,0,0,0,0,0,0,0,0xbfed3f44,0x3f44bfed,0xbf44bfed,0xbfedbf44,0xbf443fed,0xbfed3f44,0x3fed3f44,0xbf44bfed,
0x3ffd3f80,0xbea0bf80,0xbffd3f80,0x3ea0bf80,0x3fe43ff3,0xbf68bf1e,0xbfe43ff3,0x3f68bf1e,0,0,0,0,0,0,0,0,
0,0,0,0,0,0,0,0,0x3ff93fff,0xbeefbe21,0x3eefbe21,0x3ff9bfff,0x3fda3fed,0xbf86bf44,0x3f86bf44,0x3fdabfed,
0x3f963f80,0xbfcf3f80,0xbf963f80,0x3fcf3f80,0xbff3bf1e,0xbf1ebff3,0x3ff3bf1e,0x3f1ebff3,0,0,0,0,0,0,0,0,
0,0,0,0,0,0,0,0,0x3ea03fe4,0xbffdbf68,0x3ffdbf68,0x3ea0bfe4,0xbffdbfb5,0x3ea0bfb5,0xbea0bfb5,0xbffd3fb5,
0xbea03f80,0xbffdbf80,0x3ea03f80,0x3ffdbf80,0x3f68bff3,0x3fe43f1e,0xbf68bff3,0xbfe43f1e,0,0,0,0,0,0,0,0,
0,0,0,0,0,0,0,0,0xbfda3fa6,0xbf86bfc3,0x3f86bfc3,0xbfdabfa6,0x3ff9bf44,0x3eef3fed,0xbeef3fed,0x3ff93f44,
0xbfcf3f80,0xbf963f80,0x3fcf3f80,0x3f963f80,0x3f1e3f1e,0xbff33ff3,0xbf1e3f1e,0x3ff33ff3,0,0,0,0,0,0,0,0,
0,0,0,0,0,0,0,0,0xbfcf3f1e,0x3f96bff3,0xbf96bff3,0xbfcfbf1e,0xbfcf4000,0xbf960000,0x3f960000,0xbfcfc000,
0x3ff33f80,0xbf1e3f80,0xbff33f80,0x3f1e3f80,0x3f963fcf,0xbfcfbf96,0xbf963fcf,0x3fcfbf96,0,0,0,0,0,0,0,0,
0,0,0,0,0,0,0,0,0x3fe43ffd,0xbf68bea0,0x3f68bea0,0x3fe4bffd,0x3f683fb5,0xbfe4bfb5,0x3fe4bfb5,0x3f68bfb5,
0x3f683f80,0xbfe4bf80,0xbf683f80,0x3fe4bf80,0xbffdbf96,0x3ea0bfcf,0x3ffdbf96,0xbea0bfcf,0,0,0,0,0,0,0,0,
0,0,0,0,0,0,0,0,0xbe213fda,0xbfffbf86,0x3fffbf86,0xbe21bfda,0xbfc3bfed,0x3fa6bf44,0xbfa6bf44,0xbfc33fed,
0xbf1e3f80,0xbff33f80,0x3f1e3f80,0x3ff33f80,0x3fcfbfcf,0x3f963f96,0xbfcfbfcf,0xbf963f96,0,0,0,0,0,0,0,0,
0,0,0,0,0,0,0,0,0xbff33f96,0xbf1ebfcf,0x3f1ebfcf,0xbff3bf96,0x3ff30000,0xbf1e4000,0x3f1e4000,0x3ff30000,
0xbfe43f80,0xbf68bf80,0x3fe43f80,0x3f68bf80,0xbea03f96,0xbffd3fcf,0x3ea03f96,0x3ffd3fcf,0,0,0,0,0,0,0,0,
0,0,0,0,0,0,0,0,0xbfa63eef,0x3fc3bff9,0xbfc3bff9,0xbfa6beef,0xbfff3fed,0xbe21bf44,0x3e21bf44,0xbfffbfed,
0x3fe43f80,0xbf68bf80,0xbfe43f80,0x3f68bf80,0x3ea03f96,0xbffdbfcf,0xbea03f96,0x3ffdbfcf,0,0,0,0,0,0,0,0,
0,0,0,0,0,0,0,0,0x3fc33ff9,0xbfa6beef,0x3fa6beef,0x3fc3bff9,0xbe213f44,0xbfffbfed,0x3fffbfed,0xbe21bf44,
0x3f1e3f80,0xbff33f80,0xbf1e3f80,0x3ff33f80,0xbfcfbfcf,0x3f96bf96,0x3fcfbfcf,0xbf96bf96,0,0,0,0,0,0,0,0,
0,0,0,0,0,0,0,0,0xbf1e3fcf,0xbff3bf96,0x3ff3bf96,0xbf1ebfcf,0xbf1ec000,0x3ff30000,0xbff30000,0xbf1e4000,
0xbf683f80,0xbfe4bf80,0x3f683f80,0x3fe4bf80,0x3ffdbf96,0x3ea03fcf,0xbffdbf96,0xbea03fcf,0,0,0,0,0,0,0,0,
0,0,0,0,0,0,0,0,0xbfff3f86,0xbe21bfda,0x3e21bfda,0xbfffbf86,0x3fa63f44,0xbfc33fed,0x3fc33fed,0x3fa6bf44,
0xbff33f80,0xbf1e3f80,0x3ff33f80,0x3f1e3f80,0xbf963fcf,0xbfcf3f96,0x3f963fcf,0x3fcf3f96,0,0,0,0,0,0,0,0,
0,0,0,0,0,0,0,0,0xbf683ea0,0x3fe4bffd,0xbfe4bffd,0xbf68bea0,0xbfe43fb5,0x3f68bfb5,0xbf68bfb5,0xbfe4bfb5,
0x3fcf3f80,0xbf963f80,0xbfcf3f80,0x3f963f80,0xbf1e3f1e,0xbff3bff3,0x3f1e3f1e,0x3ff3bff3,0,0,0,0,0,0,0,0,
0,0,0,0,0,0,0,0,0x3f963ff3,0xbfcfbf1e,0x3fcfbf1e,0x3f96bff3,0xbf960000,0xbfcfc000,0x3fcfc000,0xbf960000,
0x3ea03f80,0xbffdbf80,0xbea03f80,0x3ffdbf80,0xbf68bff3,0x3fe4bf1e,0x3f68bff3,0xbfe4bf1e,0,0,0,0,0,0,0,0,
0,0,0,0,0,0,0,0,0xbf863fc3,0xbfdabfa6,0x3fdabfa6,0xbf86bfc3,0x3eefbfed,0x3ff93f44,0xbff93f44,0x3eef3fed,
0xbf963f80,0xbfcf3f80,0x3f963f80,0x3fcf3f80,0x3ff3bf1e,0xbf1e3ff3,0xbff3bf1e,0x3f1e3ff3,0,0,0,0,0,0,0,0,
0,0,0,0,0,0,0,0,0xbffd3f68,0x3ea0bfe4,0xbea0bfe4,0xbffdbf68,0x3ea03fb5,0xbffd3fb5,0x3ffd3fb5,0x3ea0bfb5,
0xbffd3f80,0xbea0bf80,0x3ffd3f80,0x3ea0bf80,0xbfe43ff3,0xbf683f1e,0x3fe43ff3,0x3f683f1e,0,0,0,0,0,0,0,0,
0,0,0,0,0,0,0,0,0xbeef3e21,0x3ff9bfff,0xbff9bfff,0xbeefbe21,0xbf863f44,0x3fdabfed,0xbfdabfed,0xbf86bf44,
0x3f803f80,0,0xbf7b3f7b,0x3e48be48,0x3f803f80,0,0xbf7b3f7b,0x3e48be48,0x3f803f80,0,0xbf7b3f7b,0x3e48be48,0x3f803f80,0,0xbf7b3f7b,0x3e48be48,
0,0x3f803f80,0xbe483e48,0xbf7b3f7b,0,0x3f803f80,0xbe483e48,0xbf7b3f7b,0,0x3f803f80,0xbe483e48,0xbf7b3f7b,0,0x3f803f80,0xbe483e48,0xbf7b3f7b,
0x3f2c3f80,0xbf3ebd49,0xbf043f78,0x3f5cbe79,0xbf3ebd49,0xbf2cbf80,0x3f5cbe79,0x3f04bf78,0xbf2cbf80,0x3f3e3d49,0x3f04bf78,0xbf5c3e79,0x3f3e3d49,0x3f2c3f80,0xbf5c3e79,0xbf043f78,
0x3f3e3d49,0x3f2c3f80,0xbf5c3e79,0xbf043f78,0x3f2c3f80,0xbf3ebd49,0xbf043f78,0x3f5cbe79,0xbf3ebd49,0xbf2cbf80,0x3f5cbe79,0x3f04bf78,0xbf2cbf80,0x3f3e3d49,0x3f04bf78,0xbf5c3e79,
0xbdc93f7f,0xbf7fbdc9,0x3e953f75,0x3f75be95,0x3dc9bf7f,0x3f7f3dc9,0xbe95bf75,0xbf753e95,0xbdc93f7f,0xbf7fbdc9,0x3e953f75,0x3f75be95,0x3dc9bf7f,0x3f7f3dc9,0xbe95bf75,0xbf753e95,
0x3f7f3dc9,0xbdc93f7f,0xbf753e95,0x3e953f75,0xbf7fbdc9,0x3dc9bf7f,0x3f75be95,0xbe95bf75,0x3f7f3dc9,0xbdc93f7f,0xbf753e95,0x3e953f75,0xbf7fbdc9,0x3dc9bf7f,0x3f75be95,0xbe95bf75,
0xbf4e3f7d,0xbf18be16,0x3f673f71,0x3edbbeac,0x3f183e16,0xbf4e3f7d,0xbedb3eac,0x3f673f71,0x3f4ebf7d,0x3f183e16,0xbf67bf71,0xbedb3eac,0xbf18be16,0x3f4ebf7d,0x3edbbeac,0xbf67bf71,
0x3f183e16,0xbf4e3f7d,0xbedb3eac,0x3f673f71,0x3f4ebf7d,0x3f183e16,0xbf67bf71,0xbedb3eac,0xbf18be16,0x3f4ebf7d,0x3edbbeac,0xbf67bf71,0xbf4e3f7d,0xbf18be16,0x3f673f71,0x3edbbeac,
0x3f7c3f80,0xbe2abc21,0xbf6f3f7b,0x3eb6be52,0x3f633f73,0xbeedbea3,0xbf473f5e,0x3f20beff,0x3f333f4e,0xbf37bf18,0xbf0c3f2c,0x3f56bf3e,0x3ee43f14,0xbf65bf51,0xbe863ed2,0x3f77bf6a,
0x3e2a3c21,0x3f7c3f80,0xbeb63e52,0xbf6f3f7b,0x3eed3ea3,0x3f633f73,0xbf203eff,0xbf473f5e,0x3f373f18,0x3f333f4e,0xbf563f3e,0xbf0c3f2c,0x3f653f51,0x3ee43f14,0xbf773f6a,0xbe863ed2,
0x3f0a3f80,0xbf58bd71,0xbebb3f78,0x3f6ebe81,0xbf78bebb,0xbe81bf6e,0x3f80bf0a,0x3d71bf58,0x3d71bf46,0x3f803f22,0xbe81bf22,0xbf783f46,0x3f6e3f58,0xbebb3f0a,0xbf583f6e,0x3f0a3ebb,
0x3f583d71,0x3f0a3f80,0xbf6e3e81,0xbebb3f78,0x3e813f6e,0xbf78bebb,0xbd713f58,0x3f80bf0a,0xbf80bf22,0x3d71bf46,0x3f78bf46,0xbe81bf22,0x3ebbbf0a,0x3f6e3f58,0xbf0abebb,0xbf583f6e,
0xbe863f7f,0xbf77bddd,0x3ee43f74,0x3f65be99,0x3f0cbf6a,0x3f563ed2,0xbf33bf51,0xbf373f14,0xbf473f3e,0xbf20bf2c,0x3f633f18,0x3eedbf4e,0x3f6fbeff,0x3eb63f5e,0xbf7cbea3,0xbe2a3f73,
0x3f773ddd,0xbe863f7f,0xbf653e99,0x3ee43f74,0xbf56bed2,0x3f0cbf6a,0x3f37bf14,0xbf33bf51,0x3f203f2c,0xbf473f3e,0xbeed3f4e,0x3f633f18,0xbeb6bf5e,0x3f6fbeff,0x3e2abf73,0xbf7cbea3,
0xbf643f7d,0xbee8be20,0x3f763f70,0x3e8bbeb1,0x3e203ee8,0xbf7d3f64,0x3d213f1e,0x3f803f49,0x3f7dbf35,0xbe203f35,0xbf70bf0e,0x3eb13f55,0x3ee8bf64,0x3f64bee8,0xbf1ebf76,0xbf49be8b,
0x3ee83e20,0xbf643f7d,0xbe8b3eb1,0x3f763f70,0x3f7dbf64,0x3e203ee8,0xbf80bf49,0x3d213f1e,0x3e20bf35,0x3f7dbf35,0xbeb1bf55,0xbf70bf0e,0xbf643ee8,0x3ee8bf64,0x3f493e8b,0xbf1ebf76,
0x3f723f80,0xbea8bca1,0xbf5d3f7a,0x3f01be5b,0x3f123f4c,0xbf52bf1b,0xbecd3f2a,0x3f6bbf3f,0xbca13e95,0xbf80bf75,0x3e5b3dc9,0x3f7abf7f,0xbf1bbea8,0xbf4cbf72,0x3f3fbf01,0x3f2abf5d,
0x3ea83ca1,0x3f723f80,0xbf013e5b,0xbf5d3f7a,0x3f523f1b,0x3f123f4c,0xbf6b3f3f,0xbecd3f2a,0x3f803f75,0xbca13e95,0xbf7a3f7f,0x3e5b3dc9,0x3f4c3f72,0xbf1bbea8,0xbf2a3f5d,0x3f3fbf01,
0x3ec93f7f,0xbf6cbd8d,0xbe523f77,0x3f7bbe86,0xbf7abf24,0x3e65bf44,0x3f6abf47,0xbed2bf20,0x3f41be79,0x3f283f78,0xbf5ebd49,0xbeff3f80,0x3db53f6d,0xbf7fbebf,0x3ddd3f56,0x3f7fbf0c,
0x3f6c3d8d,0x3ec93f7f,0xbf7b3e86,0xbe523f77,0xbe653f44,0xbf7abf24,0x3ed23f20,0x3f6abf47,0xbf28bf78,0x3f41be79,0x3effbf80,0xbf5ebd49,0x3f7f3ebf,0x3db53f6d,0xbf7f3f0c,0x3ddd3f56,
0xbed63f7e,0xbf68bdf1,0x3f163f73,0x3f4fbe9e,0x3f5fbf3c,0x3efa3f2e,0xbf73bf16,0xbe9e3f4f,0xbf7e3e48,0x3df1bf7b,0x3f730000,0xbe9ebf80,0x3f3c3ed6,0xbf2e3f68,0xbf163f16,0x3f4f3f4f,
0x3f683df1,0xbed63f7e,0xbf4f3e9e,0x3f163f73,0xbefabf2e,0x3f5fbf3c,0x3e9ebf4f,0xbf73bf16,0xbdf13f7b,0xbf7e3e48,0x3e9e3f80,0x3f730000,0x3f2ebf68,0x3f3c3ed6,0xbf4fbf4f,0xbf163f16,
0xbf743f7c,0xbe99be2a,0x3f7f3f6f,0x3dddbeb6,0xbea33f37,0xbf733f33,0x3eff3f56,0x3f5e3f0c,0x3f14be16,0xbf513f7d,0xbed23d49,0x3f6a3f80,0x3f80bf63,0xbc213eed,0xbf7bbf47,0x3e523f20,
0x3e993e2a,0xbf743f7c,0xbddd3eb6,0x3f7f3f6f,0x3f73bf33,0xbea33f37,0xbf5ebf0c,0x3eff3f56,0x3f51bf7d,0x3f14be16,0xbf6abf80,0xbed23d49,0x3c21beed,0x3f80bf63,0xbe52bf20,0xbf7bbf47,
0x3f613f80,0xbef6bcf1,0xbf443f7a,0x3f24be65,0x3e023f10,0xbf7ebf53,0x3d8d3ec9,0x3f7fbf6c,0xbf3abeac,0xbf30bf71,0x3f59bf04,0x3f08bf5c,0xbf7cbf76,0x3e3ebe90,0x3f6dbf7f,0xbebfbdb5,
0x3ef63cf1,0x3f613f80,0xbf243e65,0xbf443f7a,0x3f7e3f53,0x3e023f10,0xbf7f3f6c,0x3d8d3ec9,0x3f303f71,0xbf3abeac,0xbf083f5c,0x3f59bf04,0xbe3e3e90,0xbf7cbf76,0x3ebf3db5,0x3f6dbf7f,
0x3e6f3f7f,0xbf79bda1,0xbd213f76,0x3f80be8b,0xbf43bf5a,0x3f26bf06,0x3f1ebf70,0xbf49beb1,0x3f7f3ec4,0xbda13f6d,0xbf763f0e,0x3e8b3f55,0xbf5a3e6f,0xbf06bf79,0x3f703d21,0x3eb1bf80,
0x3f793da1,0x3e6f3f7f,0xbf803e8b,0xbd213f76,0xbf263f06,0xbf43bf5a,0x3f493eb1,0x3f1ebf70,0x3da1bf6d,0x3f7f3ec4,0xbe8bbf55,0xbf763f0e,0x3f063f79,0xbf5a3e6f,0xbeb13f80,0x3f703d21,
0xbf103f7e,0xbf53be02,0x3f373f73,0x3f33bea3,0x3f80bef6,0x3cf13f61,0xbf7cbe99,0x3e2a3f74,0xbf1dbedb,0x3f4bbf67,0x3ee4bf18,0xbf65bf4e,0xbe903f7c,0xbf763e3e,0x3eed3f80,0x3f63bc21,
0x3f533e02,0xbf103f7e,0xbf333ea3,0x3f373f73,0xbcf1bf61,0x3f80bef6,0xbe2abf74,0xbf7cbe99,0xbf4b3f67,0xbf1dbedb,0x3f653f4e,0x3ee4bf18,0x3f76be3e,0xbe903f7c,0xbf633c21,0x3eed3f80,
0xbf7e3f7c,0xbe0cbe34,0x3f803f6e,0xbd71bebb,0xbf393f66,0xbf313edf,0x3f583f78,0x3f0a3e81,0xbe343ef1,0xbf7c3f62,0x3ebb3f22,0x3f6e3f46,0x3edfbe0c,0xbf663f7e,0xbe813d71,0x3f783f80,
0x3e0c3e34,0xbf7e3f7c,0x3d713ebb,0x3f803f6e,0x3f31bedf,0xbf393f66,0xbf0abe81,0x3f583f78,0x3f7cbf62,0xbe343ef1,0xbf6ebf46,0x3ebb3f22,0x3f66bf7e,0x3edfbe0c,0xbf78bf80,0xbe813d71,
0x3f493f80,0xbf1ebd21,0xbf263f79,0x3f43be6f,0xbeb13e8b,0xbf70bf76,0x3f063da1,0x3f5abf7f,0xbf80bf55,0x3d21bf0e,0x3f79bf6d,0xbe6fbec4,0xbe8bbf49,0x3f763f1e,0x3da1bf26,0xbf7f3f43,
0x3f1e3d21,0x3f493f80,0xbf433e6f,0xbf263f79,0x3f703f76,0xbeb13e8b,0xbf5a3f7f,0x3f063da1,0xbd213f0e,0xbf80bf55,0x3e6f3ec4,0x3f79bf6d,0xbf76bf1e,0xbe8bbf49,0x3f7fbf43,0x3da1bf26,
0x3d8d3f7f,0xbf7fbdb5,0x3e023f76,0x3f7ebe90,0xbebfbf7a,0x3f6dbe65,0x3e3ebf80,0xbf7cbcf1,0x3f243f5c,0xbf443f04,0xbef63f71,0x3f613eac,0xbf59bf28,0x3f08bf41,0x3f3abf4b,0xbf30bf1d,
0x3f7f3db5,0x3d8d3f7f,0xbf7e3e90,0x3e023f76,0xbf6d3e65,0xbebfbf7a,0x3f7c3cf1,0x3e3ebf80,0x3f44bf04,0x3f243f5c,0xbf61beac,0xbef63f71,0xbf083f41,0xbf59bf28,0x3f303f1d,0x3f3abf4b,
0xbf313f7e,0xbf39be0c,0x3f523f72,0x3f12bea8,0x3f66be34,0xbedf3f7c,0xbf4c3ca1,0x3f1b3f80,0x3e0cbf62,0x3f7ebef1,0xbea8bf75,0xbf72be95,0xbf7c3f39,0xbe34bf31,0x3f803f12,0xbca1bf52,
0x3f393e0c,0xbf313f7e,0xbf123ea8,0x3f523f72,0x3edfbf7c,0x3f66be34,0xbf1bbf80,0xbf4c3ca1,0xbf7e3ef1,0x3e0cbf62,0x3f723e95,0xbea8bf75,0x3e343f31,0xbf7c3f39,0x3ca13f52,0x3f803f12,
0xbf803f7c,0x3cf1be3e,0x3f7a3f6d,0xbe65bebf,0xbf763f7e,0xbe903e02,0x3f7f3f7f,0x3db5bd8d,0xbf533f67,0xbf103edb,0x3f6c3f78,0x3ec93e79,0xbf1d3f3a,0xbf4b3f30,0x3f413f59,0x3f283f08,
0xbcf13e3e,0xbf803f7c,0x3e653ebf,0x3f7a3f6d,0x3e90be02,0xbf763f7e,0xbdb53d8d,0x3f7f3f7f,0x3f10bedb,0xbf533f67,0xbec9be79,0x3f6c3f78,0x3f4bbf30,0xbf1d3f3a,0xbf28bf08,0x3f413f59,
0x3f803f80,0,0xbf6d3f6d,0x3ec4bec4,0x3f803f80,0,0xbf6d3f6d,0x3ec4bec4,0x3f803f80,0,0xbf6d3f6d,0x3ec4bec4,0x3f803f80,0,0xbf6d3f6d,0x3ec4bec4,
0,0x3f803f80,0xbec43ec4,0xbf6d3f6d,0,0x3f803f80,0xbec43ec4,0xbf6d3f6d,0,0x3f803f80,0xbec43ec4,0xbf6d3f6d,0,0x3f803f80,0xbec43ec4,0xbf6d3f6d,
0x3f223f7f,0xbf46bdc9,0xbe953f62,0x3f75bef1,0xbf46bdc9,0xbf22bf7f,0x3f75bef1,0x3e95bf62,0xbf22bf7f,0x3f463dc9,0x3e95bf62,0xbf753ef1,0x3f463dc9,0x3f223f7f,0xbf753ef1,0xbe953f62,
0x3f463dc9,0x3f223f7f,0xbf753ef1,0xbe953f62,0x3f223f7f,0xbf46bdc9,0xbe953f62,0x3f75bef1,0xbf46bdc9,0xbf22bf7f,0x3f75bef1,0x3e95bf62,0xbf22bf7f,0x3f463dc9,0x3e95bf62,0xbf753ef1,
0xbe483f7b,0xbf7bbe48,0x3f0e3f55,0x3f55bf0e,0x3e48bf7b,0x3f7b3e48,0xbf0ebf55,0xbf553f0e,0xbe483f7b,0xbf7bbe48,0x3f0e3f55,0x3f55bf0e,0x3e48bf7b,0x3f7b3e48,0xbf0ebf55,0xbf553f0e,
0x3f7b3e48,0xbe483f7b,0xbf553f0e,0x3f0e3f55,0xbf7bbe48,0x3e48bf7b,0x3f55bf0e,0xbf0ebf55,0x3f7b3e48,0xbe483f7b,0xbf553f0e,0x3f0e3f55,0xbf7bbe48,0x3e48bf7b,0x3f55bf0e,0xbf0ebf55,
0xbf623f75,0xbef1be95,0x3f7f3f46,0x3dc9bf22,0x3ef13e95,0xbf623f75,0xbdc93f22,0x3f7f3f46,0x3f62bf75,0x3ef13e95,0xbf7fbf46,0xbdc93f22,0xbef1be95,0x3f62bf75,0x3dc9bf22,0xbf7fbf46,
0x3ef13e95,0xbf623f75,0xbdc93f22,0x3f7f3f46,0x3f62bf75,0x3ef13e95,0xbf7fbf46,0xbdc93f22,0xbef1be95,0x3f62bf75,0x3dc9bf22,0xbf7fbf46,0xbf623f75,0xbef1be95,0x3f7f3f46,0x3dc9bf22,
0x3f7c3f80,0xbe34bca1,0xbf583f6b,0x3f0abecd,0x3f623f72,0xbef1bea8,0xbf223f3f,0x3f46bf2a,0x3f313f4c,0xbf39bf1b,0xbebb3f01,0x3f6ebf5d,0x3edf3f12,0xbf66bf52,0xbd713e5b,0x3f80bf7a,
0x3e343ca1,0x3f7c3f80,0xbf0a3ecd,0xbf583f6b,0x3ef13ea8,0x3f623f72,0xbf463f2a,0xbf223f3f,0x3f393f1b,0x3f313f4c,0xbf6e3f5d,0xbebb3f01,0x3f663f52,0x3edf3f12,0xbf803f7a,0xbd713e5b,
0x3efa3f7e,0xbf5fbdf1,0xbdf13f5f,0x3f7ebefa,0xbf7bbed6,0xbe48bf68,0x3f7bbf3c,0xbe48bf2e,0x3df1bf3c,0x3f7e3f2e,0xbefabed6,0xbf5f3f68,0x3f683f5f,0xbed63efa,0xbf2e3f7e,0x3f3c3df1,
0x3f5f3df1,0x3efa3f7e,0xbf7e3efa,0xbdf13f5f,0x3e483f68,0xbf7bbed6,0x3e483f2e,0x3f7bbf3c,0xbf7ebf2e,0x3df1bf3c,0x3f5fbf68,0xbefabed6,0x3ed6befa,0x3f683f5f,0xbf3cbdf1,0xbf2e3f7e,
0xbebb3f7a,0xbf6ebe5b,0x3f313f52,0x3f39bf12,0x3f22bf5d,0x3f463f01,0xbf62bf1b,0xbef13f4c,0xbf583f2a,0xbf0abf3f,0x3f7c3ea8,0x3e34bf72,0x3f78becd,0x3e813f6b,0xbf7ebca1,0x3e0c3f80,
0x3f6e3e5b,0xbebb3f7a,0xbf393f12,0x3f313f52,0xbf46bf01,0x3f22bf5d,0x3ef1bf4c,0xbf62bf1b,0x3f0a3f3f,0xbf583f2a,0xbe343f72,0x3f7c3ea8,0xbe81bf6b,0x3f78becd,0xbe0cbf80,0xbf7ebca1,
0xbf733f73,0xbe9ebe9e,0x3f7f3f43,0xbda1bf26,0x3f16,0xbf803f4f,0x3ec43f5a,0x3f6d3f06,0x3f73bf16,0xbe9e3f4f,0xbf43be6f,0x3f263f79,0x3f16bf73,0x3f4fbe9e,0xbf5abf7f,0xbf063da1,
0x3e9e3e9e,0xbf733f73,0x3da13f26,0x3f7f3f43,0x3f80bf4f,0x3f16,0xbf6dbf06,0x3ec43f5a,0x3e9ebf4f,0x3f73bf16,0xbf26bf79,0xbf43be6f,0xbf4f3e9e,0x3f16bf73,0x3f06bda1,0xbf5abf7f,
0x3f703f80,0xbeb1bd21,0xbf3c3f68,0x3f2ebed6,0x3f0e3f49,0xbf55bf1e,0xbe483efa,0x3f7bbf5f,0xbd213e8b,0xbf80bf76,0x3ed6bdf1,0x3f68bf7e,0xbf1ebeb1,0xbf49bf70,0x3f5fbf2e,0x3efabf3c,
0x3eb13d21,0x3f703f80,0xbf2e3ed6,0xbf3c3f68,0x3f553f1e,0x3f0e3f49,0xbf7b3f5f,0xbe483efa,0x3f803f76,0xbd213e8b,0xbf683f7e,0x3ed6bdf1,0x3f493f70,0xbf1ebeb1,0xbefa3f3c,0x3f5fbf2e,
0x3ea83f7e,0xbf72be0c,0x3d713f5d,0x3f80bf01,0xbf75bf31,0x3e95bf39,0x3f46bf6b,0xbf22becd,0x3f4cbe34,0x3f1b3f7c,0xbf783e5b,0xbe813f7a,0x3ca13f66,0xbf80bedf,0x3ebb3f2a,0x3f6ebf3f,
0x3f723e0c,0x3ea83f7e,0xbf803f01,0x3d713f5d,0xbe953f39,0xbf75bf31,0x3f223ecd,0x3f46bf6b,0xbf1bbf7c,0x3f4cbe34,0x3e81bf7a,0xbf783e5b,0x3f803edf,0x3ca13f66,0xbf6e3f3f,0x3ebb3f2a,
0xbf063f79,0xbf5abe6f,0x3f4f3f4f,0x3f16bf16,0x3f6dbf26,0x3ec43f43,0xbf80be9e,0x3f73,0xbf793da1,0x3e6fbf7f,0x3f4fbe9e,0xbf16bf73,0x3f263f06,0xbf433f5a,0xbe9e3f4f,0x3f733f16,
0x3f5a3e6f,0xbf063f79,0xbf163f16,0x3f4f3f4f,0xbec4bf43,0x3f6dbf26,0xbf73,0xbf80be9e,0xbe6f3f7f,0xbf793da1,0x3f163f73,0x3f4fbe9e,0x3f43bf5a,0x3f263f06,0xbf73bf16,0xbe9e3f4f,
0xbf7e3f72,0xbe0cbea8,0x3f783f3f,0xbe81bf2a,0xbef13f52,0xbf623f12,0x3f463f7a,0x3f223e5b,0x3edf3ca1,0xbf663f80,0xbd713ecd,0x3f803f6b,0x3f7cbf4c,0xbe343f1b,0xbf58bf01,0x3f0a3f5d,
0x3e0c3ea8,0xbf7e3f72,0x3e813f2a,0x3f783f3f,0x3f62bf12,0xbef13f52,0xbf22be5b,0x3f463f7a,0x3f66bf80,0x3edf3ca1,0xbf80bf6b,0xbd713ecd,0x3e34bf1b,0x3f7cbf4c,0xbf0abf5d,0xbf58bf01,
0x3f5d3f80,0xbf01bd71,0xbf1b3f66,0x3f4cbedf,0x3dc93f0a,0xbf7fbf58,0x3e953e34,0x3f75bf7c,0xbf3fbebb,0xbf2abf6e,0x3f72bf31,0x3ea8bf39,0xbf7abf78,0x3e5bbe81,0x3f52bf7e,0xbf123e0c,
0x3f013d71,0x3f5d3f80,0xbf4c3edf,0xbf1b3f66,0x3f7f3f58,0x3dc93f0a,0xbf753f7c,0x3e953e34,0x3f2a3f6e,0xbf3fbebb,0xbea83f39,0x3f72bf31,0xbe5b3e81,0xbf7abf78,0x3f12be0c,0x3f52bf7e,
0x3e203f7d,0xbf7dbe20,0x3e6f3f5a,0x3f79bf06,0xbf35bf64,0x3f35bee8,0x3ec4bf7f,0xbf6dbda1,0x3f7d3ee8,0xbe203f64,0xbf5a3f43,0x3f063f26,0xbf643e20,0xbee8bf7d,0x3f7fbe6f,0x3da1bf79,
0x3f7d3e20,0x3e203f7d,0xbf793f06,0x3e6f3f5a,0xbf353ee8,0xbf35bf64,0x3f6d3da1,0x3ec4bf7f,0x3e20bf64,0x3f7d3ee8,0xbf06bf26,0xbf5a3f43,0x3ee83f7d,0xbf643e20,0xbda13f79,0x3f7fbe6f,
0xbf2a3f78,0xbf3fbe81,0x3f663f4c,0x3edfbf1b,0x3f7fbebb,0xbdc93f6e,0xbf623ca1,0x3ef13f80,0xbf01bf0a,0x3f5dbf58,0x3e0cbf52,0xbf7ebf12,0xbecd3f80,0xbf6b3d71,0x3f393f72,0x3f31bea8,
0x3f3f3e81,0xbf2a3f78,0xbedf3f1b,0x3f663f4c,0x3dc9bf6e,0x3f7fbebb,0xbef1bf80,0xbf623ca1,0xbf5d3f58,0xbf01bf0a,0x3f7e3f12,0x3e0cbf52,0x3f6bbd71,0xbecd3f80,0xbf313ea8,0x3f393f72,
0xbf803f70,0x3d21beb1,0x3f683f3c,0xbed6bf2e,0xbf553f76,0xbf0e3e8b,0x3f7b3f7e,0x3e48bdf1,0xbeb13f1e,0xbf703f49,0x3f2e3f5f,0x3f3c3efa,0x3e8b3d21,0xbf763f80,0x3df13ed6,0x3f7e3f68,
0xbd213eb1,0xbf803f70,0x3ed63f2e,0x3f683f3c,0x3f0ebe8b,0xbf553f76,0xbe483df1,0x3f7b3f7e,0x3f70bf49,0xbeb13f1e,0xbf3cbefa,0x3f2e3f5f,0x3f76bf80,0x3e8b3d21,0xbf7ebf68,0x3df13ed6,
0x3f433f7f,0xbf26bda1,0xbee83f64,0x3f64bee8,0xbec43e6f,0xbf6dbf79,0x3f35be20,0x3f35bf7d,0xbf7fbf5a,0x3da1bf06,0x3f64bf7d,0xbee8be20,0xbe6fbf43,0x3f793f26,0xbe20bee8,0xbf7d3f64,
0x3f263da1,0x3f433f7f,0xbf643ee8,0xbee83f64,0x3f6d3f79,0xbec43e6f,0xbf353f7d,0x3f35be20,0xbda13f06,0xbf7fbf5a,0x3ee83e20,0x3f64bf7d,0xbf79bf26,0xbe6fbf43,0x3f7dbf64,0xbe20bee8,
0xbca13f7c,0xbf80be34,0x3ecd3f58,0x3f6bbf0a,0xbe95bf7e,0x3f75be0c,0xbdc9bf78,0xbf7f3e81,0x3f123f66,0xbf523edf,0xbe5b3f80,0x3f7a3d71,0xbf4cbf39,0x3f1bbf31,0x3f01bf6e,0xbf5dbebb,
0x3f803e34,0xbca13f7c,0xbf6b3f0a,0x3ecd3f58,0xbf753e0c,0xbe95bf7e,0x3f7fbe81,0xbdc9bf78,0x3f52bedf,0x3f123f66,0xbf7abd71,0xbe5b3f80,0xbf1b3f31,0xbf4cbf39,0x3f5d3ebb,0x3f01bf6e,
0xbf493f76,0xbf1ebe8b,0x3f763f49,0x3e8bbf1e,0x3f55bd21,0xbf0e3f80,0xbf0e3eb1,0x3f553f70,0x3e8bbf70,0x3f76beb1,0xbf1ebf80,0xbf493d21,0xbf803f1e,0xbd21bf49,0x3f703e8b,0xbeb1bf76,
0x3f1e3e8b,0xbf493f76,0xbe8b3f1e,0x3f763f49,0x3f0ebf80,0x3f55bd21,0xbf55bf70,0xbf0e3eb1,0xbf763eb1,0x3e8bbf70,0x3f49bd21,0xbf1ebf80,0x3d213f49,0xbf803f1e,0x3eb13f76,0x3f703e8b,
0xbf7a3f6e,0x3e5bbebb,0x3f523f39,0xbf12bf31,0xbf7f3f80,0xbdc9bd71,0x3f753f66,0xbe95bedf,0xbf6b3f78,0xbecd3e81,0x3f803f7e,0x3ca1be0c,0xbf3f3f58,0xbf2a3f0a,0x3f723f7c,0x3ea83e34,
0xbe5b3ebb,0xbf7a3f6e,0x3f123f31,0x3f523f39,0x3dc93d71,0xbf7f3f80,0x3e953edf,0x3f753f66,0x3ecdbe81,0xbf6b3f78,0xbca13e0c,0x3f803f7e,0x3f2abf0a,0xbf3f3f58,0xbea8be34,0x3f723f7c,
0x3f803f80,0,0xbf553f55,0x3f0ebf0e,0x3f803f80,0,0xbf553f55,0x3f0ebf0e,0x3f803f80,0,0xbf553f55,0x3f0ebf0e,0x3f803f80,0,0xbf553f55,0x3f0ebf0e,
0,0x3f803f80,0xbf0e3f0e,0xbf553f55,0,0x3f803f80,0xbf0e3f0e,0xbf553f55,0,0x3f803f80,0xbf0e3f0e,0xbf553f55,0,0x3f803f80,0xbf0e3f0e,0xbf553f55,
0x3f183f7d,0xbf4ebe16,0xbd493f3e,0x3f80bf2c,0xbf4ebe16,0xbf18bf7d,0x3f80bf2c,0x3d49bf3e,0xbf18bf7d,0x3f4e3e16,0x3d49bf3e,0xbf803f2c,0x3f4e3e16,0x3f183f7d,0xbf803f2c,0xbd493f3e,
0x3f4e3e16,0x3f183f7d,0xbf803f2c,0xbd493f3e,0x3f183f7d,0xbf4ebe16,0xbd493f3e,0x3f80bf2c,0xbf4ebe16,0xbf18bf7d,0x3f80bf2c,0x3d49bf3e,0xbf18bf7d,0x3f4e3e16,0x3d49bf3e,0xbf803f2c,
0xbe953f75,0xbf75be95,0x3f463f22,0x3f22bf46,0x3e95bf75,0x3f753e95,0xbf46bf22,0xbf223f46,0xbe953f75,0xbf75be95,0x3f463f22,0x3f22bf46,0x3e95bf75,0x3f753e95,0xbf46bf22,0xbf223f46,
0x3f753e95,0xbe953f75,0xbf223f46,0x3f463f22,0xbf75be95,0x3e95bf75,0x3f22bf46,0xbf46bf22,0x3f753e95,0xbe953f75,0xbf223f46,0x3f463f22,0xbf75be95,0x3e95bf75,0x3f22bf46,0xbf46bf22,
0xbf713f67,0xbeacbedb,0x3f783f04,0xbe79bf5c,0x3eac3edb,0xbf713f67,0x3e793f5c,0x3f783f04,0x3f71bf67,0x3eac3edb,0xbf78bf04,0x3e793f5c,0xbeacbedb,0x3f71bf67,0xbe79bf5c,0xbf78bf04,
0x3eac3edb,0xbf713f67,0x3e793f5c,0x3f783f04,0x3f71bf67,0x3eac3edb,0xbf78bf04,0x3e793f5c,0xbeacbedb,0x3f71bf67,0xbe79bf5c,0xbf78bf04,0xbf713f67,0xbeacbedb,0x3f783f04,0xbe79bf5c,
0x3f7c3f80,0xbe3ebcf1,0xbf373f51,0x3f33bf14,0x3f613f71,0xbef6beac,0xbeed3f18,0x3f63bf4e,0x3f303f4b,0xbf3abf1d,0xbe2a3ea3,0x3f7cbf73,0x3edb3f10,0xbf67bf53,0x3e163c21,0x3f7dbf80,
0x3e3e3cf1,0x3f7c3f80,0xbf333f14,0xbf373f51,0x3ef63eac,0x3f613f71,0xbf633f4e,0xbeed3f18,0x3f3a3f1d,0x3f303f4b,0xbf7c3f73,0xbe2a3ea3,0x3f673f53,0x3edb3f10,0xbf7d3f80,0x3e163c21,
0x3edf3f7c,0xbf66be34,0x3e0c3f39,0x3f7ebf31,0xbf7ebef1,0xbe0cbf62,0x3f66bf62,0xbedfbef1,0x3e34bf31,0x3f7c3f39,0xbf31be34,0xbf393f7c,0x3f623f66,0xbef13edf,0xbef13f7e,0x3f62be0c,
0x3f663e34,0x3edf3f7c,0xbf7e3f31,0x3e0c3f39,0x3e0c3f62,0xbf7ebef1,0x3edf3ef1,0x3f66bf62,0xbf7cbf39,0x3e34bf31,0x3f39bf7c,0xbf31be34,0x3ef1bedf,0x3f623f66,0xbf623e0c,0xbef13f7e,
0xbeed3f73,0xbf63bea3,0x3f613f1d,0x3ef6bf4b,0x3f37bf4e,0x3f333f18,0xbf7cbeac,0xbe3e3f71,0xbf653f14,0xbee4bf51,0x3f7e3cf1,0xbe02bf80,0x3f7dbe99,0x3e163f74,0xbf673e90,0x3edb3f76,
0x3f633ea3,0xbeed3f73,0xbef63f4b,0x3f613f1d,0xbf33bf18,0x3f37bf4e,0x3e3ebf71,0xbf7cbeac,0x3ee43f51,0xbf653f14,0x3e023f80,0x3f7e3cf1,0xbe16bf74,0x3f7dbe99,0xbedbbf76,0xbf673e90,
0xbf7d3f64,0xbe20bee8,0x3f683efa,0xbed6bf5f,0xbe203f35,0xbf7d3f35,0x3f2e3f7b,0x3f3c3e48,0x3f64bee8,0xbee83f64,0xbefa3df1,0x3f5f3f7e,0x3f35bf7d,0x3f35be20,0xbf7bbf68,0xbe483ed6,
0x3e203ee8,0xbf7d3f64,0x3ed63f5f,0x3f683efa,0x3f7dbf35,0xbe203f35,0xbf3cbe48,0x3f2e3f7b,0x3ee8bf64,0x3f64bee8,0xbf5fbf7e,0xbefa3df1,0xbf353e20,0x3f35bf7d,0x3e48bed6,0xbf7bbf68,
0x3f6e3f80,0xbebbbd71,0xbf123f4c,0x3f52bf1b,0x3f0a3f46,0xbf58bf22,0x3ca13e95,0x3f80bf75,0xbd713e81,0xbf80bf78,0x3f1bbea8,0x3f4cbf72,0xbf22bebb,0xbf46bf6e,0x3f75bf52,0x3e95bf12,
0x3ebb3d71,0x3f6e3f80,0xbf523f1b,0xbf123f4c,0x3f583f22,0x3f0a3f46,0xbf803f75,0x3ca13e95,0x3f803f78,0xbd713e81,0xbf4c3f72,0x3f1bbea8,0x3f463f6e,0xbf22bebb,0xbe953f12,0x3f75bf52,
0x3e863f7b,0xbf77be52,0x3ea33f33,0x3f73bf37,0xbf6fbf3e,0x3eb6bf2c,0x3f14bf7d,0xbf51be16,0x3f56bddd,0x3f0c3f7f,0xbf803eed,0x3c213f63,0xbd493f5e,0xbf80beff,0x3f183ee4,0x3f4ebf65,
0x3f773e52,0x3e863f7b,0xbf733f37,0x3ea33f33,0xbeb63f2c,0xbf6fbf3e,0x3f513e16,0x3f14bf7d,0xbf0cbf7f,0x3f56bddd,0xbc21bf63,0xbf803eed,0x3f803eff,0xbd493f5e,0xbf4e3f65,0x3f183ee4,
0xbf1e3f70,0xbf49beb1,0x3f733f16,0x3e9ebf4f,0x3f76bf0e,0x3e8b3f55,0xbf730000,0x3e9e3f80,0xbf70bd21,0x3eb1bf80,0x3f16bf16,0xbf4fbf4f,0x3f0e3f1e,0xbf553f49,0x3f73,0x3f803e9e,
0x3f493eb1,0xbf1e3f70,0xbe9e3f4f,0x3f733f16,0xbe8bbf55,0x3f76bf0e,0xbe9ebf80,0xbf730000,0xbeb13f80,0xbf70bd21,0x3f4f3f4f,0x3f16bf16,0x3f55bf49,0x3f0e3f1e,0xbf80be9e,0x3f73,
0xbf803f61,0x3cf1bef6,0x3f513eed,0xbf14bf63,0xbf1d3f67,0xbf4b3edb,0x3f733f7d,0x3ea3be16,0x3e903e3e,0xbf763f7c,0x3e993f33,0x3f743f37,0x3f71bf30,0xbeac3f3a,0xbf18be2a,0x3f4e3f7c,
0xbcf13ef6,0xbf803f61,0x3f143f63,0x3f513eed,0x3f4bbedb,0xbf1d3f67,0xbea33e16,0x3f733f7d,0x3f76bf7c,0x3e903e3e,0xbf74bf37,0x3e993f33,0x3eacbf3a,0x3f71bf30,0xbf4ebf7c,0xbf18be2a,
0x3f593f7f,0xbf08bdb5,0xbed23f47,0x3f6abf20,0x3d8d3f04,0xbf7fbf5c,0x3effbd49,0x3f5ebf80,0xbf44bec9,0xbf24bf6c,0x3f7fbf56,0x3dddbf0c,0xbf78bf7a,0x3e79be65,0x3f2cbf6f,0xbf3e3eb6,
0x3f083db5,0x3f593f7f,0xbf6a3f20,0xbed23f47,0x3f7f3f5c,0x3d8d3f04,0xbf5e3f80,0x3effbd49,0x3f243f6c,0xbf44bec9,0xbddd3f0c,0x3f7fbf56,0xbe793e65,0xbf78bf7a,0x3f3ebeb6,0x3f2cbf6f,
0x3da13f79,0xbf7fbe6f,0x3efa3f2e,0x3f5fbf3c,0xbf26bf6d,0x3f43bec4,0x3df1bf7b,0xbf7e3e48,0x3f793f06,0xbe6f3f5a,0xbf2e3f68,0x3f3c3ed6,0xbf6d3da1,0xbec4bf7f,0x3f7bbefa,0xbe48bf5f,
0x3f7f3e6f,0x3da13f79,0xbf5f3f3c,0x3efa3f2e,0xbf433ec4,0xbf26bf6d,0x3f7ebe48,0x3df1bf7b,0x3e6fbf5a,0x3f793f06,0xbf3cbed6,0xbf2e3f68,0x3ec43f7f,0xbf6d3da1,0x3e483f5f,0x3f7bbefa,
0xbf413f6d,0xbf28bebf,0x3f7e3f10,0x3e02bf53,0x3f7abe79,0xbe653f78,0xbf303eac,0x3f3a3f71,0xbec9bf24,0x3f6cbf44,0xbe3ebf76,0xbf7cbe90,0xbf043f7f,0xbf5cbd8d,0x3f673f4b,0x3edbbf1d,
0x3f283ebf,0xbf413f6d,0xbe023f53,0x3f7e3f10,0x3e65bf78,0x3f7abe79,0xbf3abf71,0xbf303eac,0xbf6c3f44,0xbec9bf24,0x3f7c3e90,0xbe3ebf76,0x3f5c3d8d,0xbf043f7f,0xbedb3f1d,0x3f673f4b,
0xbf7a3f5d,0x3e5bbf01,0x3f313edf,0xbf39bf66,0xbf6b3f7f,0xbecd3dc9,0x3f7c3f62,0xbe34bef1,0xbf013f3f,0xbf5d3f2a,0x3f663f7e,0x3edf3e0c,0x3dc93e5b,0xbf7f3f7a,0x3ef13f39,0x3f623f31,
0xbe5b3f01,0xbf7a3f5d,0x3f393f66,0x3f313edf,0x3ecdbdc9,0xbf6b3f7f,0x3e343ef1,0x3f7c3f62,0x3f5dbf2a,0xbf013f3f,0xbedfbe0c,0x3f663f7e,0x3f7fbf7a,0x3dc93e5b,0xbf62bf31,0x3ef13f39,
0x3f3c3f7e,0xbf2ebdf1,0xbe6f3f43,0x3f79bf26,0xbed63e48,0xbf68bf7b,0x3f5abec4,0x3f06bf6d,0xbf7ebf5f,0x3df1befa,0x3f43bf7f,0xbf263da1,0xbe48bf3c,0x3f7b3f2e,0xbec4be6f,0xbf6d3f79,
0x3f2e3df1,0x3f3c3f7e,0xbf793f26,0xbe6f3f43,0x3f683f7b,0xbed63e48,0xbf063f6d,0x3f5abec4,0xbdf13efa,0xbf7ebf5f,0x3f26bda1,0x3f43bf7f,0xbf7bbf2e,0xbe48bf3c,0x3f6dbf79,0xbec4be6f,
0xbddd3f77,0xbf7fbe86,0x3f243f28,0x3f44bf41,0xbe52bf80,0x3f7bbd49,0xbebfbf5c,0xbf6d3f04,0x3eff3f6f,0xbf5e3eb6,0x3d8d3f7a,0x3f7fbe65,0xbf3ebf47,0x3f2cbf20,0x3e79bf7f,0xbf78bdb5,
0x3f7f3e86,0xbddd3f77,0xbf443f41,0x3f243f28,0xbf7b3d49,0xbe52bf80,0x3f6dbf04,0xbebfbf5c,0x3f5ebeb6,0x3eff3f6f,0xbf7f3e65,0x3d8d3f7a,0xbf2c3f20,0xbf3ebf47,0x3f783db5,0x3e79bf7f,
0xbf5d3f6b,0xbf01becd,0x3f803f0a,0xbd71bf58,0x3f3f3dc9,0xbf2a3f7f,0xbe813f22,0x3f783f46,0x3ecdbf7a,0x3f6bbe5b,0xbf58bf6e,0xbf0a3ebb,0xbf7f3f01,0x3dc9bf5d,0x3f46bd71,0xbf22bf80,
0x3f013ecd,0xbf5d3f6b,0x3d713f58,0x3f803f0a,0x3f2abf7f,0x3f3f3dc9,0xbf78bf46,0xbe813f22,0xbf6b3e5b,0x3ecdbf7a,0x3f0abebb,0xbf58bf6e,0xbdc93f5d,0xbf7f3f01,0x3f223f80,0x3f46bd71,
0xbf6c3f59,0x3ec9bf08,0x3f0c3ed2,0xbf56bf6a,0xbf7f3f78,0x3db5be79,0x3f473f2c,0xbf20bf3e,0xbf7a3f7f,0xbe653d8d,0x3f6f3f5e,0xbeb6beff,0xbf5c3f6d,0xbf043ebf,0x3f803f7b,0xbd49be52,
0xbec93f08,0xbf6c3f59,0x3f563f6a,0x3f0c3ed2,0xbdb53e79,0xbf7f3f78,0x3f203f3e,0x3f473f2c,0x3e65bd8d,0xbf7a3f7f,0x3eb63eff,0x3f6f3f5e,0x3f04bebf,0xbf5c3f6d,0x3d493e52,0x3f803f7b,
0x3f803f80,0,0xbf353f35,0x3f35bf35,0x3f803f80,0,0xbf353f35,0x3f35bf35,0x3f803f80,0,0xbf353f35,0x3f35bf35,0x3f803f80,0,0xbf353f35,0x3f35bf35,
0,0x3f803f80,0xbf353f35,0xbf353f35,0,0x3f803f80,0xbf353f35,0xbf353f35,0,0x3f803f80,0xbf353f35,0xbf353f35,0,0x3f803f80,0xbf353f35,0xbf353f35,
0x3f0e3f7b,0xbf55be48,0x3e483f0e,0x3f7bbf55,0xbf55be48,0xbf0ebf7b,0x3f7bbf55,0xbe48bf0e,0xbf0ebf7b,0x3f553e48,0xbe48bf0e,0xbf7b3f55,0x3f553e48,0x3f0e3f7b,0xbf7b3f55,0x3e483f0e,
0x3f553e48,0x3f0e3f7b,0xbf7b3f55,0x3e483f0e,0x3f0e3f7b,0xbf55be48,0x3e483f0e,0x3f7bbf55,0xbf55be48,0xbf0ebf7b,0x3f7bbf55,0xbe48bf0e,0xbf0ebf7b,0x3f553e48,0xbe48bf0e,0xbf7b3f55,
0xbec43f6d,0xbf6dbec4,0x3f6d3ec4,0x3ec4bf6d,0x3ec4bf6d,0x3f6d3ec4,0xbf6dbec4,0xbec43f6d,0xbec43f6d,0xbf6dbec4,0x3f6d3ec4,0x3ec4bf6d,0x3ec4bf6d,0x3f6d3ec4,0xbf6dbec4,0xbec43f6d,
0x3f6d3ec4,0xbec43f6d,0xbec43f6d,0x3f6d3ec4,0xbf6dbec4,0x3ec4bf6d,0x3ec4bf6d,0xbf6dbec4,0x3f6d3ec4,0xbec43f6d,0xbec43f6d,0x3f6d3ec4,0xbf6dbec4,0x3ec4bf6d,0x3ec4bf6d,0xbf6dbec4,
0xbf7b3f55,0xbe48bf0e,0x3f553e48,0xbf0ebf7b,0x3e483f0e,0xbf7b3f55,0x3f0e3f7b,0x3f553e48,0x3f7bbf55,0x3e483f0e,0xbf55be48,0x3f0e3f7b,0xbe48bf0e,0x3f7bbf55,0xbf0ebf7b,0xbf55be48,
0x3e483f0e,0xbf7b3f55,0x3f0e3f7b,0x3f553e48,0x3f7bbf55,0x3e483f0e,0xbf55be48,0x3f0e3f7b,0xbe48bf0e,0x3f7bbf55,0xbf0ebf7b,0xbf55be48,0xbf7b3f55,0xbe48bf0e,0x3f553e48,0xbf0ebf7b,
0x3f7b3f80,0xbe48bd21,0xbf0e3f2e,0x3f55bf3c,0x3f5f3f70,0xbefabeb1,0xbe8b3ed6,0x3f76bf68,0x3f2e3f49,0xbf3cbf1e,0x3d213df1,0x3f80bf7e,0x3ed63f0e,0xbf68bf55,0x3eb1be48,0x3f70bf7b,
0x3e483d21,0x3f7b3f80,0xbf553f3c,0xbf0e3f2e,0x3efa3eb1,0x3f5f3f70,0xbf763f68,0xbe8b3ed6,0x3f3c3f1e,0x3f2e3f49,0xbf803f7e,0x3d213df1,0x3f683f55,0x3ed63f0e,0xbf703f7b,0x3eb1be48,
0x3ec43f79,0xbf6dbe6f,0x3ec43f06,0x3f6dbf5a,0xbf7fbf06,0xbda1bf5a,0x3f43bf79,0xbf26be6f,0x3e6fbf26,0x3f793f43,0xbf5a3da1,0xbf063f7f,0x3f5a3f6d,0xbf063ec4,0xbe6f3f6d,0x3f79bec4,
0x3f6d3e6f,0x3ec43f79,0xbf6d3f5a,0x3ec43f06,0x3da13f5a,0xbf7fbf06,0x3f263e6f,0x3f43bf79,0xbf79bf43,0x3e6fbf26,0x3f06bf7f,0xbf5a3da1,0x3f06bec4,0x3f5a3f6d,0xbf793ec4,0xbe6f3f6d,
0xbf0e3f68,0xbf55bed6,0x3f7b3eb1,0x3e48bf70,0x3f49bf3c,0x3f1e3f2e,0xbf7ebd21,0x3df13f80,0xbf703efa,0xbeb1bf5f,0x3f68be8b,0xbed6bf76,0x3f80be48,0x3d213f7b,0xbf3c3f0e,0x3f2e3f55,
0x3f553ed6,0xbf0e3f68,0xbe483f70,0x3f7b3eb1,0xbf1ebf2e,0x3f49bf3c,0xbdf1bf80,0xbf7ebd21,0x3eb13f5f,0xbf703efa,0x3ed63f76,0x3f68be8b,0xbd21bf7b,0x3f80be48,0xbf2ebf55,0xbf3c3f0e,
0xbf803f4f,0xbf16,0x3f353e20,0xbf35bf7d,0xbe9e3f4f,0xbf733f16,0x3f643f7d,0x3ee8be20,0x3f4fbe9e,0xbf163f73,0xbe203ee8,0x3f7d3f64,0x3f4fbf80,0x3f160000,0xbf7dbf35,0x3e203f35,
0x3f16,0xbf803f4f,0x3f353f7d,0x3f353e20,0x3f73bf16,0xbe9e3f4f,0xbee83e20,0x3f643f7d,0x3f16bf73,0x3f4fbe9e,0xbf7dbf64,0xbe203ee8,0xbf160000,0x3f4fbf80,0xbe20bf35,0xbf7dbf35,
0x3f6d3f7f,0xbec4bda1,0xbec43f26,0x3f6dbf43,0x3f063f43,0xbf5abf26,0x3e6f3da1,0x3f79bf7f,0xbda13e6f,0xbf7fbf79,0x3f43bf06,0x3f26bf5a,0xbf26bec4,0xbf43bf6d,0x3f7fbf6d,0x3da1bec4,
0x3ec43da1,0x3f6d3f7f,0xbf6d3f43,0xbec43f26,0x3f5a3f26,0x3f063f43,0xbf793f7f,0x3e6f3da1,0x3f7f3f79,0xbda13e6f,0xbf263f5a,0x3f43bf06,0x3f433f6d,0xbf26bec4,0xbda13ec4,0x3f7fbf6d,
0x3e483f76,0xbf7bbe8b,0x3f0e3efa,0x3f55bf5f,0xbf68bf49,0x3ed6bf1e,0x3eb1bf7e,0xbf703df1,0x3f5fbd21,0x3efa3f80,0xbf763f2e,0x3e8b3f3c,0xbdf13f55,0xbf7ebf0e,0x3f493e48,0x3f1ebf7b,
0x3f7b3e8b,0x3e483f76,0xbf553f5f,0x3f0e3efa,0xbed63f1e,0xbf68bf49,0x3f70bdf1,0x3eb1bf7e,0xbefabf80,0x3f5fbd21,0xbe8bbf3c,0xbf763f2e,0x3f7e3f0e,0xbdf13f55,0xbf1e3f7b,0x3f493e48,
0xbf353f64,0xbf35bee8,0x3f803e9e,0xbf73,0x3f7dbee8,0x3e203f64,0xbf4f3e9e,0x3f163f73,0xbf64be20,0x3ee8bf7d,0x3e9ebf4f,0xbf73bf16,0x3ee83f35,0xbf643f35,0x3e9e3f80,0x3f730000,
0x3f353ee8,0xbf353f64,0x3f73,0x3f803e9e,0xbe20bf64,0x3f7dbee8,0xbf16bf73,0xbf4f3e9e,0xbee83f7d,0xbf64be20,0x3f733f16,0x3e9ebf4f,0x3f64bf35,0x3ee83f35,0xbf730000,0x3e9e3f80,
0xbf7b3f49,0x3e48bf1e,0x3f0e3df1,0xbf55bf7e,0xbf3c3f76,0xbf2e3e8b,0x3f803f5f,0xbd21befa,0x3df13eb1,0xbf7e3f70,0x3f1e3f68,0x3f493ed6,0x3f5fbf0e,0xbefa3f55,0xbe8b3e48,0x3f763f7b,
0xbe483f1e,0xbf7b3f49,0x3f553f7e,0x3f0e3df1,0x3f2ebe8b,0xbf3c3f76,0x3d213efa,0x3f803f5f,0x3f7ebf70,0x3df13eb1,0xbf49bed6,0x3f1e3f68,0x3efabf55,0x3f5fbf0e,0xbf76bf7b,0xbe8b3e48,
0x3f553f7e,0xbf0ebdf1,0xbe483f1e,0x3f7bbf49,0x3d213efa,0xbf80bf5f,0x3f2ebe8b,0x3f3cbf76,0xbf49bed6,0xbf1ebf68,0x3f7ebf70,0xbdf1beb1,0xbf76bf7b,0x3e8bbe48,0x3efabf55,0xbf5f3f0e,
0x3f0e3df1,0x3f553f7e,0xbf7b3f49,0xbe483f1e,0x3f803f5f,0x3d213efa,0xbf3c3f76,0x3f2ebe8b,0x3f1e3f68,0xbf49bed6,0x3df13eb1,0x3f7ebf70,0xbe8b3e48,0xbf76bf7b,0x3f5fbf0e,0x3efabf55,
0x3f73,0xbf80be9e,0x3f353ee8,0x3f35bf64,0xbf16bf73,0x3f4fbe9e,0xbe20bf64,0xbf7d3ee8,0x3f733f16,0xbe9e3f4f,0xbee83f7d,0x3f643e20,0xbf730000,0xbe9ebf80,0x3f64bf35,0xbee8bf35,
0x3f803e9e,0x3f73,0xbf353f64,0x3f353ee8,0xbf4f3e9e,0xbf16bf73,0x3f7dbee8,0xbe20bf64,0x3e9ebf4f,0x3f733f16,0xbf64be20,0xbee83f7d,0x3e9e3f80,0xbf730000,0x3ee83f35,0x3f64bf35,
0xbf553f5f,0xbf0ebefa,0x3f7b3e8b,0xbe48bf76,0x3f70bdf1,0xbeb13f7e,0xbed63f1e,0x3f683f49,0xbe8bbf3c,0x3f76bf2e,0xbefabf80,0xbf5f3d21,0xbf1e3f7b,0xbf49be48,0x3f7e3f0e,0x3df1bf55,
0x3f0e3efa,0xbf553f5f,0x3e483f76,0x3f7b3e8b,0x3eb1bf7e,0x3f70bdf1,0xbf68bf49,0xbed63f1e,0xbf763f2e,0xbe8bbf3c,0x3f5fbd21,0xbefabf80,0x3f493e48,0xbf1e3f7b,0xbdf13f55,0x3f7e3f0e,
0xbf6d3f43,0x3ec4bf26,0x3ec43da1,0xbf6dbf7f,0xbf793f7f,0xbe6fbda1,0x3f5a3f26,0xbf06bf43,0xbf263f5a,0xbf433f06,0x3f7f3f79,0x3da1be6f,0xbda13ec4,0xbf7f3f6d,0x3f433f6d,0x3f263ec4,
0xbec43f26,0xbf6d3f43,0x3f6d3f7f,0x3ec43da1,0x3e6f3da1,0xbf793f7f,0x3f063f43,0x3f5a3f26,0x3f43bf06,0xbf263f5a,0xbda13e6f,0x3f7f3f79,0x3f7fbf6d,0xbda13ec4,0xbf26bec4,0x3f433f6d,
0x3f353f7d,0xbf35be20,0x3f16,0x3f80bf4f,0xbee83e20,0xbf64bf7d,0x3f73bf16,0x3e9ebf4f,0xbf7dbf64,0x3e20bee8,0x3f16bf73,0xbf4f3e9e,0xbe20bf35,0x3f7d3f35,0xbf160000,0xbf4f3f80,
0x3f353e20,0x3f353f7d,0xbf803f4f,0x3f16,0x3f643f7d,0xbee83e20,0xbe9e3f4f,0x3f73bf16,0xbe203ee8,0xbf7dbf64,0x3f4fbe9e,0x3f16bf73,0xbf7dbf35,0xbe20bf35,0x3f4fbf80,0xbf160000,
0xbe483f70,0xbf7bbeb1,0x3f553ed6,0x3f0ebf68,0xbdf1bf80,0x3f7e3d21,0xbf1ebf2e,0xbf493f3c,0x3ed63f76,0xbf683e8b,0x3eb13f5f,0x3f70befa,0xbf2ebf55,0x3f3cbf0e,0xbd21bf7b,0xbf803e48,
0x3f7b3eb1,0xbe483f70,0xbf0e3f68,0x3f553ed6,0xbf7ebd21,0xbdf1bf80,0x3f49bf3c,0xbf1ebf2e,0x3f68be8b,0x3ed63f76,0xbf703efa,0x3eb13f5f,0xbf3c3f0e,0xbf2ebf55,0x3f80be48,0xbd21bf7b,
0xbf6d3f5a,0xbec4bf06,0x3f6d3e6f,0xbec4bf79,0x3f263e6f,0xbf433f79,0x3da13f5a,0x3f7f3f06,0x3f06bf7f,0x3f5abda1,0xbf79bf43,0xbe6f3f26,0xbf793ec4,0x3e6fbf6d,0x3f06bec4,0xbf5abf6d,
0x3ec43f06,0xbf6d3f5a,0x3ec43f79,0x3f6d3e6f,0x3f43bf79,0x3f263e6f,0xbf7fbf06,0x3da13f5a,0xbf5a3da1,0x3f06bf7f,0x3e6fbf26,0xbf79bf43,0xbe6f3f6d,0xbf793ec4,0x3f5a3f6d,0x3f06bec4,
0xbf553f3c,0x3f0ebf2e,0x3e483d21,0xbf7bbf80,0xbf763f68,0x3e8bbed6,0x3efa3eb1,0xbf5fbf70,0xbf803f7e,0xbd21bdf1,0x3f3c3f1e,0xbf2ebf49,0xbf703f7b,0xbeb13e48,0x3f683f55,0xbed6bf0e,
0xbf0e3f2e,0xbf553f3c,0x3f7b3f80,0x3e483d21,0xbe8b3ed6,0xbf763f68,0x3f5f3f70,0x3efa3eb1,0x3d213df1,0xbf803f7e,0x3f2e3f49,0x3f3c3f1e,0x3eb1be48,0xbf703f7b,0x3ed63f0e,0x3f683f55,
0x3f803f80,0,0xbf0e3f0e,0x3f55bf55,0x3f803f80,0,0xbf0e3f0e,0x3f55bf55,0x3f803f80,0,0xbf0e3f0e,0x3f55bf55,0x3f803f80,0,0xbf0e3f0e,0x3f55bf55,
0,0x3f803f80,0xbf553f55,0xbf0e3f0e,0,0x3f803f80,0xbf553f55,0xbf0e3f0e,0,0x3f803f80,0xbf553f55,0xbf0e3f0e,0,0x3f803f80,0xbf553f55,0xbf0e3f0e,
0x3f043f78,0xbf5cbe79,0x3edb3eac,0x3f67bf71,0xbf5cbe79,0xbf04bf78,0x3f67bf71,0xbedbbeac,0xbf04bf78,0x3f5c3e79,0xbedbbeac,0xbf673f71,0x3f5c3e79,0x3f043f78,0xbf673f71,0x3edb3eac,
0x3f5c3e79,0x3f043f78,0xbf673f71,0x3edb3eac,0x3f043f78,0xbf5cbe79,0x3edb3eac,0x3f67bf71,0xbf5cbe79,0xbf04bf78,0x3f67bf71,0xbedbbeac,0xbf04bf78,0x3f5c3e79,0xbedbbeac,0xbf673f71,
0xbef13f62,0xbf62bef1,0x3f7f3dc9,0x3dc9bf7f,0x3ef1bf62,0x3f623ef1,0xbf7fbdc9,0xbdc93f7f,0xbef13f62,0xbf62bef1,0x3f7f3dc9,0x3dc9bf7f,0x3ef1bf62,0x3f623ef1,0xbf7fbdc9,0xbdc93f7f,
0x3f623ef1,0xbef13f62,0xbdc93f7f,0x3f7f3dc9,0xbf62bef1,0x3ef1bf62,0x3dc9bf7f,0xbf7fbdc9,0x3f623ef1,0xbef13f62,0xbdc93f7f,0x3f7f3dc9,0xbf62bef1,0x3ef1bf62,0x3dc9bf7f,0xbf7fbdc9,
0xbf803f3e,0xbd49bf2c,0x3f18be16,0xbf4ebf7d,0x3d493f2c,0xbf803f3e,0x3f4e3f7d,0x3f18be16,0x3f80bf3e,0x3d493f2c,0xbf183e16,0x3f4e3f7d,0xbd49bf2c,0x3f80bf3e,0xbf4ebf7d,0xbf183e16,
0x3d493f2c,0xbf803f3e,0x3f4e3f7d,0x3f18be16,0x3f80bf3e,0x3d493f2c,0xbf183e16,0x3f4e3f7d,0xbd49bf2c,0x3f80bf3e,0xbf4ebf7d,0xbf183e16,0xbf803f3e,0xbd49bf2c,0x3f18be16,0xbf4ebf7d,
0x3f7b3f80,0xbe52bd49,0xbebf3f04,0x3f6dbf5c,0x3f5e3f6f,0xbeffbeb6,0xbd8d3e65,0x3f7fbf7a,0x3f2c3f47,0xbf3ebf20,0x3e79bdb5,0x3f78bf7f,0x3ed23f0c,0xbf6abf56,0x3f08bec9,0x3f59bf6c,
0x3e523d49,0x3f7b3f80,0xbf6d3f5c,0xbebf3f04,0x3eff3eb6,0x3f5e3f6f,0xbf7f3f7a,0xbd8d3e65,0x3f3e3f20,0x3f2c3f47,0xbf783f7f,0x3e79bdb5,0x3f6a3f56,0x3ed23f0c,0xbf593f6c,0x3f08bec9,
0x3ea83f75,0xbf72be95,0x3f1b3e95,0x3f4cbf75,0xbf80bf12,0xbca1bf52,0x3f12bf80,0xbf523ca1,0x3e95bf1b,0x3f753f4c,0xbf753ea8,0xbe953f72,0x3f523f72,0xbf123ea8,0x3ca13f4c,0x3f80bf1b,
0x3f723e95,0x3ea83f75,0xbf4c3f75,0x3f1b3e95,0x3ca13f52,0xbf80bf12,0x3f52bca1,0x3f12bf80,0xbf75bf4c,0x3e95bf1b,0x3e95bf72,0xbf753ea8,0x3f12bea8,0x3f523f72,0xbf803f1b,0x3ca13f4c,
0xbf243f5c,0xbf44bf04,0x3f7f3d49,0xbdddbf80,0x3f59bf28,0x3f083f41,0xbf6a3e86,0x3ed23f77,0xbf783ec9,0xbe79bf6c,0x3f3ebf0c,0xbf2cbf56,0x3f7fbdb5,0xbd8d3f7f,0xbeff3f47,0x3f5e3f20,
0x3f443f04,0xbf243f5c,0x3ddd3f80,0x3f7f3d49,0xbf08bf41,0x3f59bf28,0xbed2bf77,0xbf6a3e86,0x3e793f6c,0xbf783ec9,0x3f2c3f56,0x3f3ebf0c,0x3d8dbf7f,0x3f7fbdb5,0xbf5ebf20,0xbeff3f47,
0xbf7d3f35,0x3e20bf35,0x3ed6be48,0xbf68bf7b,0xbee83f64,0xbf643ee8,0x3f7e3f5f,0x3df1befa,0x3f35be20,0xbf353f7d,0x3e483f3c,0x3f7b3f2e,0x3f64bf7d,0x3ee83e20,0xbf5fbed6,0x3efa3f68,
0xbe203f35,0xbf7d3f35,0x3f683f7b,0x3ed6be48,0x3f64bee8,0xbee83f64,0xbdf13efa,0x3f7e3f5f,0x3f35bf7d,0x3f35be20,0xbf7bbf2e,0x3e483f3c,0xbee8be20,0x3f64bf7d,0xbefabf68,0xbf5fbed6,
0x3f6b3f7f,0xbecdbdc9,0xbe343ef1,0x3f7cbf62,0x3f013f3f,0xbf5dbf2a,0x3edfbe0c,0x3f66bf7e,0xbdc93e5b,0xbf7fbf7a,0x3f62bf31,0x3ef1bf39,0xbf2abecd,0xbf3fbf6b,0x3f7ebf7c,0xbe0cbe34,
0x3ecd3dc9,0x3f6b3f7f,0xbf7c3f62,0xbe343ef1,0x3f5d3f2a,0x3f013f3f,0xbf663f7e,0x3edfbe0c,0x3f7f3f7a,0xbdc93e5b,0xbef13f39,0x3f62bf31,0x3f3f3f6b,0xbf2abecd,0x3e0c3e34,0x3f7ebf7c,
0x3e023f71,0xbf7ebeac,0x3f413e79,0x3f28bf78,0xbf61bf53,0x3ef6bf10,0x3db5bf6d,0xbf7f3ebf,0x3f673cf1,0x3edb3f80,0xbf5c3f59,0x3f043f08,0xbe3e3f4b,0xbf7cbf1d,0x3f6cbd8d,0x3ec9bf7f,
0x3f7e3eac,0x3e023f71,0xbf283f78,0x3f413e79,0xbef63f10,0xbf61bf53,0x3f7fbebf,0x3db5bf6d,0xbedbbf80,0x3f673cf1,0xbf04bf08,0xbf5c3f59,0x3f7c3f1d,0xbe3e3f4b,0xbec93f7f,0x3f6cbd8d,
0xbf493f55,0xbf1ebf0e,0x3f730000,0xbe9ebf80,0x3f80beb1,0x3d213f70,0xbf163f16,0x3f4f3f4f,0xbf55be8b,0x3f0ebf76,0xbf73,0xbf80be9e,0x3eb13f49,0xbf703f1e,0x3f163f73,0x3f4fbe9e,
0x3f1e3f0e,0xbf493f55,0x3e9e3f80,0x3f730000,0xbd21bf70,0x3f80beb1,0xbf4fbf4f,0xbf163f16,0xbf0e3f76,0xbf55be8b,0x3f803e9e,0xbf73,0x3f70bf1e,0x3eb13f49,0xbf4f3e9e,0x3f163f73,
0xbf6f3f2c,0x3eb6bf3e,0x3e65be79,0xbf7abf78,0xbf563f7f,0xbf0c3ddd,0x3f6c3f24,0xbec9bf44,0xbd493eff,0xbf803f5e,0x3f5c3f7f,0x3f043d8d,0x3f47bed2,0xbf203f6a,0x3db53f08,0x3f7f3f59,
0xbeb63f3e,0xbf6f3f2c,0x3f7a3f78,0x3e65be79,0x3f0cbddd,0xbf563f7f,0x3ec93f44,0x3f6c3f24,0x3f80bf5e,0xbd493eff,0xbf04bd8d,0x3f5c3f7f,0x3f20bf6a,0x3f47bed2,0xbf7fbf59,0x3db53f08,
0x3f513f7d,0xbf14be16,0x3cf13edb,0x3f80bf67,0x3c213eed,0xbf80bf63,0x3f53bef6,0x3f10bf61,0xbf4ebee4,0xbf18bf65,0x3f71bf7e,0xbeacbe02,0xbf74bf7c,0x3e99be2a,0x3e90bf30,0xbf763f3a,
0x3f143e16,0x3f513f7d,0xbf803f67,0x3cf13edb,0x3f803f63,0x3c213eed,0xbf103f61,0x3f53bef6,0x3f183f65,0xbf4ebee4,0x3eac3e02,0x3f71bf7e,0xbe993e2a,0xbf74bf7c,0x3f76bf3a,0x3e90bf30,
0xbda13f6d,0xbf7fbec4,0x3f5f3e48,0x3efabf7b,0xbf06bf79,0x3f5abe6f,0xbed6bf3c,0xbf683f2e,0x3f6d3f26,0xbec43f43,0xbe483f7e,0x3f7bbdf1,0xbf79bda1,0xbe6fbf7f,0x3f3cbf5f,0xbf2ebefa,
0x3f7f3ec4,0xbda13f6d,0xbefa3f7b,0x3f5f3e48,0xbf5a3e6f,0xbf06bf79,0x3f68bf2e,0xbed6bf3c,0x3ec4bf43,0x3f6d3f26,0xbf7b3df1,0xbe483f7e,0x3e6f3f7f,0xbf79bda1,0x3f2e3efa,0x3f3cbf5f,
0xbf653f4e,0xbee4bf18,0x3f5ebd49,0xbeffbf80,0x3f633c21,0xbeed3f80,0xbddd3f56,0x3f7f3f0c,0xbe16bf51,0x3f7dbf14,0xbf3ebf6f,0xbf2c3eb6,0xbf373f73,0xbf33bea3,0x3f7b3e86,0xbe52bf77,
0x3ee43f18,0xbf653f4e,0x3eff3f80,0x3f5ebd49,0x3eedbf80,0x3f633c21,0xbf7fbf0c,0xbddd3f56,0xbf7d3f14,0xbe16bf51,0x3f2cbeb6,0xbf3ebf6f,0x3f333ea3,0xbf373f73,0x3e523f77,0x3f7b3e86,
0xbf583f22,0x3f0abf46,0x3ca1be95,0xbf80bf75,0xbf803f78,0xbd71be81,0x3f1b3ea8,0xbf4cbf72,0xbf463f6e,0xbf223ebb,0x3f753f52,0xbe95bf12,0xbe813f0a,0xbf783f58,0x3f723f80,0x3ea83ca1,
0xbf0a3f46,0xbf583f22,0x3f803f75,0x3ca1be95,0x3d713e81,0xbf803f78,0x3f4c3f72,0x3f1b3ea8,0x3f22bebb,0xbf463f6e,0x3e953f12,0x3f753f52,0x3f78bf58,0xbe813f0a,0xbea8bca1,0x3f723f80,
0x3f2e3f7b,0xbf3cbe48,0x3e6f3ec4,0x3f79bf6d,0xbefa3df1,0xbf5fbf7e,0x3f7fbf43,0x3da1bf26,0xbf7bbf68,0x3e48bed6,0x3ec4bf5a,0xbf6d3f06,0xbdf1bf2e,0x3f7e3f3c,0xbf433e6f,0xbf263f79,
0x3f3c3e48,0x3f2e3f7b,0xbf793f6d,0x3e6f3ec4,0x3f5f3f7e,0xbefa3df1,0xbda13f26,0x3f7fbf43,0xbe483ed6,0xbf7bbf68,0x3f6dbf06,0x3ec4bf5a,0xbf7ebf3c,0xbdf1bf2e,0x3f26bf79,0xbf433e6f,
0xbe903f67,0xbf76bedb,0x3f743e16,0x3e99bf7d,0xbcf1bf7e,0x3f803e02,0xbf51bee4,0xbf143f65,0x3eac3f7c,0xbf713e3e,0x3f183f33,0x3f4ebf37,0xbf1dbf61,0x3f4bbef6,0xbea3bf63,0xbf733eed,
0x3f763edb,0xbe903f67,0xbe993f7d,0x3f743e16,0xbf80be02,0xbcf1bf7e,0x3f14bf65,0xbf51bee4,0x3f71be3e,0x3eac3f7c,0xbf4e3f37,0x3f183f33,0xbf4b3ef6,0xbf1dbf61,0x3f73beed,0xbea3bf63,
0xbf783f46,0xbe81bf22,0x3f3fbdc9,0xbf2abf7f,0x3f0a3ebb,0xbf583f6e,0x3ecd3f7a,0x3f6b3e5b,0x3f22bf80,0x3f463d71,0xbf7fbf01,0x3dc93f5d,0xbf6e3e81,0x3ebbbf78,0x3e5bbf2a,0xbf7abf3f,
0x3e813f22,0xbf783f46,0x3f2a3f7f,0x3f3fbdc9,0x3f58bf6e,0x3f0a3ebb,0xbf6bbe5b,0x3ecd3f7a,0xbf46bd71,0x3f22bf80,0xbdc9bf5d,0xbf7fbf01,0xbebb3f78,0xbf6e3e81,0x3f7a3f3f,0x3e5bbf2a,
0xbf373f18,0x3f33bf4e,0xbe3ebeac,0xbf7cbf71,0xbf653f51,0x3ee4bf14,0x3e02bcf1,0xbf7ebf80,0xbf7d3f74,0x3e16be99,0x3edb3e90,0xbf67bf76,0xbf7c3f80,0xbe2a3c21,0x3f303f10,0xbf3abf53,
0xbf333f4e,0xbf373f18,0x3f7c3f71,0xbe3ebeac,0xbee43f14,0xbf653f51,0x3f7e3f80,0x3e02bcf1,0xbe163e99,0xbf7d3f74,0x3f673f76,0x3edb3e90,0x3e2abc21,0xbf7c3f80,0x3f3a3f53,0x3f303f10,
0x3f803f80,0,0xbec43ec4,0x3f6dbf6d,0x3f803f80,0,0xbec43ec4,0x3f6dbf6d,0x3f803f80,0,0xbec43ec4,0x3f6dbf6d,0x3f803f80,0,0xbec43ec4,0x3f6dbf6d,
0,0x3f803f80,0xbf6d3f6d,0xbec43ec4,0,0x3f803f80,0xbf6d3f6d,0xbec43ec4,0,0x3f803f80,0xbf6d3f6d,0xbec43ec4,0,0x3f803f80,0xbf6d3f6d,0xbec43ec4,
0x3ef13f75,0xbf62be95,0x3f223dc9,0x3f46bf7f,0xbf62be95,0xbef1bf75,0x3f46bf7f,0xbf22bdc9,0xbef1bf75,0x3f623e95,0xbf22bdc9,0xbf463f7f,0x3f623e95,0x3ef13f75,0xbf463f7f,0x3f223dc9,
0x3f623e95,0x3ef13f75,0xbf463f7f,0x3f223dc9,0x3ef13f75,0xbf62be95,0x3f223dc9,0x3f46bf7f,0xbf62be95,0xbef1bf75,0x3f46bf7f,0xbf22bdc9,0xbef1bf75,0x3f623e95,0xbf22bdc9,0xbf463f7f,
0xbf0e3f55,0xbf55bf0e,0x3f7bbe48,0xbe48bf7b,0x3f0ebf55,0x3f553f0e,0xbf7b3e48,0x3e483f7b,0xbf0e3f55,0xbf55bf0e,0x3f7bbe48,0xbe48bf7b,0x3f0ebf55,0x3f553f0e,0xbf7b3e48,0x3e483f7b,
0x3f553f0e,0xbf0e3f55,0x3e483f7b,0x3f7bbe48,0xbf55bf0e,0x3f0ebf55,0xbe48bf7b,0xbf7b3e48,0x3f553f0e,0xbf0e3f55,0x3e483f7b,0x3f7bbe48,0xbf55bf0e,0x3f0ebf55,0xbe48bf7b,0xbf7b3e48,
0xbf7f3f22,0x3dc9bf46,0x3e95bef1,0xbf75bf62,0xbdc93f46,0xbf7f3f22,0x3f753f62,0x3e95bef1,0x3f7fbf22,0xbdc93f46,0xbe953ef1,0x3f753f62,0x3dc9bf46,0x3f7fbf22,0xbf75bf62,0xbe953ef1,
0xbdc93f46,0xbf7f3f22,0x3f753f62,0x3e95bef1,0x3f7fbf22,0xbdc93f46,0xbe953ef1,0x3f753f62,0x3dc9bf46,0x3f7fbf22,0xbf75bf62,0xbe953ef1,0xbf7f3f22,0x3dc9bf46,0x3e95bef1,0xbf75bf62,
0x3f7a3f80,0xbe5bbd71,0xbe343ea8,0x3f7cbf72,0x3f5d3f6e,0xbf01bebb,0x3e0c3ca1,0x3f7ebf80,0x3f2a3f46,0xbf3fbf22,0x3edfbe95,0x3f66bf75,0x3ecd3f0a,0xbf6bbf58,0x3f31bf12,0x3f39bf52,
0x3e5b3d71,0x3f7a3f80,0xbf7c3f72,0xbe343ea8,0x3f013ebb,0x3f5d3f6e,0xbf7e3f80,0x3e0c3ca1,0x3f3f3f22,0x3f2a3f46,0xbf663f75,0x3edfbe95,0x3f6b3f58,0x3ecd3f0a,0xbf393f52,0x3f31bf12,
0x3e8b3f70,0xbf76beb1,0x3f493d21,0x3f1ebf80,0xbf80bf1e,0x3d21bf49,0x3eb1bf76,0xbf703e8b,0x3eb1bf0e,0x3f703f55,0xbf803f0e,0xbd213f55,0x3f493f76,0xbf1e3e8b,0x3e8b3f1e,0x3f76bf49,
0x3f763eb1,0x3e8b3f70,0xbf1e3f80,0x3f493d21,0xbd213f49,0xbf80bf1e,0x3f70be8b,0x3eb1bf76,0xbf70bf55,0x3eb1bf0e,0x3d21bf55,0xbf803f0e,0x3f1ebe8b,0x3f493f76,0xbf763f49,0x3e8b3f1e,
0xbf393f4c,0xbf31bf1b,0x3f6bbe81,0xbecdbf78,0x3f66bf12,0x3edf3f52,0xbf3f3f0a,0x3f2a3f58,0xbf7e3e95,0xbe0cbf75,0x3f01bf46,0xbf5dbf22,0x3f7c3ca1,0xbe343f80,0xbe5b3f6e,0x3f7a3ebb,
0x3f313f1b,0xbf393f4c,0x3ecd3f78,0x3f6bbe81,0xbedfbf52,0x3f66bf12,0xbf2abf58,0xbf3f3f0a,0x3e0c3f75,0xbf7e3e95,0x3f5d3f22,0x3f01bf46,0x3e34bf80,0x3f7c3ca1,0xbf7abebb,0xbe5b3f6e,
0xbf733f16,0x3e9ebf4f,0x3da1bf06,0xbf7fbf5a,0xbf163f73,0xbf4f3e9e,0x3f793f26,0xbe6fbf43,0x3f160000,0xbf4f3f80,0x3f063f6d,0x3f5a3ec4,0x3f73bf73,0x3e9e3e9e,0xbf26bda1,0x3f433f7f,
0xbe9e3f4f,0xbf733f16,0x3f7f3f5a,0x3da1bf06,0x3f4fbe9e,0xbf163f73,0x3e6f3f43,0x3f793f26,0x3f4fbf80,0x3f160000,0xbf5abec4,0x3f063f6d,0xbe9ebe9e,0x3f73bf73,0xbf43bf7f,0xbf26bda1,
0x3f683f7e,0xbed6bdf1,0x3d213e8b,0x3f80bf76,0x3efa3f3c,0xbf5fbf2e,0x3f1ebeb1,0x3f49bf70,0xbdf13e48,0xbf7ebf7b,0x3f76bf55,0x3e8bbf0e,0xbf2ebed6,0xbf3cbf68,0x3f70bf80,0xbeb13d21,
0x3ed63df1,0x3f683f7e,0xbf803f76,0x3d213e8b,0x3f5f3f2e,0x3efa3f3c,0xbf493f70,0x3f1ebeb1,0x3f7e3f7b,0xbdf13e48,0xbe8b3f0e,0x3f76bf55,0x3f3c3f68,0xbf2ebed6,0x3eb1bd21,0x3f70bf80,
0x3d713f6b,0xbf80becd,0x3f66bca1,0x3edfbf80,0xbf58bf5d,0x3f0abf01,0xbe34bf4c,0xbf7c3f1b,0x3f6e3dc9,0x3ebb3f7f,0xbf313f75,0x3f393e95,0xbe813f3f,0xbf78bf2a,0x3f7ebea8,0x3e0cbf72,
0x3f803ecd,0x3d713f6b,0xbedf3f80,0x3f66bca1,0xbf0a3f01,0xbf58bf5d,0x3f7cbf1b,0xbe34bf4c,0xbebbbf7f,0x3f6e3dc9,0xbf39be95,0xbf313f75,0x3f783f2a,0xbe813f3f,0xbe0c3f72,0x3f7ebea8,
0xbf5a3f43,0xbf06bf26,0x3f4fbe9e,0xbf16bf73,0x3f7fbe6f,0xbda13f79,0xbe9e3f4f,0x3f733f16,0xbf43bec4,0x3f26bf6d,0xbe9ebf80,0xbf730000,0x3e6f3f5a,0xbf793f06,0x3f4f3f4f,0x3f16bf16,
0x3f063f26,0xbf5a3f43,0x3f163f73,0x3f4fbe9e,0x3da1bf79,0x3f7fbe6f,0xbf73bf16,0xbe9e3f4f,0xbf263f6d,0xbf43bec4,0x3f730000,0xbe9ebf80,0x3f79bf06,0x3e6f3f5a,0xbf163f16,0x3f4f3f4f,
0xbf5d3f0a,0x3f01bf58,0xbe0cbf12,0xbf7ebf52,0xbf6b3f80,0xbecdbd71,0x3f393ea8,0xbf31bf72,0xbe5b3f22,0xbf7a3f46,0x3f7c3f75,0x3e34be95,0x3f2abe81,0xbf3f3f78,0x3edf3f4c,0x3f663f1b,
0xbf013f58,0xbf5d3f0a,0x3f7e3f52,0xbe0cbf12,0x3ecd3d71,0xbf6b3f80,0x3f313f72,0x3f393ea8,0x3f7abf46,0xbe5b3f22,0xbe343e95,0x3f7c3f75,0x3f3fbf78,0x3f2abe81,0xbf66bf1b,0x3edf3f4c,
0x3f4c3f7c,0xbf1bbe34,0x3e813e5b,0x3f78bf7a,0xbca13edf,0xbf80bf66,0x3f6ebf2a,0x3ebbbf3f,0xbf52bef1,0xbf12bf62,0x3f58bf7f,0xbf0a3dc9,0xbf72bf7e,0x3ea8be0c,0x3d71bf01,0xbf803f5d,
0x3f1b3e34,0x3f4c3f7c,0xbf783f7a,0x3e813e5b,0x3f803f66,0xbca13edf,0xbebb3f3f,0x3f6ebf2a,0x3f123f62,0xbf52bef1,0x3f0abdc9,0x3f58bf7f,0xbea83e0c,0xbf72bf7e,0x3f80bf5d,0x3d71bf01,
0xbe203f64,0xbf7dbee8,0x3f79bda1,0x3e6fbf7f,0xbee8bf7d,0x3f64be20,0xbf26bf06,0xbf433f5a,0x3f643f35,0xbee83f35,0x3da13f6d,0x3f7fbec4,0xbf7dbe20,0xbe20bf7d,0x3f06bf79,0xbf5abe6f,
0x3f7d3ee8,0xbe203f64,0xbe6f3f7f,0x3f79bda1,0xbf643e20,0xbee8bf7d,0x3f43bf5a,0xbf26bf06,0x3ee8bf35,0x3f643f35,0xbf7f3ec4,0x3da13f6d,0x3e203f7d,0xbf7dbe20,0x3f5a3e6f,0x3f06bf79,
0xbf723f39,0xbea8bf31,0x3f2abebb,0xbf3fbf6e,0x3f523e0c,0xbf123f7e,0x3e5b3f78,0x3f7a3e81,0xbca1bf62,0x3f80bef1,0xbf6bbf46,0xbecd3f22,0xbf4c3f66,0xbf1bbedf,0x3f5dbd71,0xbf01bf80,
0x3ea83f31,0xbf723f39,0x3f3f3f6e,0x3f2abebb,0x3f12bf7e,0x3f523e0c,0xbf7abe81,0x3e5b3f78,0xbf803ef1,0xbca1bf62,0x3ecdbf22,0xbf6bbf46,0x3f1b3edf,0xbf4c3f66,0x3f013f80,0x3f5dbd71,
0xbf3c3efa,0x3f2ebf5f,0xbeb1bf1e,0xbf70bf49,0xbf7e3f68,0x3df1bed6,0x3e8bbd21,0xbf76bf80,0xbf5f3f7b,0xbefa3e48,0x3f493f0e,0xbf1ebf55,0xbed63f2e,0xbf683f3c,0x3f803f70,0xbd21beb1,
0xbf2e3f5f,0xbf3c3efa,0x3f703f49,0xbeb1bf1e,0xbdf13ed6,0xbf7e3f68,0x3f763f80,0x3e8bbd21,0x3efabe48,0xbf5f3f7b,0x3f1e3f55,0x3f493f0e,0x3f68bf3c,0xbed63f2e,0x3d213eb1,0x3f803f70,
0x3f263f79,0xbf43be6f,0x3ee83e20,0x3f64bf7d,0xbf063da1,0xbf5abf7f,0x3f7dbf64,0xbe20bee8,0xbf79bf6d,0x3e6fbec4,0x3e20bf35,0xbf7d3f35,0xbda1bf26,0x3f7f3f43,0xbf643ee8,0xbee83f64,
0x3f433e6f,0x3f263f79,0xbf643f7d,0x3ee83e20,0x3f5a3f7f,0xbf063da1,0x3e203ee8,0x3f7dbf64,0xbe6f3ec4,0xbf79bf6d,0x3f7dbf35,0x3e20bf35,0xbf7fbf43,0xbda1bf26,0x3ee8bf64,0xbf643ee8,
0xbebb3f5d,0xbf6ebf01,0x3f80be0c,0x3ca1bf7e,0x3d71bf7a,0x3f803e5b,0xbf72be34,0xbea83f7c,0x3e813f7f,0xbf783dc9,0x3f4c3ef1,0x3f1bbf62,0xbf0abf6b,0x3f58becd,0xbf12bf39,0xbf523f31,
0x3f6e3f01,0xbebb3f5d,0xbca13f7e,0x3f80be0c,0xbf80be5b,0x3d71bf7a,0x3ea8bf7c,0xbf72be34,0x3f78bdc9,0x3e813f7f,0xbf1b3f62,0x3f4c3ef1,0xbf583ecd,0xbf0abf6b,0x3f52bf31,0xbf12bf39,
0xbf7e3f2e,0xbdf1bf3c,0x3efabed6,0xbf5fbf68,0x3ed63efa,0xbf683f5f,0x3f2e3f7e,0x3f3cbdf1,0x3f3cbf7b,0x3f2e3e48,0xbf68be48,0x3ed63f7b,0xbf5f3df1,0x3efabf7e,0xbdf1bf5f,0xbf7ebefa,
0x3df13f3c,0xbf7e3f2e,0x3f5f3f68,0x3efabed6,0x3f68bf5f,0x3ed63efa,0xbf3c3df1,0x3f2e3f7e,0xbf2ebe48,0x3f3cbf7b,0xbed6bf7b,0xbf68be48,0xbefa3f7e,0xbf5f3df1,0x3f7e3efa,0xbdf1bf5f,
0xbf123edf,0x3f52bf66,0xbf0abf2a,0xbf58bf3f,0xbf4c3f31,0x3f1bbf39,0xbe81becd,0xbf78bf6b,0xbf723f62,0x3ea8bef1,0x3d71bdc9,0xbf80bf7f,0xbf803f7c,0x3ca1be34,0x3ebb3e5b,0xbf6ebf7a,
0xbf523f66,0xbf123edf,0x3f583f3f,0xbf0abf2a,0xbf1b3f39,0xbf4c3f31,0x3f783f6b,0xbe81becd,0xbea83ef1,0xbf723f62,0x3f803f7f,0x3d71bdc9,0xbca13e34,0xbf803f7c,0x3f6e3f7a,0x3ebb3e5b,
0x3f803f80,0,0xbe483e48,0x3f7bbf7b,0x3f803f80,0,0xbe483e48,0x3f7bbf7b,0x3f803f80,0,0xbe483e48,0x3f7bbf7b,0x3f803f80,0,0xbe483e48,0x3f7bbf7b,
0,0x3f803f80,0xbf7b3f7b,0xbe483e48,0,0x3f803f80,0xbf7b3f7b,0xbe483e48,0,0x3f803f80,0xbf7b3f7b,0xbe483e48,0,0x3f803f80,0xbf7b3f7b,0xbe483e48,
0x3edb3f71,0xbf67beac,0x3f4ebe16,0x3f18bf7d,0xbf67beac,0xbedbbf71,0x3f18bf7d,0xbf4e3e16,0xbedbbf71,0x3f673eac,0xbf4e3e16,0xbf183f7d,0x3f673eac,0x3edb3f71,0xbf183f7d,0x3f4ebe16,
0x3f673eac,0x3edb3f71,0xbf183f7d,0x3f4ebe16,0x3edb3f71,0xbf67beac,0x3f4ebe16,0x3f18bf7d,0xbf67beac,0xbedbbf71,0x3f18bf7d,0xbf4e3e16,0xbedbbf71,0x3f673eac,0xbf4e3e16,0xbf183f7d,
0xbf223f46,0xbf46bf22,0x3f62bef1,0xbef1bf62,0x3f22bf46,0x3f463f22,0xbf623ef1,0x3ef13f62,0xbf223f46,0xbf46bf22,0x3f62bef1,0xbef1bf62,0x3f22bf46,0x3f463f22,0xbf623ef1,0x3ef13f62,
0x3f463f22,0xbf223f46,0x3ef13f62,0x3f62bef1,0xbf46bf22,0x3f22bf46,0xbef1bf62,0xbf623ef1,0x3f463f22,0xbf223f46,0x3ef13f62,0x3f62bef1,0xbf46bf22,0x3f22bf46,0xbef1bf62,0xbf623ef1,
0xbf783f04,0x3e79bf5c,0xbd49bf3e,0xbf80bf2c,0xbe793f5c,0xbf783f04,0x3f803f2c,0xbd49bf3e,0x3f78bf04,0xbe793f5c,0x3d493f3e,0x3f803f2c,0x3e79bf5c,0x3f78bf04,0xbf80bf2c,0x3d493f3e,
0xbe793f5c,0xbf783f04,0x3f803f2c,0xbd49bf3e,0x3f78bf04,0xbe793f5c,0x3d493f3e,0x3f803f2c,0x3e79bf5c,0x3f78bf04,0xbf80bf2c,0x3d493f3e,0xbf783f04,0x3e79bf5c,0xbd49bf3e,0xbf80bf2c,
0x3f7a3f7f,0xbe65bd8d,0x3cf13e02,0x3f80bf7e,0x3f5c3f6d,0xbf04bebf,0x3eacbe3e,0x3f71bf7c,0x3f283f44,0xbf41bf24,0x3f1dbef6,0x3f4bbf61,0x3ec93f08,0xbf6cbf59,0x3f53bf3a,0x3f10bf30,
0x3e653d8d,0x3f7a3f7f,0xbf803f7e,0x3cf13e02,0x3f043ebf,0x3f5c3f6d,0xbf713f7c,0x3eacbe3e,0x3f413f24,0x3f283f44,0xbf4b3f61,0x3f1dbef6,0x3f6c3f59,0x3ec93f08,0xbf103f30,0x3f53bf3a,
0x3e5b3f6b,0xbf7abecd,0x3f6bbe5b,0x3ecdbf7a,0xbf7fbf2a,0x3dc9bf3f,0x3dc9bf5d,0xbf7f3f01,0x3ecdbf01,0x3f6b3f5d,0xbf7a3f3f,0x3e5b3f2a,0x3f3f3f7a,0xbf2a3e5b,0x3f013ecd,0x3f5dbf6b,
0x3f7a3ecd,0x3e5b3f6b,0xbecd3f7a,0x3f6bbe5b,0xbdc93f3f,0xbf7fbf2a,0x3f7fbf01,0x3dc9bf5d,0xbf6bbf5d,0x3ecdbf01,0xbe5bbf2a,0xbf7a3f3f,0x3f2abe5b,0x3f3f3f7a,0xbf5d3f6b,0x3f013ecd,
0xbf4b3f3a,0xbf1dbf30,0x3f41bf08,0xbf28bf59,0x3f71bef6,0x3eac3f61,0xbf043f44,0x3f5c3f24,0xbf803e3e,0xbcf1bf7c,0x3e65bf6d,0xbf7abebf,0x3f763e02,0xbe903f7e,0x3db53f7f,0x3f7f3d8d,
0x3f1d3f30,0xbf4b3f3a,0x3f283f59,0x3f41bf08,0xbeacbf61,0x3f71bef6,0xbf5cbf24,0xbf043f44,0x3cf13f7c,0xbf803e3e,0x3f7a3ebf,0x3e65bf6d,0x3e90bf7e,0x3f763e02,0xbf7fbd8d,0x3db53f7f,
0xbf643ee8,0x3ee8bf64,0xbe8bbf49,0xbf76bf1e,0xbf353f7d,0xbf353e20,0x3f553eb1,0xbf0ebf70,0x3ee83e20,0xbf643f7d,0x3f493f80,0x3f1e3d21,0x3f7dbf64,0x3e203ee8,0xbeb13e8b,0x3f703f76,
0xbee83f64,0xbf643ee8,0x3f763f1e,0xbe8bbf49,0x3f35be20,0xbf353f7d,0x3f0e3f70,0x3f553eb1,0x3f64bf7d,0x3ee83e20,0xbf1ebd21,0x3f493f80,0xbe20bee8,0x3f7dbf64,0xbf70bf76,0xbeb13e8b,
0x3f663f7e,0xbedfbe0c,0x3e813d71,0x3f78bf80,0x3ef13f39,0xbf62bf31,0x3f46bf0a,0x3f22bf58,0xbe0c3e34,0xbf7ebf7c,0x3f80bf6e,0x3d71bebb,0xbf31bedf,0xbf39bf66,0x3f58bf78,0xbf0a3e81,
0x3edf3e0c,0x3f663f7e,0xbf783f80,0x3e813d71,0x3f623f31,0x3ef13f39,0xbf223f58,0x3f46bf0a,0x3f7e3f7c,0xbe0c3e34,0xbd713ebb,0x3f80bf6e,0x3f393f66,0xbf31bedf,0x3f0abe81,0x3f58bf78,
0xbc213f63,0xbf80beed,0x3f7cbe90,0x3e3ebf76,0xbf4ebf65,0x3f18bee4,0xbedbbf1d,0xbf673f4b,0x3f743e2a,0x3e993f7c,0xbef63f80,0x3f613cf1,0xbea33f33,0xbf73bf37,0x3f7ebf10,0xbe02bf53,
0x3f803eed,0xbc213f63,0xbe3e3f76,0x3f7cbe90,0xbf183ee4,0xbf4ebf65,0x3f67bf4b,0xbedbbf1d,0xbe99bf7c,0x3f743e2a,0xbf61bcf1,0xbef63f80,0x3f733f37,0xbea33f33,0x3e023f53,0x3f7ebf10,
0xbf683f2e,0xbed6bf3c,0x3f16bf16,0xbf4fbf4f,0x3f7bbdf1,0xbe483f7e,0x3f73,0x3f803e9e,0xbf2ebefa,0x3f3cbf5f,0xbf16bf73,0xbf4f3e9e,0x3df13f68,0xbf7e3ed6,0x3f733f16,0x3e9ebf4f,
0x3ed63f3c,0xbf683f2e,0x3f4f3f4f,0x3f16bf16,0x3e48bf7e,0x3f7bbdf1,0xbf80be9e,0x3f73,0xbf3c3f5f,0xbf2ebefa,0x3f4fbe9e,0xbf16bf73,0x3f7ebed6,0x3df13f68,0xbe9e3f4f,0x3f733f16,
0xbf443ec9,0x3f24bf6c,0xbef6bf53,0xbf61bf10,0xbf783f7a,0xbe79be65,0x3edbbcf1,0xbf67bf80,0xbebf3f41,0xbf6d3f28,0x3f7c3f4b,0xbe3ebf1d,0x3f08bdb5,0xbf593f7f,0x3f3a3f76,0x3f303e90,
0xbf243f6c,0xbf443ec9,0x3f613f10,0xbef6bf53,0x3e793e65,0xbf783f7a,0x3f673f80,0x3edbbcf1,0x3f6dbf28,0xbebf3f41,0x3e3e3f1d,0x3f7c3f4b,0x3f59bf7f,0x3f08bdb5,0xbf30be90,0x3f3a3f76,
0x3f473f7b,0xbf20be52,0x3eedbc21,0x3f63bf80,0xbd493ed2,0xbf80bf6a,0x3f7dbf51,0x3e16bf14,0xbf56beff,0xbf0cbf5e,0x3f33bf73,0xbf373ea3,0xbf6fbf7f,0x3eb6bddd,0xbe2abe99,0xbf7c3f74,
0x3f203e52,0x3f473f7b,0xbf633f80,0x3eedbc21,0x3f803f6a,0xbd493ed2,0xbe163f14,0x3f7dbf51,0x3f0c3f5e,0xbf56beff,0x3f37bea3,0x3f33bf73,0xbeb63ddd,0xbf6fbf7f,0x3f7cbf74,0xbe2abe99,
0xbe6f3f5a,0xbf79bf06,0x3f80beb1,0xbd21bf70,0xbec4bf7f,0x3f6dbda1,0xbf55be8b,0xbf0e3f76,0x3f5a3f43,0xbf063f26,0x3eb13f49,0x3f70bf1e,0xbf7fbe6f,0xbda1bf79,0x3e8bbf80,0xbf763d21,
0x3f793f06,0xbe6f3f5a,0x3d213f70,0x3f80beb1,0xbf6d3da1,0xbec4bf7f,0x3f0ebf76,0xbf55be8b,0x3f06bf26,0x3f5a3f43,0xbf703f1e,0x3eb13f49,0x3da13f79,0xbf7fbe6f,0x3f76bd21,0x3e8bbf80,
0xbf7b3f20,0xbe52bf47,0x3ec9bf24,0xbf6cbf44,0x3f3e3e86,0xbf2c3f77,0x3f043f7f,0x3f5cbd8d,0x3dddbf6f,0x3f7fbeb6,0xbf7fbf08,0xbdb53f59,0xbf5e3f56,0xbeffbf0c,0x3f28bebf,0xbf41bf6d,
0x3e523f47,0xbf7b3f20,0x3f6c3f44,0x3ec9bf24,0x3f2cbf77,0x3f3e3e86,0xbf5c3d8d,0x3f043f7f,0xbf7f3eb6,0x3dddbf6f,0x3db5bf59,0xbf7fbf08,0x3eff3f0c,0xbf5e3f56,0x3f413f6d,0x3f28bebf,
0xbf1b3ea8,0x3f4cbf72,0xbf2abf5d,0xbf3fbf01,0xbf753f52,0x3e95bf12,0xbdc9becd,0xbf7fbf6b,0xbf723f80,0xbea83ca1,0x3f013e5b,0xbf5dbf7a,0xbf123f4c,0xbf523f1b,0x3f6b3f3f,0xbecdbf2a,
0xbf4c3f72,0xbf1b3ea8,0x3f3f3f01,0xbf2abf5d,0xbe953f12,0xbf753f52,0x3f7f3f6b,0xbdc9becd,0x3ea8bca1,0xbf723f80,0x3f5d3f7a,0x3f013e5b,0x3f52bf1b,0xbf123f4c,0x3ecd3f2a,0x3f6b3f3f,
0x3f1e3f76,0xbf49be8b,0x3f26bda1,0x3f43bf7f,0xbf0e3d21,0xbf55bf80,0x3f6dbf79,0xbec4be6f,0xbf76bf70,0x3e8bbeb1,0xbda1bf06,0xbf7f3f5a,0xbd21bf1e,0x3f803f49,0xbf793f26,0xbe6f3f43,
0x3f493e8b,0x3f1e3f76,0xbf433f7f,0x3f26bda1,0x3f553f80,0xbf0e3d21,0x3ec43e6f,0x3f6dbf79,0xbe8b3eb1,0xbf76bf70,0x3f7fbf5a,0xbda1bf06,0xbf80bf49,0xbd21bf1e,0x3e6fbf43,0xbf793f26,
0xbee43f51,0xbf65bf14,0x3f77bed2,0xbe86bf6a,0x3e16bf74,0x3f7d3e99,0xbf803ddd,0xbd493f7f,0x3e2a3f80,0xbf7c3c21,0x3f6f3e52,0x3eb6bf7b,0xbeedbf73,0x3f63bea3,0xbf47beff,0xbf203f5e,
0x3f653f14,0xbee43f51,0x3e863f6a,0x3f77bed2,0xbf7dbe99,0x3e16bf74,0x3d49bf7f,0xbf803ddd,0x3f7cbc21,0x3e2a3f80,0xbeb63f7b,0x3f6f3e52,0xbf633ea3,0xbeedbf73,0x3f20bf5e,0xbf47beff,
0xbf803f12,0x3ca1bf52,0x3e34bf31,0xbf7cbf39,0x3e953f1b,0xbf753f4c,0x3f623f66,0x3ef1bedf,0x3f52bf72,0x3f123ea8,0xbf393e0c,0x3f313f7e,0xbf4cbca1,0x3f1bbf80,0xbedfbf7c,0xbf66be34,
0xbca13f52,0xbf803f12,0x3f7c3f39,0x3e34bf31,0x3f75bf4c,0x3e953f1b,0xbef13edf,0x3f623f66,0xbf12bea8,0x3f52bf72,0xbf31bf7e,0xbf393e0c,0xbf1b3f80,0xbf4cbca1,0x3f663e34,0xbedfbf7c,
0xbed23e86,0x3f6abf77,0xbf51bf65,0xbf14bee4,0xbf2c3f0c,0x3f3ebf56,0xbf18bf37,0xbf4ebf33,0xbf5e3f47,0x3effbf20,0xbea3beed,0xbf73bf63,0xbf7b3f6f,0x3e52beb6,0xbc21be2a,0xbf80bf7c,
0xbf6a3f77,0xbed23e86,0x3f143ee4,0xbf51bf65,0xbf3e3f56,0xbf2c3f0c,0x3f4e3f33,0xbf18bf37,0xbeff3f20,0xbf5e3f47,0x3f733f63,0xbea3beed,0xbe523eb6,0xbf7b3f6f,0x3f803f7c,0xbc21be2a,
0x3f80,0x3f80,0x3f80,0x3f80,0x3f80,0xbf80,0x3f80,0xbf80,0x3f80,0x3f80,0x3f80,0x3f80,0x3f80,0xbf80,0x3f80,0xbf80,
0x3f80,0x3f80,0x3f800000,0x3f800000,0x3ec43f6d,0xbec4bf6d,0x3f6dbec4,0xbf6d3ec4,0x3f353f35,0x3f353f35,0x3f35bf35,0x3f35bf35,0x3f6d3ec4,0xbf6dbec4,0x3ec4bf6d,0xbec43f6d,
0x3f80,0x3f80,0xbf80,0xbf80,0x3f353f35,0xbf35bf35,0xbf35bf35,0x3f353f35,0x3f800000,0x3f800000,0xbf800000,0xbf800000,0x3f35bf35,0xbf353f35,0xbf353f35,0x3f35bf35,
0x3f80,0x3f80,0xbf800000,0xbf800000,0x3f6d3ec4,0xbf6dbec4,0xbec43f6d,0x3ec4bf6d,0x3f35bf35,0x3f35bf35,0x3f353f35,0x3f353f35,0xbec4bf6d,0x3ec43f6d,0x3f6dbec4,0xbf6d3ec4,
0x3f80,0x3f80,0x3f80,0x3f80,0x3f800000,0xbf800000,0x3f800000,0xbf800000,0xbf80,0xbf80,0xbf80,0xbf80,0xbf800000,0x3f800000,0xbf800000,0x3f800000,
0x3f80,0x3f80,0x3f800000,0x3f800000,0x3f6dbec4,0xbf6d3ec4,0xbec4bf6d,0x3ec43f6d,0xbf35bf35,0xbf35bf35,0xbf353f35,0xbf353f35,0xbec43f6d,0x3ec4bf6d,0x3f6d3ec4,0xbf6dbec4,
0x3f80,0x3f80,0xbf80,0xbf80,0x3f35bf35,0xbf353f35,0xbf353f35,0x3f35bf35,0xbf800000,0xbf800000,0x3f800000,0x3f800000,0x3f353f35,0xbf35bf35,0xbf35bf35,0x3f353f35,
0x3f80,0x3f80,0xbf800000,0xbf800000,0x3ec4bf6d,0xbec43f6d,0x3f6d3ec4,0xbf6dbec4,0xbf353f35,0xbf353f35,0xbf35bf35,0xbf35bf35,0x3f6dbec4,0xbf6d3ec4,0x3ec43f6d,0xbec4bf6d,
0x3f80,0x3f80,0x3f80,0x3f80,0x3f80,0xbf80,0x3f80,0xbf80,0x3f80,0x3f80,0x3f80,0x3f80,0x3f80,0xbf80,0x3f80,0xbf80,
0xbf80,0xbf80,0xbf800000,0xbf800000,0xbec4bf6d,0x3ec43f6d,0xbf6d3ec4,0x3f6dbec4,0xbf35bf35,0xbf35bf35,0xbf353f35,0xbf353f35,0xbf6dbec4,0x3f6d3ec4,0xbec43f6d,0x3ec4bf6d,
0x3f80,0x3f80,0xbf80,0xbf80,0x3f353f35,0xbf35bf35,0xbf35bf35,0x3f353f35,0x3f800000,0x3f800000,0xbf800000,0xbf800000,0x3f35bf35,0xbf353f35,0xbf353f35,0x3f35bf35,
0xbf80,0xbf80,0x3f800000,0x3f800000,0xbf6dbec4,0x3f6d3ec4,0x3ec4bf6d,0xbec43f6d,0xbf353f35,0xbf353f35,0xbf35bf35,0xbf35bf35,0x3ec43f6d,0xbec4bf6d,0xbf6d3ec4,0x3f6dbec4,
0x3f80,0x3f80,0x3f80,0x3f80,0x3f800000,0xbf800000,0x3f800000,0xbf800000,0xbf80,0xbf80,0xbf80,0xbf80,0xbf800000,0x3f800000,0xbf800000,0x3f800000,
0xbf80,0xbf80,0xbf800000,0xbf800000,0xbf6d3ec4,0x3f6dbec4,0x3ec43f6d,0xbec4bf6d,0x3f353f35,0x3f353f35,0x3f35bf35,0x3f35bf35,0x3ec4bf6d,0xbec43f6d,0xbf6dbec4,0x3f6d3ec4,
0x3f80,0x3f80,0xbf80,0xbf80,0x3f35bf35,0xbf353f35,0xbf353f35,0x3f35bf35,0xbf800000,0xbf800000,0x3f800000,0x3f800000,0x3f353f35,0xbf35bf35,0xbf35bf35,0x3f353f35,
0xbf80,0xbf80,0x3f800000,0x3f800000,0xbec43f6d,0x3ec4bf6d,0xbf6dbec4,0x3f6d3ec4,0x3f35bf35,0x3f35bf35,0x3f353f35,0x3f353f35,0xbf6d3ec4,0x3f6dbec4,0xbec4bf6d,0x3ec43f6d,
0x3f800000,0x3f800000,0x3f800000,0x3f800000,0x3f800000,0xbf800000,0x3f800000,0xbf800000,0x3f800000,0x3f800000,0x3f800000,0x3f800000,0x3f800000,0xbf800000,0x3f800000,0xbf800000,
0x3f800000,0x3f800000,0xbf80,0xbf80,0x3f6dbec4,0xbf6d3ec4,0xbec4bf6d,0x3ec43f6d,0x3f35bf35,0x3f35bf35,0xbf35bf35,0xbf35bf35,0x3ec4bf6d,0xbec43f6d,0xbf6dbec4,0x3f6d3ec4,
0x3f800000,0x3f800000,0xbf800000,0xbf800000,0x3f35bf35,0xbf353f35,0xbf353f35,0x3f35bf35,0xbf80,0xbf80,0x3f80,0x3f80,0xbf35bf35,0x3f353f35,0x3f353f35,0xbf35bf35,
0x3f800000,0x3f800000,0x3f80,0x3f80,0x3ec4bf6d,0xbec43f6d,0x3f6d3ec4,0xbf6dbec4,0xbf35bf35,0xbf35bf35,0x3f35bf35,0x3f35bf35,0xbf6d3ec4,0x3f6dbec4,0xbec4bf6d,0x3ec43f6d,
0x3f800000,0x3f800000,0x3f800000,0x3f800000,0xbf80,0x3f80,0xbf80,0x3f80,0xbf800000,0xbf800000,0xbf800000,0xbf800000,0x3f80,0xbf80,0x3f80,0xbf80,
0x3f800000,0x3f800000,0xbf80,0xbf80,0xbec4bf6d,0x3ec43f6d,0xbf6d3ec4,0x3f6dbec4,0xbf353f35,0xbf353f35,0x3f353f35,0x3f353f35,0x3f6d3ec4,0xbf6dbec4,0x3ec4bf6d,0xbec43f6d,
0x3f800000,0x3f800000,0xbf800000,0xbf800000,0xbf35bf35,0x3f353f35,0x3f353f35,0xbf35bf35,0x3f80,0x3f80,0xbf80,0xbf80,0x3f35bf35,0xbf353f35,0xbf353f35,0x3f35bf35,
0x3f800000,0x3f800000,0x3f80,0x3f80,0xbf6dbec4,0x3f6d3ec4,0x3ec4bf6d,0xbec43f6d,0x3f353f35,0x3f353f35,0xbf353f35,0xbf353f35,0xbec4bf6d,0x3ec43f6d,0x3f6dbec4,0xbf6d3ec4,
0x3f800000,0x3f800000,0x3f800000,0x3f800000,0x3f800000,0xbf800000,0x3f800000,0xbf800000,0x3f800000,0x3f800000,0x3f800000,0x3f800000,0x3f800000,0xbf800000,0x3f800000,0xbf800000,
0xbf800000,0xbf800000,0x3f80,0x3f80,0xbf6d3ec4,0x3f6dbec4,0x3ec43f6d,0xbec4bf6d,0xbf353f35,0xbf353f35,0x3f353f35,0x3f353f35,0xbec43f6d,0x3ec4bf6d,0x3f6d3ec4,0xbf6dbec4,
0x3f800000,0x3f800000,0xbf800000,0xbf800000,0x3f35bf35,0xbf353f35,0xbf353f35,0x3f35bf35,0xbf80,0xbf80,0x3f80,0x3f80,0xbf35bf35,0x3f353f35,0x3f353f35,0xbf35bf35,
0xbf800000,0xbf800000,0xbf80,0xbf80,0xbec43f6d,0x3ec4bf6d,0xbf6dbec4,0x3f6d3ec4,0x3f353f35,0x3f353f35,0xbf353f35,0xbf353f35,0x3f6dbec4,0xbf6d3ec4,0x3ec43f6d,0xbec4bf6d,
0x3f800000,0x3f800000,0x3f800000,0x3f800000,0xbf80,0x3f80,0xbf80,0x3f80,0xbf800000,0xbf800000,0xbf800000,0xbf800000,0x3f80,0xbf80,0x3f80,0xbf80,
0xbf800000,0xbf800000,0x3f80,0x3f80,0x3ec43f6d,0xbec4bf6d,0x3f6dbec4,0xbf6d3ec4,0x3f35bf35,0x3f35bf35,0xbf35bf35,0xbf35bf35,0xbf6dbec4,0x3f6d3ec4,0xbec43f6d,0x3ec4bf6d,
0x3f800000,0x3f800000,0xbf800000,0xbf800000,0xbf35bf35,0x3f353f35,0x3f353f35,0xbf35bf35,0x3f80,0x3f80,0xbf80,0xbf80,0x3f35bf35,0xbf353f35,0xbf353f35,0x3f35bf35,
0xbf800000,0xbf800000,0xbf80,0xbf80,0x3f6d3ec4,0xbf6dbec4,0xbec43f6d,0x3ec4bf6d,0xbf35bf35,0xbf35bf35,0x3f35bf35,0x3f35bf35,0x3ec43f6d,0xbec4bf6d,0xbf6d3ec4,0x3f6dbec4,
0x3f803f80,0xbf803f80,0x3f803f80,0xbf803f80,0x3f803f80,0xbf803f80,0x3f803f80,0xbf803f80,0x3f803f80,0xbf803f80,0x3f803f80,0xbf803f80,0x3f803f80,0xbf803f80,0x3f803f80,0xbf803f80,
0x3f6d3f80,0xbf6d3f80,0xbf6dbf80,0x3f6dbf80,0x3ec43f35,0xbec43f35,0xbec4bf35,0x3ec4bf35,0xbec40000,0x3ec40000,0x3ec40000,0xbec40000,0xbf6dbf35,0x3f6dbf35,0x3f6d3f35,0xbf6d3f35,
0x3f353f80,0xbf353f80,0x3f353f80,0xbf353f80,0xbf350000,0x3f350000,0xbf350000,0x3f350000,0xbf35bf80,0x3f35bf80,0xbf35bf80,0x3f35bf80,0x3f350000,0xbf350000,0x3f350000,0xbf350000,
0x3ec43f80,0xbec43f80,0xbec4bf80,0x3ec4bf80,0xbf6dbf35,0x3f6dbf35,0x3f6d3f35,0xbf6d3f35,0x3f6d0000,0xbf6d0000,0xbf6d0000,0x3f6d0000,0xbec43f35,0x3ec43f35,0x3ec4bf35,0xbec4bf35,
0x3f80,0x3f80,0x3f80,0x3f80,0xbf80,0xbf80,0xbf80,0xbf80,0x3f80,0x3f80,0x3f80,0x3f80,0xbf80,0xbf80,0xbf80,0xbf80,
0xbec43f80,0x3ec43f80,0x3ec4bf80,0xbec4bf80,0x3f6dbf35,0xbf6dbf35,0xbf6d3f35,0x3f6d3f35,0xbf6d0000,0x3f6d0000,0x3f6d0000,0xbf6d0000,0x3ec43f35,0xbec43f35,0xbec4bf35,0x3ec4bf35,
0xbf353f80,0x3f353f80,0xbf353f80,0x3f353f80,0x3f350000,0xbf350000,0x3f350000,0xbf350000,0x3f35bf80,0xbf35bf80,0x3f35bf80,0xbf35bf80,0xbf350000,0x3f350000,0xbf350000,0x3f350000,
0xbf6d3f80,0x3f6d3f80,0x3f6dbf80,0xbf6dbf80,0xbec43f35,0x3ec43f35,0x3ec4bf35,0xbec4bf35,0x3ec40000,0xbec40000,0xbec40000,0x3ec40000,0x3f6dbf35,0xbf6dbf35,0xbf6d3f35,0x3f6d3f35,
0,0,0,0,0,0,0,0,0,0,0,0,0,0,0,0,
0x3ec40000,0xbec40000,0xbec40000,0x3ec40000,0x3f6d3f35,0xbf6d3f35,0xbf6dbf35,0x3f6dbf35,0x3f6d3f80,0xbf6d3f80,0xbf6dbf80,0x3f6dbf80,0x3ec43f35,0xbec43f35,0xbec4bf35,0x3ec4bf35,
0x3f350000,0xbf350000,0x3f350000,0xbf350000,0x3f353f80,0xbf353f80,0x3f353f80,0xbf353f80,0xbf350000,0x3f350000,0xbf350000,0x3f350000,0xbf35bf80,0x3f35bf80,0xbf35bf80,0x3f35bf80,
0x3f6d0000,0xbf6d0000,0xbf6d0000,0x3f6d0000,0xbec43f35,0x3ec43f35,0x3ec4bf35,0xbec4bf35,0xbec4bf80,0x3ec4bf80,0x3ec43f80,0xbec43f80,0x3f6d3f35,0xbf6d3f35,0xbf6dbf35,0x3f6dbf35,
0x3f800000,0xbf800000,0x3f800000,0xbf800000,0xbf800000,0x3f800000,0xbf800000,0x3f800000,0x3f800000,0xbf800000,0x3f800000,0xbf800000,0xbf800000,0x3f800000,0xbf800000,0x3f800000,
0x3f6d0000,0xbf6d0000,0xbf6d0000,0x3f6d0000,0xbec4bf35,0x3ec4bf35,0x3ec43f35,0xbec43f35,0xbec43f80,0x3ec43f80,0x3ec4bf80,0xbec4bf80,0x3f6dbf35,0xbf6dbf35,0xbf6d3f35,0x3f6d3f35,
0x3f350000,0xbf350000,0x3f350000,0xbf350000,0x3f35bf80,0xbf35bf80,0x3f35bf80,0xbf35bf80,0xbf350000,0x3f350000,0xbf350000,0x3f350000,0xbf353f80,0x3f353f80,0xbf353f80,0x3f353f80,
0x3ec40000,0xbec40000,0xbec40000,0x3ec40000,0x3f6dbf35,0xbf6dbf35,0xbf6d3f35,0x3f6d3f35,0x3f6dbf80,0xbf6dbf80,0xbf6d3f80,0x3f6d3f80,0x3ec4bf35,0xbec4bf35,0xbec43f35,0x3ec43f35,
0,0,0,0,0,0,0,0,0,0,0,0,0,0,0,0,
0xbec40000,0x3ec40000,0x3ec40000,0xbec40000,0xbf6dbf35,0x3f6dbf35,0x3f6d3f35,0xbf6d3f35,0xbf6dbf80,0x3f6dbf80,0x3f6d3f80,0xbf6d3f80,0xbec4bf35,0x3ec4bf35,0x3ec43f35,0xbec43f35,
0xbf350000,0x3f350000,0xbf350000,0x3f350000,0xbf35bf80,0x3f35bf80,0xbf35bf80,0x3f35bf80,0x3f350000,0xbf350000,0x3f350000,0xbf350000,0x3f353f80,0xbf353f80,0x3f353f80,0xbf353f80,
0xbf6d0000,0x3f6d0000,0x3f6d0000,0xbf6d0000,0x3ec4bf35,0xbec4bf35,0xbec43f35,0x3ec43f35,0x3ec43f80,0xbec43f80,0xbec4bf80,0x3ec4bf80,0xbf6dbf35,0x3f6dbf35,0x3f6d3f35,0xbf6d3f35,
0xbf800000,0x3f800000,0xbf800000,0x3f800000,0x3f800000,0xbf800000,0x3f800000,0xbf800000,0xbf800000,0x3f800000,0xbf800000,0x3f800000,0x3f800000,0xbf800000,0x3f800000,0xbf800000,
0xbf6d0000,0x3f6d0000,0x3f6d0000,0xbf6d0000,0x3ec43f35,0xbec43f35,0xbec4bf35,0x3ec4bf35,0x3ec4bf80,0xbec4bf80,0xbec43f80,0x3ec43f80,0xbf6d3f35,0x3f6d3f35,0x3f6dbf35,0xbf6dbf35,
0xbf350000,0x3f350000,0xbf350000,0x3f350000,0xbf353f80,0x3f353f80,0xbf353f80,0x3f353f80,0x3f350000,0xbf350000,0x3f350000,0xbf350000,0x3f35bf80,0xbf35bf80,0x3f35bf80,0xbf35bf80,
0xbec40000,0x3ec40000,0x3ec40000,0xbec40000,0xbf6d3f35,0x3f6d3f35,0x3f6dbf35,0xbf6dbf35,0xbf6d3f80,0x3f6d3f80,0x3f6dbf80,0xbf6dbf80,0xbec43f35,0x3ec43f35,0x3ec4bf35,0xbec4bf35,
0x3f800000,0x3f800000,0x3f800000,0x3f6c835e,0x3f800000,0x3f800000,0x3f3504f3,0x3ec3ef15,0x3f800000,0x3f800000,0,0xbec3ef15,0x3f800000,0x3f800000,0xbf3504f3,0xbf6c835e,
0x3f800000,0x3f7fb10f,0x3f800000,0x3f676bd8,0x3f7ec46d,0x3f7d3aac,0x3f226799,0x3e78cfcc,0x3f7b14be,0x3f7853f8,0xbe47c5c2,0xbf187fc0,0x3f74fa0b,0x3f710908,0xbf61c598,0xbf7fb10f,
0x3f800000,0x3f7ec46d,0x3f800000,0x3f61c598,0x3f7b14be,0x3f74fa0b,0x3f0e39da,0x3dc8bd36,0x3f6c835e,0x3f61c598,0xbec3ef15,0xbf45e403,0x3f54db31,0x3f45e403,0xbf7b14be,0xbf74fa0b,
0x3f800000,0x3f7d3aac,0x3f800000,0x3f5b941a,0x3f74fa0b,0x3f676bd8,0x3ef15aea,0xbd48fb30,0x3f54db31,0x3f3daef9,0xbf0e39da,0xbf676bd8,0x3f226799,0x3f039c3d,0xbf7ec46d,0xbf4d9f02,
0x3f800000,0x3f7b14be,0x3f800000,0x3f54db31,0x3f6c835e,0x3f54db31,0x3ec3ef15,0xbe47c5c2,0x3f3504f3,0x3f0e39da,0xbf3504f3,0xbf7b14be,0x3ec3ef15,0x3e47c5c2,0xbf6c835e,0xbf0e39da,
0x3f800000,0x3f7853f8,0x3f800000,0x3f4d9f02,0x3f61c598,0x3f3daef9,0x3e94a031,0xbeac7cd4,0x3f0e39da,0x3eac7cd4,0xbf54db31,0xbf7fb10f,0x3dc8bd36,0xbe164083,0xbf45e403,0xbe78cfcc,
0x3f800000,0x3f74fa0b,0x3f800000,0x3f45e403,0x3f54db31,0x3f226799,0x3e47c5c2,0xbef15aea,0x3ec3ef15,0x3dc8bd36,0xbf6c835e,0xbf74fa0b,0xbe47c5c2,0xbef15aea,0xbf0e39da,0x3dc8bd36,
0x3f800000,0x3f710908,0x3f800000,0x3f3daef9,0x3f45e403,0x3f039c3d,0x3dc8bd36,0xbf187fc0,0x3e47c5c2,0xbe164083,0xbf7b14be,0xbf5b941a,0xbef15aea,0xbf3daef9,0xbe94a031,0x3edae880,
0,0,0,0x3ec3ef15,0,0,0x3f3504f3,0x3f6c835e,0,0,0x3f800000,0x3f6c835e,0,0,0x3f3504f3,0x3ec3ef15,
0,0x3d48fb30,0,0x3edae880,0x3dc8bd36,0x3e164083,0x3f45e403,0x3f7853f8,0x3e47c5c2,0x3e78cfcc,0x3f7b14be,0x3f4d9f02,0x3e94a031,0x3eac7cd4,0x3ef15aea,0x3d48fb30,
0,0x3dc8bd36,0,0x3ef15aea,0x3e47c5c2,0x3e94a031,0x3f54db31,0x3f7ec46d,0x3ec3ef15,0x3ef15aea,0x3f6c835e,0x3f226799,0x3f0e39da,0x3f226799,0x3e47c5c2,0xbe94a031,
0,0x3e164083,0,0x3f039c3d,0x3e94a031,0x3edae880,0x3f61c598,0x3f7fb10f,0x3f0e39da,0x3f2beb4a,0x3f54db31,0x3edae880,0x3f45e403,0x3f5b941a,0xbdc8bd36,0xbf187fc0,
0,0x3e47c5c2,0,0x3f0e39da,0x3ec3ef15,0x3f0e39da,0x3f6c835e,0x3f7b14be,0x3f3504f3,0x3f54db31,0x3f3504f3,0x3e47c5c2,0x3f6c835e,0x3f7b14be,0xbec3ef15,0xbf54db31,
0,0x3e78cfcc,0,0x3f187fc0,0x3ef15aea,0x3f2beb4a,0x3f74fa0b,0x3f710908,0x3f54db31,0x3f710908,0x3f0e39da,0xbd48fb30,0x3f7ec46d,0x3f7d3aac,0xbf226799,0xbf7853f8,
0,0x3e94a031,0,0x3f226799,0x3f0e39da,0x3f45e403,0x3f7b14be,0x3f61c598,0x3f6c835e,0x3f7ec46d,0x3ec3ef15,0xbe94a031,0x3f7b14be,0x3f61c598,0xbf54db31,0xbf7ec46d,
0,0x3eac7cd4,0,0x3f2beb4a,0x3f226799,0x3f5b941a,0x3f7ec46d,0x3f4d9f02,0x3f7b14be,0x3f7d3aac,0x3e47c5c2,0xbf039c3d,0x3f61c598,0x3f2beb4a,0xbf74fa0b,0xbf676bd8,
0x354ccccd,0x354ccccd,0x354ccccd,0x354ccccd,0x354ccccd,0x354ccccd,0x354ccccd,0x354ccccd,0x354ccccd,0x354ccccd,0x354ccccd,0x354ccccd,0x354ccccd,0x354ccccd,0x354ccccd,0x354ccccd,
0x354ccccd,0x3548dd65,0,0xb41fd168,0x353d35e5,0x352a48f4,0xb49cbf44,0xb4e38fc3,0x3510d0c3,0x34e38fc3,0xb510d0c3,0xb52a48f4,0x349cbf44,0x341fd168,0xb53d35e5,0xb548dd65,
0x354ccccd,0x354c8da6,0x353d35e5,0x35392313,0x354bd057,0x354a9556,0x35349e13,0x352fa9af,0x3548dd65,0x3546a993,0x352a48f4,0x35247f35,0x3543fb3c,0x3540d407,0x351e5003,0x3517bf2e,
0x354ccccd,0x3546a993,0xb49cbf44,0xb4f3ff99,0x35349e13,0x3517bf2e,0xb51e5003,0xb5392313,0x34e38fc3,0x3489fd76,0xb548dd65,0xb54c8da6,0x33a0975e,0xb3f06739,0xb543fb3c,0xb52fa9af,
0x354ccccd,0x354bd057,0x3510d0c3,0x3501ec7b,0x3548dd65,0x3543fb3c,0x34e38fc3,0x34c11588,0x353d35e5,0x35349e13,0x349cbf44,0x346dcd1c,0x352a48f4,0x351e5003,0x341fd168,0x33a0975e,
0x354ccccd,0x3543fb3c,0xb510d0c3,0xb5349e13,0x352a48f4,0x3501ec7b,0xb548dd65,0xb54bd057,0x349cbf44,0x33a0975e,0xb53d35e5,0xb51e5003,0xb41fd168,0xb4c11588,0xb4e38fc3,0xb46dcd1c,
0x354ccccd,0x354a9556,0x349cbf44,0x34470ca3,0x3543fb3c,0x35392313,0x33a0975e,0xb320c8f3,0x352a48f4,0x3517bf2e,0xb41fd168,0xb489fd76,0x3501ec7b,0x34d29394,0xb4c11588,0xb4f3ff99,
0x354ccccd,0x3540d407,0xb53d35e5,0xb54c8da6,0x351e5003,0x34d29394,0xb543fb3c,0xb5247f35,0x341fd168,0xb3f06739,0xb4e38fc3,0xb4470ca3,0xb4c11588,0xb517bf2e,0x33a0975e,0x34af2067,
0,0,0,0,0,0,0,0,0,0,0,0,0,0,0,0,
0,0x341fd168,0x354ccccd,0x3548dd65,0x349cbf44,0x34e38fc3,0x353d35e5,0x352a48f4,0x3510d0c3,0x352a48f4,0x3510d0c3,0x34e38fc3,0x353d35e5,0x3548dd65,0x349cbf44,0x341fd168,
0,0x3320c8f3,0x349cbf44,0x34af2067,0x33a0975e,0x33f06739,0x34c11588,0x34d29394,0x341fd168,0x34470ca3,0x34e38fc3,0x34f3ff99,0x346dcd1c,0x3489fd76,0x3501ec7b,0x35098908,
0,0x34470ca3,0x353d35e5,0x35247f35,0x34c11588,0x35098908,0x3501ec7b,0x34af2067,0x352a48f4,0x3540d407,0x341fd168,0xb320c8f3,0x354bd057,0x354a9556,0xb46dcd1c,0xb4d29394,
0,0x33a0975e,0x3510d0c3,0x351e5003,0x341fd168,0x346dcd1c,0x352a48f4,0x35349e13,0x349cbf44,0x34c11588,0x353d35e5,0x3543fb3c,0x34e38fc3,0x3501ec7b,0x3548dd65,0x354bd057,
0,0x346dcd1c,0x3510d0c3,0x34c11588,0x34e38fc3,0x351e5003,0x341fd168,0xb3a0975e,0x353d35e5,0x354bd057,0xb49cbf44,0xb501ec7b,0x3548dd65,0x35349e13,0xb52a48f4,0xb543fb3c,
0,0x33f06739,0x353d35e5,0x3546a993,0x346dcd1c,0x34af2067,0x354bd057,0x354c8da6,0x34e38fc3,0x35098908,0x3548dd65,0x3540d407,0x351e5003,0x352fa9af,0x35349e13,0x35247f35,
0,0x3489fd76,0x349cbf44,0x3320c8f3,0x3501ec7b,0x352fa9af,0xb46dcd1c,0xb4f3ff99,0x3548dd65,0x354a9556,0xb52a48f4,0xb546a993,0x35349e13,0x35098908,0xb54bd057,0xb5392313,
0x3f80,0x3f80,0x3dc93f7f,0x3dc93f7f,0x3cc93f80,0xbcc9bf80,0x3dfb3f7e,0xbdfbbf7e,0x3d493f80,0x3d493f80,0x3e163f7d,0x3e163f7d,0x3d973f7f,0xbd97bf7f,0x3e2f3f7c,0xbe2fbf7c,
0x3f80,0x3f80,0x3f7fbdc9,0x3f7fbdc9,0x3ecf3f6a,0xbecfbf6a,0x3f5fbefc,0xbf5f3efc,0x3f3e3f2c,0x3f3e3f2c,0x3f18bf4e,0x3f18bf4e,0x3f733ea1,0xbf73bea1,0x3e60bf7a,0xbe603f7a,
0x3f80,0x3f80,0xbdc9bf7f,0xbdc9bf7f,0x3f393f31,0xbf39bf31,0xbf4abf1d,0x3f4a3f1d,0x3f80bd49,0x3f80bd49,0xbf7d3e16,0xbf7d3e16,0x3f27bf42,0xbf273f42,0xbf133f51,0x3f13bf51,
0x3f80,0x3f80,0xbf7f3dc9,0xbf7f3dc9,0x3f6f3eb8,0xbf6fbeb8,0xbe893f77,0x3e89bf77,0x3f2cbf3e,0x3f2cbf3e,0x3f4e3f18,0x3f4e3f18,0xbee6bf65,0x3ee63f65,0x3f58bf09,0xbf583f09,
0x3f80,0x3f80,0x3dc93f7f,0x3dc93f7f,0x3f80bcc9,0xbf803cc9,0x3f7ebdfb,0xbf7e3dfb,0xbd49bf80,0xbd49bf80,0xbe16bf7d,0xbe16bf7d,0xbf7f3d97,0x3f7fbd97,0xbf7c3e2f,0x3f7cbe2f,
0x3f80,0x3f80,0x3f7fbdc9,0x3f7fbdc9,0x3f6abecf,0xbf6a3ecf,0xbefcbf5f,0x3efc3f5f,0xbf3ebf2c,0xbf3ebf2c,0xbf183f4e,0xbf183f4e,0xbea13f73,0x3ea1bf73,0x3f7a3e60,0xbf7abe60,
0x3f80,0x3f80,0xbdc9bf7f,0xbdc9bf7f,0x3f31bf39,0xbf313f39,0xbf1d3f4a,0x3f1dbf4a,0xbf803d49,0xbf803d49,0x3f7dbe16,0x3f7dbe16,0x3f423f27,0xbf42bf27,0xbf51bf13,0x3f513f13,
0x3f80,0x3f80,0xbf7f3dc9,0xbf7f3dc9,0x3eb8bf6f,0xbeb83f6f,0x3f773e89,0xbf77be89,0xbf2c3f3e,0xbf2c3f3e,0xbf4ebf18,0xbf4ebf18,0x3f65bee6,0xbf653ee6,0x3f093f58,0xbf09bf58,
0x3e483f7b,0x3e483f7b,0x3e953f75,0x3e953f75,0x3e603f7a,0xbe60bf7a,0x3ea13f73,0xbea1bf73,0x3e793f78,0x3e793f78,0x3eac3f71,0x3eac3f71,0x3e893f77,0xbe89bf77,0x3eb83f6f,0xbeb8bf6f,
0xbe48bf7b,0xbe48bf7b,0xbf753e95,0xbf753e95,0xbf13bf51,0x3f133f51,0xbf423f27,0x3f42bf27,0xbf5cbf04,0xbf5cbf04,0xbedb3f67,0xbedb3f67,0xbf7ebdfb,0x3f7e3dfb,0xbcc93f80,0x3cc9bf80,
0x3e483f7b,0x3e483f7b,0xbe95bf75,0xbe95bf75,0x3f583f09,0xbf58bf09,0xbf65bee6,0x3f653ee6,0x3f78be79,0x3f78be79,0xbf713eac,0xbf713eac,0x3efcbf5f,0xbefc3f5f,0xbecf3f6a,0x3ecfbf6a,
0xbe48bf7b,0xbe48bf7b,0x3f75be95,0x3f75be95,0xbf7cbe2f,0x3f7c3e2f,0x3d97bf7f,0xbd973f7f,0xbf043f5c,0xbf043f5c,0xbf67bedb,0xbf67bedb,0x3f1d3f4a,0xbf1dbf4a,0xbf393f31,0x3f39bf31,
0x3e483f7b,0x3e483f7b,0x3e953f75,0x3e953f75,0x3f7abe60,0xbf7a3e60,0x3f73bea1,0xbf733ea1,0xbe79bf78,0xbe79bf78,0xbeacbf71,0xbeacbf71,0xbf773e89,0x3f77be89,0xbf6f3eb8,0x3f6fbeb8,
0xbe48bf7b,0xbe48bf7b,0xbf753e95,0xbf753e95,0xbf513f13,0x3f51bf13,0x3f273f42,0xbf27bf42,0x3f5c3f04,0x3f5c3f04,0x3edbbf67,0x3edbbf67,0x3dfbbf7e,0xbdfb3f7e,0xbf80bcc9,0x3f803cc9,
0x3e483f7b,0x3e483f7b,0xbe95bf75,0xbe95bf75,0x3f09bf58,0xbf093f58,0xbee63f65,0x3ee6bf65,0xbf783e79,0xbf783e79,0x3f71beac,0x3f71beac,0x3f5f3efc,0xbf5fbefc,0xbf6abecf,0x3f6a3ecf,
0xbe48bf7b,0xbe48bf7b,0x3f75be95,0x3f75be95,0xbe2f3f7c,0x3e2fbf7c,0xbf7fbd97,0x3f7f3d97,0x3f04bf5c,0x3f04bf5c,0x3f673edb,0x3f673edb,0xbf4a3f1d,0x3f4abf1d,0xbf31bf39,0x3f313f39,
0x3f800000,0x3f800000,0x3f7fbdc9,0x3f7fbdc9,0x3f80bcc9,0xbf803cc9,0x3f7ebdfb,0xbf7e3dfb,0x3f80bd49,0x3f80bd49,0x3f7dbe16,0x3f7dbe16,0x3f7fbd97,0xbf7f3d97,0x3f7cbe2f,0xbf7c3e2f,
0x3f800000,0x3f800000,0xbdc9bf7f,0xbdc9bf7f,0x3f6abecf,0xbf6a3ecf,0xbefcbf5f,0x3efc3f5f,0x3f2cbf3e,0x3f2cbf3e,0xbf4ebf18,0xbf4ebf18,0x3ea1bf73,0xbea13f73,0xbf7abe60,0x3f7a3e60,
0x3f800000,0x3f800000,0xbf7f3dc9,0xbf7f3dc9,0x3f31bf39,0xbf313f39,0xbf1d3f4a,0x3f1dbf4a,0xbd49bf80,0xbd49bf80,0x3e163f7d,0x3e163f7d,0xbf42bf27,0x3f423f27,0x3f513f13,0xbf51bf13,
0x3f800000,0x3f800000,0x3dc93f7f,0x3dc93f7f,0x3eb8bf6f,0xbeb83f6f,0x3f773e89,0xbf77be89,0xbf3ebf2c,0xbf3ebf2c,0x3f18bf4e,0x3f18bf4e,0xbf653ee6,0x3f65bee6,0xbf09bf58,0x3f093f58,
0x3f800000,0x3f800000,0x3f7fbdc9,0x3f7fbdc9,0xbcc9bf80,0x3cc93f80,0xbdfbbf7e,0x3dfb3f7e,0xbf803d49,0xbf803d49,0xbf7d3e16,0xbf7d3e16,0x3d973f7f,0xbd97bf7f,0x3e2f3f7c,0xbe2fbf7c,
0x3f800000,0x3f800000,0xbdc9bf7f,0xbdc9bf7f,0xbecfbf6a,0x3ecf3f6a,0xbf5f3efc,0x3f5fbefc,0xbf2c3f3e,0xbf2c3f3e,0x3f4e3f18,0x3f4e3f18,0x3f733ea1,0xbf73bea1,0x3e60bf7a,0xbe603f7a,
0x3f800000,0x3f800000,0xbf7f3dc9,0xbf7f3dc9,0xbf39bf31,0x3f393f31,0x3f4a3f1d,0xbf4abf1d,0x3d493f80,0x3d493f80,0xbe16bf7d,0xbe16bf7d,0x3f27bf42,0xbf273f42,0xbf133f51,0x3f13bf51,
0x3f800000,0x3f800000,0x3dc93f7f,0x3dc93f7f,0xbf6fbeb8,0x3f6f3eb8,0x3e89bf77,0xbe893f77,0x3f3e3f2c,0x3f3e3f2c,0xbf183f4e,0xbf183f4e,0xbee6bf65,0x3ee63f65,0x3f58bf09,0xbf583f09,
0x3f7bbe48,0x3f7bbe48,0x3f75be95,0x3f75be95,0x3f7abe60,0xbf7a3e60,0x3f73bea1,0xbf733ea1,0x3f78be79,0x3f78be79,0x3f71beac,0x3f71beac,0x3f77be89,0xbf773e89,0x3f6fbeb8,0xbf6f3eb8,
0xbf7b3e48,0xbf7b3e48,0x3e953f75,0x3e953f75,0xbf513f13,0x3f51bf13,0x3f273f42,0xbf27bf42,0xbf043f5c,0xbf043f5c,0x3f673edb,0x3f673edb,0xbdfb3f7e,0x3dfbbf7e,0x3f803cc9,0xbf80bcc9,
0x3f7bbe48,0x3f7bbe48,0xbf753e95,0xbf753e95,0x3f09bf58,0xbf093f58,0xbee63f65,0x3ee6bf65,0xbe79bf78,0xbe79bf78,0x3eac3f71,0x3eac3f71,0xbf5fbefc,0x3f5f3efc,0x3f6a3ecf,0xbf6abecf,
0xbf7b3e48,0xbf7b3e48,0xbe95bf75,0xbe95bf75,0xbe2f3f7c,0x3e2fbf7c,0xbf7fbd97,0x3f7f3d97,0x3f5c3f04,0x3f5c3f04,0xbedb3f67,0xbedb3f67,0x3f4abf1d,0xbf4a3f1d,0x3f313f39,0xbf31bf39,
0x3f7bbe48,0x3f7bbe48,0x3f75be95,0x3f75be95,0xbe60bf7a,0x3e603f7a,0xbea1bf73,0x3ea13f73,0xbf783e79,0xbf783e79,0xbf713eac,0xbf713eac,0x3e893f77,0xbe89bf77,0x3eb83f6f,0xbeb8bf6f,
0xbf7b3e48,0xbf7b3e48,0x3e953f75,0x3e953f75,0x3f133f51,0xbf13bf51,0x3f42bf27,0xbf423f27,0x3f04bf5c,0x3f04bf5c,0xbf67bedb,0xbf67bedb,0xbf7ebdfb,0x3f7e3dfb,0xbcc93f80,0x3cc9bf80,
0x3f7bbe48,0x3f7bbe48,0xbf753e95,0xbf753e95,0xbf58bf09,0x3f583f09,0x3f653ee6,0xbf65bee6,0x3e793f78,0x3e793f78,0xbeacbf71,0xbeacbf71,0x3efcbf5f,0xbefc3f5f,0xbecf3f6a,0x3ecfbf6a,
0xbf7b3e48,0xbf7b3e48,0xbe95bf75,0xbe95bf75,0x3f7c3e2f,0xbf7cbe2f,0xbd973f7f,0x3d97bf7f,0xbf5cbf04,0xbf5cbf04,0x3edbbf67,0x3edbbf67,0x3f1d3f4a,0xbf1dbf4a,0xbf393f31,0x3f39bf31,
0x3f803f80,0xbf7b3f7b,0x3f803f80,0xbf7b3f7b,0x3f803f80,0xbf7b3f7b,0x3f803f80,0xbf7b3f7b,0x3f803f80,0xbf7b3f7b,0x3f803f80,0xbf7b3f7b,0x3f803f80,0xbf7b3f7b,0x3f803f80,0xbf7b3f7b,
0x3f6a3f80,0xbf513f7a,0xbf6abf80,0x3f51bf7a,0x3eb83f31,0xbe2f3f09,0xbeb8bf31,0x3e2fbf09,0xbecfbcc9,0x3f13be60,0x3ecf3cc9,0xbf133e60,0xbf6fbf39,0x3f7cbf58,0x3f6f3f39,0xbf7c3f58,
0x3f2c3f80,0xbf043f78,0x3f2c3f80,0xbf043f78,0xbf3ebd49,0x3f5cbe79,0xbf3ebd49,0x3f5cbe79,0xbf2cbf80,0x3f04bf78,0xbf2cbf80,0x3f04bf78,0x3f3e3d49,0xbf5c3e79,0x3f3e3d49,0xbf5c3e79,
0x3ea13f7f,0xbdfb3f77,0xbea1bf7f,0x3dfbbf77,0xbf65bf42,0x3f4abf5f,0x3f653f42,0xbf4a3f5f,0x3f733d97,0xbf7e3e89,0xbf73bd97,0x3f7ebe89,0xbee63f27,0x3f1d3efc,0x3ee6bf27,0xbf1dbefc,
0xbdc93f7f,0x3e953f75,0xbdc93f7f,0x3e953f75,0x3dc9bf7f,0xbe95bf75,0x3dc9bf7f,0xbe95bf75,0xbdc93f7f,0x3e953f75,0xbdc93f7f,0x3e953f75,0x3dc9bf7f,0xbe95bf75,0x3dc9bf7f,0xbe95bf75,
0xbefc3f7e,0x3f273f73,0x3efcbf7e,0xbf27bf73,0x3f77bf1d,0xbf7fbee6,0xbf773f1d,0x3f7f3ee6,0xbf5fbdfb,0x3f42bea1,0x3f5f3dfb,0xbf423ea1,0x3e893f4a,0xbd973f65,0xbe89bf4a,0x3d97bf65,
0xbf4e3f7d,0x3f673f71,0xbf4e3f7d,0x3f673f71,0x3f183e16,0xbedb3eac,0x3f183e16,0xbedb3eac,0x3f4ebf7d,0xbf67bf71,0x3f4ebf7d,0xbf67bf71,0xbf18be16,0x3edbbeac,0xbf18be16,0x3edbbeac,
0xbf7a3f7c,0x3f803f6f,0x3f7abf7c,0xbf80bf6f,0xbf093f51,0x3f313f6a,0x3f09bf51,0xbf31bf6a,0x3e603e2f,0xbcc93eb8,0xbe60be2f,0x3cc9beb8,0x3f58bf13,0xbf39becf,0xbf583f13,0x3f393ecf,
0,0xbe483e48,0,0xbe483e48,0,0xbe483e48,0,0xbe483e48,0,0xbe483e48,0,0xbe483e48,0,0xbe483e48,0,0xbe483e48,
0x3ecf3cc9,0xbf133e60,0xbecfbcc9,0x3f13be60,0x3f6f3f39,0xbf7c3f58,0xbf6fbf39,0x3f7cbf58,0x3f6a3f80,0xbf513f7a,0xbf6abf80,0x3f51bf7a,0x3eb83f31,0xbe2f3f09,0xbeb8bf31,0x3e2fbf09,
0x3f3e3d49,0xbf5c3e79,0x3f3e3d49,0xbf5c3e79,0x3f2c3f80,0xbf043f78,0x3f2c3f80,0xbf043f78,0xbf3ebd49,0x3f5cbe79,0xbf3ebd49,0x3f5cbe79,0xbf2cbf80,0x3f04bf78,0xbf2cbf80,0x3f04bf78,
0x3f733d97,0xbf7e3e89,0xbf73bd97,0x3f7ebe89,0xbee63f27,0x3f1d3efc,0x3ee6bf27,0xbf1dbefc,0xbea1bf7f,0x3dfbbf77,0x3ea13f7f,0xbdfb3f77,0x3f653f42,0xbf4a3f5f,0xbf65bf42,0x3f4abf5f,
0x3f7f3dc9,0xbf753e95,0x3f7f3dc9,0xbf753e95,0xbf7fbdc9,0x3f75be95,0xbf7fbdc9,0x3f75be95,0x3f7f3dc9,0xbf753e95,0x3f7f3dc9,0xbf753e95,0xbf7fbdc9,0x3f75be95,0xbf7fbdc9,0x3f75be95,
0x3f5f3dfb,0xbf423ea1,0xbf5fbdfb,0x3f42bea1,0xbe89bf4a,0x3d97bf65,0x3e893f4a,0xbd973f65,0xbefc3f7e,0x3f273f73,0x3efcbf7e,0xbf27bf73,0x3f77bf1d,0xbf7fbee6,0xbf773f1d,0x3f7f3ee6,
0x3f183e16,0xbedb3eac,0x3f183e16,0xbedb3eac,0x3f4ebf7d,0xbf67bf71,0x3f4ebf7d,0xbf67bf71,0xbf18be16,0x3edbbeac,0xbf18be16,0x3edbbeac,0xbf4e3f7d,0x3f673f71,0xbf4e3f7d,0x3f673f71,
0x3e603e2f,0xbcc93eb8,0xbe60be2f,0x3cc9beb8,0x3f58bf13,0xbf39becf,0xbf583f13,0x3f393ecf,0x3f7abf7c,0xbf80bf6f,0xbf7a3f7c,0x3f803f6f,0x3f09bf51,0xbf31bf6a,0xbf093f51,0x3f313f6a,
0,0x3e48be48,0,0x3e48be48,0,0x3e48be48,0,0x3e48be48,0,0x3e48be48,0,0x3e48be48,0,0x3e48be48,0,0x3e48be48,
0xbecfbcc9,0x3f13be60,0x3ecf3cc9,0xbf133e60,0xbf6fbf39,0x3f7cbf58,0x3f6f3f39,0xbf7c3f58,0xbf6abf80,0x3f51bf7a,0x3f6a3f80,0xbf513f7a,0xbeb8bf31,0x3e2fbf09,0x3eb83f31,0xbe2f3f09,
0xbf3ebd49,0x3f5cbe79,0xbf3ebd49,0x3f5cbe79,0xbf2cbf80,0x3f04bf78,0xbf2cbf80,0x3f04bf78,0x3f3e3d49,0xbf5c3e79,0x3f3e3d49,0xbf5c3e79,0x3f2c3f80,0xbf043f78,0x3f2c3f80,0xbf043f78,
0xbf73bd97,0x3f7ebe89,0x3f733d97,0xbf7e3e89,0x3ee6bf27,0xbf1dbefc,0xbee63f27,0x3f1d3efc,0x3ea13f7f,0xbdfb3f77,0xbea1bf7f,0x3dfbbf77,0xbf65bf42,0x3f4abf5f,0x3f653f42,0xbf4a3f5f,
0xbf7fbdc9,0x3f75be95,0xbf7fbdc9,0x3f75be95,0x3f7f3dc9,0xbf753e95,0x3f7f3dc9,0xbf753e95,0xbf7fbdc9,0x3f75be95,0xbf7fbdc9,0x3f75be95,0x3f7f3dc9,0xbf753e95,0x3f7f3dc9,0xbf753e95,
0xbf5fbdfb,0x3f42bea1,0x3f5f3dfb,0xbf423ea1,0x3e893f4a,0xbd973f65,0xbe89bf4a,0x3d97bf65,0x3efcbf7e,0xbf27bf73,0xbefc3f7e,0x3f273f73,0xbf773f1d,0x3f7f3ee6,0x3f77bf1d,0xbf7fbee6,
0xbf18be16,0x3edbbeac,0xbf18be16,0x3edbbeac,0xbf4e3f7d,0x3f673f71,0xbf4e3f7d,0x3f673f71,0x3f183e16,0xbedb3eac,0x3f183e16,0xbedb3eac,0x3f4ebf7d,0xbf67bf71,0x3f4ebf7d,0xbf67bf71,
0xbe60be2f,0x3cc9beb8,0x3e603e2f,0xbcc93eb8,0xbf583f13,0x3f393ecf,0x3f58bf13,0xbf39becf,0xbf7a3f7c,0x3f803f6f,0x3f7abf7c,0xbf80bf6f,0xbf093f51,0x3f313f6a,0x3f09bf51,0xbf31bf6a,
0x3f800000,0x3f7fffb1,0x3f800000,0x3f6c3624,0x3f7ffec4,0x3f7ffd39,0x3f33e7bc,0x3ebf926f,0x3f7ffb11,0x3f7ff84a,0xbc490e90,0xbecb2aae,0x3f7ff4e6,0x3f7ff0e3,0xbf385216,0xbf6e8ff8,
0x3f800000,0x3f7fa6e3,0x3f800000,0x3f671599,0x3f7e9bc9,0x3f7cdf6c,0x3f212ff9,0x3e6fa8b2,0x3f7a7302,0x3f77583a,0xbe541501,0xbf1ba299,0x3f73913f,0x3f6f20b0,0xbf63f473,0xbf7fe705,
0x3f800000,0x3f7eb069,0x3f800000,0x3f61668a,0x3f7ac516,0x3f74484b,0x3f0cead0,0x3db5f8da,0x3f6b4b0c,0x3f5fe4e9,0xbec9b953,0xbf485bca,0x3f5233c6,0x3f425b89,0xbf7bf531,0xbf73530e,
0x3f800000,0x3f7d1cdd,0x3f800000,0x3f5b2c79,0x3f748422,0x3f666771,0x3eee9479,0xbd6ea038,0x3f531849,0x3f3b0629,0xbf10d3cd,0xbf6912ae,0x3f1ebc12,0x3efdbabb,0xbf7e4323,0xbf4a4c87,
0x3f800000,0x3f7aed37,0x3f800000,0x3f546b3b,0x3f6be858,0x3f5389c7,0x3ec1071e,0xbe5101f1,0x3f32c8c9,0x3f0af1b7,0xbf373a23,0xbf7bd14d,0x3ebb31a0,0x3e3228d4,0xbf6aab7b,0xbf099f4e,
0x3f800000,0x3f7822d1,0x3f800000,0x3f4d26fd,0x3f6106f2,0x3f3c17d9,0x3e919ddd,0xbeb0eacb,0x3f0b9a6b,0x3ea5129f,0xbf5695e5,0xbf7f7808,0x3da3308c,0xbe2bf804,0xbf42de29,0xbe636c83,
0x3f800000,0x3f74bf62,0x3f800000,0x3f456439,0x3f53fac3,0x3f209393,0x3e419b37,0xbef58035,0x3ebe1d4a,0x3da973ba,0xbf6db293,0xbf73ced9,0xbe5a3997,0xbefafef7,0xbf0a48ad,0x3df475c0,
0x3f800000,0x3f70c501,0x3f800000,0x3f3d27b8,0x3f44e3f5,0x3f019573,0x3dbc3ac3,0xbf1a6293,0x3e3b6ecf,0xbe25c58c,0xbf7baccd,0xbf5988ad,0xbef9a02d,0xbf4154e1,0xbe8b9507,0x3ee4cbfe,
0,0x3b490fc6,0,0x3ec5625c,0x3bc90f88,0x3c16cb58,0x3f36206c,0x3f6d67a1,0x3c490e90,0x3c7b514b,0x3f7ffb11,0x3f6afb8c,0x3c96c9b6,0x3cafea69,0x3f31a81d,0x3eb9bb1e,
0,0x3d55880e,0,0x3edc53c1,0x3dd53db9,0x3e1f917b,0x3f46e22a,0x3f78e3d6,0x3e541501,0x3e840270,0x3f7a7302,0x3f4b41fa,0x3e9d9e78,0x3eb6ccc3,0x3ee900b7,0x3ce22a7a,
0,0x3dcefdb7,0,0x3ef2bd43,0x3e4dee60,0x3e9920fe,0x3f55b993,0x3f7efcc9,0x3ec9b953,0x3ef840c8,0x3f6b4b0c,0x3f1f599f,0x3f121eb0,0x3f269de3,0x3e354098,0xbe9f1cdf,
0,0x3e195be0,0,0x3f044889,0x3e97a117,0x3edf28a9,0x3f628210,0x3f7f90b1,0x3f10d3cd,0x3f2ecef7,0x3f531849,0x3ed3c867,0x3f48d8b3,0x3f5e5aa6,0xbdee3876,0xbf1ce11f,
0,0x3e4ada4f,0,0x3f0ee0db,0x3ec6d529,0x3f102dd5,0x3f6d1c1d,0x3f7a9c59,0x3f373a23,0x3f570348,0x3f32c8c9,0x3e3857ec,0x3f6e46be,0x3f7c187a,0xbecc9b8b,0xbf57dc7f,
0,0x3e7bdba4,0,0x3f19210f,0x3ef41f07,0x3f2da859,0x3f756d97,0x3f703b37,0x3f5695e5,0x3f725470,0x3f0b9a6b,0xbd83db0a,0x3f7f2f9d,0x3f7c5d3a,0xbf26050a,0xbf799b43,
0,0x3e9620d2,0,0x3f2302d3,0x3f0f8784,0x3f476085,0x3f7b61fc,0x3f60a6cf,0x3f6db293,0x3f7f1f49,0x3ebe1d4a,0xbe9c1faf,0x3f7a1e84,0x3f5f20db,0xbf577026,0xbf7e2b72,
0,0x3eadf73c,0,0x3f2c800f,0x3f239da9,0x3f5cc7d1,0x3f7eea9d,0x3f4c3578,0x3f7baccd,0x3f7c9f8a,0x3e3b6ecf,0xbf06f686,0x3f5f8327,0x3f27ce61,0xbf764d97,0xbf650479,
0x354ccccd,0x354ccccd,0x354ccccd,0x354ccccd,0x354ccccd,0x354ccccd,0x354ccccd,0x354ccccd,0x354ccccd,0x354ccccd,0x354ccccd,0x354ccccd,0x354ccccd,0x354ccccd,0x354ccccd,0x354ccccd,
0x354cc8da,0x35485c01,0xb220d873,0xb429aa67,0x353c3c09,0x3528e03a,0xb4a1610f,0xb4e7b948,0x350f0707,0x34df5d78,0xb51294e9,0xb52bab1e,0x3498176e,0x3415f23f,0xb53e2876,0xb549570a,
0x354ccc8e,0x354c8582,0x353cf81d,0x3538de14,0x354bc054,0x354a7d7e,0x35345208,0x352f56c7,0x3548bdc6,0x35468241,0x3529ef63,0x35241f31,0x3543cc4e,0x35409d9b,0x351de9c7,0x351752fa,
0x354cc6a2,0x3545e02f,0xb4a2888b,0xb4f90428,0x35331d87,0x35159e88,0xb520496e,0xb53a7558,0x34de4f8b,0x34840ee5,0xb549743e,0xb54c6006,0x33878fc8,0xb4049e0a,0xb5430be1,0xb52e06f1,
0x354ccbd0,0x354bafd4,0x350fec97,0x3500f32d,0x35489dab,0x35439ce8,0x34e177b4,0x34bedd2d,0x353cb9e0,0x3534058e,0x349a6c18,0x3468fc95,0x35299568,0x351d832a,0x341ae293,0x33969569,
0x354cc3eb,0x3542da99,0xb51374de,0xb5365d28,0x3528296b,0x34fdf9b6,0xb54990f4,0xb54b68e9,0x3495c14d,0x33828d3d,0xb53bbc62,0xb51be4ed,0xb42e9479,0xb4c7b357,0xb4dd4116,0xb45f54d8,
0x354cca94,0x354a4c56,0x349941f2,0x343fba28,0x35436d09,0x353852c1,0x339193e2,0xb33ee693,0x35293b06,0x3516797a,0xb42734c1,0xb48d88a2,0x3500760f,0x34cf5584,0xb4c46691,0xb4f7041e,
0x354cc0b6,0x353f4d5a,0xb53ed993,0xb54cb8d1,0x351b7c6d,0x34cafbc9,0xb542a8d8,0xb521d6d2,0x340e8710,0xb4099337,0xb4dc3217,0xb435f068,0xb4c8cbf9,0xb51aaa4d,0x33c39166,0x34b70998,
0,0,0,0,0,0,0,0,0,0,0,0,0,0,0,0,
0x3220d873,0x3429aa67,0x354cc8da,0x35485c01,0x34a1610f,0x34e7b948,0x353c3c09,0x3528e03a,0x351294e9,0x352bab1e,0x350f0707,0x34df5d78,0x353e2876,0x3549570a,0x3498176e,0x3415f23f,
0x3120d96b,0x332ad33e,0x349de84a,0x34b04301,0x33a597c6,0x33f55fcc,0x34c23103,0x34d3a742,0x3422483f,0x34497c83,0x34e49af8,0x34f501b2,0x34703484,0x348b2c30,0x350268a9,0x350a000c,
0x32490dd6,0x3453371a,0x353bfc70,0x35229b2e,0x34c69a3a,0x350bd8c6,0x34fef5cc,0x34a96d1f,0x352c02a0,0x3541dd26,0x3413798a,0xb352f811,0x354c1907,0x354a193c,0xb479cc4b,0xb4d7f0d6,
0x31a0d93a,0x33aa97c7,0x3511b389,0x351f1b54,0x3424beb3,0x34729b58,0x352afadc,0x353534da,0x349f10ee,0x34c34c06,0x353db017,0x354457ac,0x34e5a5a1,0x3502e487,0x35491b30,0x354beee4,
0x327142bd,0x347c30c0,0x350e2017,0x34ba66f9,0x34e9cab3,0x3520ad5c,0x3411007a,0xb3be9392,0x353e9eff,0x354c2618,0xb4a3afa2,0xb504d0d5,0x3548186a,0x3532cf52,0xb52c59b8,0xb5450adf,
0x31f1455a,0x33ff4f2b,0x353dec81,0x35471cab,0x34750196,0x34b286ed,0x354bfd6e,0x354c73c1,0x34e6afbb,0x350aed14,0x35487d14,0x35402f5f,0x351f806a,0x35309fda,0x3533b8a6,0x35235df9,
0x328cbb87,0x34923d69,0x349495b2,0x32b4eec8,0x35054b1c,0x3531e21f,0xb47e9498,0xb4fb01cb,0x3549ad2f,0x3549e42e,0xb52cb065,0xb547af69,0x353280af,0x35063eb4,0xb54b55f5,0xb53736c7,
0x3f80,0x3f80,0x3e483f7b,0x3e483f7b,0x3d493f80,0xbd49bf80,0x3e793f78,0xbe79bf78,0x3dc93f7f,0x3dc93f7f,0x3e953f75,0x3e953f75,0x3e163f7d,0xbe16bf7d,0x3eac3f71,0xbeacbf71,
0x3f80,0x3f80,0x3f7bbe48,0x3f7bbe48,0x3edb3f67,0xbedbbf67,0x3f4ebf18,0xbf4e3f18,0x3f463f22,0x3f463f22,0x3ef1bf62,0x3ef1bf62,0x3f783e79,0xbf78be79,0x3d49bf80,0xbd493f80,
0x3f80,0x3f80,0xbe48bf7b,0xbe48bf7b,0x3f3e3f2c,0xbf3ebf2c,0xbf5cbf04,0x3f5c3f04,0x3f7fbdc9,0x3f7fbdc9,0xbf753e95,0xbf753e95,0x3f18bf4e,0xbf183f4e,0xbedb3f67,0x3edbbf67,
0x3f80,0x3f80,0xbf7b3e48,0xbf7b3e48,0x3f713eac,0xbf71beac,0xbe163f7d,0x3e16bf7d,0x3f22bf46,0x3f22bf46,0x3f623ef1,0x3f623ef1,0xbf04bf5c,0x3f043f5c,0x3f3ebf2c,0xbf3e3f2c,
0x3f80,0x3f80,0x3e483f7b,0x3e483f7b,0x3f80bd49,0xbf803d49,0x3f78be79,0xbf783e79,0xbdc9bf7f,0xbdc9bf7f,0xbe95bf75,0xbe95bf75,0xbf7d3e16,0x3f7dbe16,0xbf713eac,0x3f71beac,
0x3f80,0x3f80,0x3f7bbe48,0x3f7bbe48,0x3f67bedb,0xbf673edb,0xbf18bf4e,0x3f183f4e,0xbf46bf22,0xbf46bf22,0xbef13f62,0xbef13f62,0xbe793f78,0x3e79bf78,0x3f803d49,0xbf80bd49,
0x3f80,0x3f80,0xbe48bf7b,0xbe48bf7b,0x3f2cbf3e,0xbf2c3f3e,0xbf043f5c,0x3f04bf5c,0xbf7f3dc9,0xbf7f3dc9,0x3f75be95,0x3f75be95,0x3f4e3f18,0xbf4ebf18,0xbf67bedb,0x3f673edb,
0x3f80,0x3f80,0xbf7b3e48,0xbf7b3e48,0x3eacbf71,0xbeac3f71,0x3f7d3e16,0xbf7dbe16,0xbf223f46,0xbf223f46,0xbf62bef1,0xbf62bef1,0x3f5cbf04,0xbf5c3f04,0x3f2c3f3e,0xbf2cbf3e,
0x3ec43f6d,0x3ec43f6d,0x3f0e3f55,0x3f0e3f55,0x3edb3f67,0xbedbbf67,0x3f183f4e,0xbf18bf4e,0x3ef13f62,0x3ef13f62,0x3f223f46,0x3f223f46,0x3f043f5c,0xbf04bf5c,0x3f2c3f3e,0xbf2cbf3e,
0xbec4bf6d,0xbec4bf6d,0xbf553f0e,0xbf553f0e,0xbf3ebf2c,0x3f3e3f2c,0xbf043f5c,0x3f04bf5c,0xbf75be95,0xbf75be95,0xbdc93f7f,0xbdc93f7f,0xbf7d3e16,0x3f7dbe16,0x3eac3f71,0xbeacbf71,
0x3ec43f6d,0x3ec43f6d,0xbf0ebf55,0xbf0ebf55,0x3f713eac,0xbf71beac,0xbf7dbe16,0x3f7d3e16,0x3f62bef1,0x3f62bef1,0xbf463f22,0xbf463f22,0x3e79bf78,0xbe793f78,0xbd493f80,0x3d49bf80,
0xbec4bf6d,0xbec4bf6d,0x3f55bf0e,0x3f55bf0e,0xbf803d49,0x3f80bd49,0xbe79bf78,0x3e793f78,0xbe953f75,0xbe953f75,0xbf7fbdc9,0xbf7fbdc9,0x3f4e3f18,0xbf4ebf18,0xbedb3f67,0x3edbbf67,
0x3ec43f6d,0x3ec43f6d,0x3f0e3f55,0x3f0e3f55,0x3f67bedb,0xbf673edb,0x3f4ebf18,0xbf4e3f18,0xbef1bf62,0xbef1bf62,0xbf22bf46,0xbf22bf46,0xbf5c3f04,0x3f5cbf04,0xbf3e3f2c,0x3f3ebf2c,
0xbec4bf6d,0xbec4bf6d,0xbf553f0e,0xbf553f0e,0xbf2c3f3e,0x3f2cbf3e,0x3f5c3f04,0xbf5cbf04,0x3f753e95,0x3f753e95,0x3dc9bf7f,0x3dc9bf7f,0xbe16bf7d,0x3e163f7d,0xbf713eac,0x3f71beac,
0x3ec43f6d,0x3ec43f6d,0xbf0ebf55,0xbf0ebf55,0x3eacbf71,0xbeac3f71,0xbe163f7d,0x3e16bf7d,0xbf623ef1,0xbf623ef1,0x3f46bf22,0x3f46bf22,0x3f783e79,0xbf78be79,0xbf80bd49,0x3f803d49,
0xbec4bf6d,0xbec4bf6d,0x3f55bf0e,0x3f55bf0e,0x3d493f80,0xbd49bf80,0xbf783e79,0x3f78be79,0x3e95bf75,0x3e95bf75,0x3f7f3dc9,0x3f7f3dc9,0xbf183f4e,0x3f18bf4e,0xbf67bedb,0x3f673edb,
0x3f800000,0x3f800000,0x3f7bbe48,0x3f7bbe48,0x3f80bd49,0xbf803d49,0x3f78be79,0xbf783e79,0x3f7fbdc9,0x3f7fbdc9,0x3f75be95,0x3f75be95,0x3f7dbe16,0xbf7d3e16,0x3f71beac,0xbf713eac,
0x3f800000,0x3f800000,0xbe48bf7b,0xbe48bf7b,0x3f67bedb,0xbf673edb,0xbf18bf4e,0x3f183f4e,0x3f22bf46,0x3f22bf46,0xbf62bef1,0xbf62bef1,0x3e79bf78,0xbe793f78,0xbf80bd49,0x3f803d49,
0x3f800000,0x3f800000,0xbf7b3e48,0xbf7b3e48,0x3f2cbf3e,0xbf2c3f3e,0xbf043f5c,0x3f04bf5c,0xbdc9bf7f,0xbdc9bf7f,0x3e953f75,0x3e953f75,0xbf4ebf18,0x3f4e3f18,0x3f673edb,0xbf67bedb,
0x3f800000,0x3f800000,0x3e483f7b,0x3e483f7b,0x3eacbf71,0xbeac3f71,0x3f7d3e16,0xbf7dbe16,0xbf46bf22,0xbf46bf22,0x3ef1bf62,0x3ef1bf62,0xbf5c3f04,0x3f5cbf04,0xbf2cbf3e,0x3f2c3f3e,
0x3f800000,0x3f800000,0x3f7bbe48,0x3f7bbe48,0xbd49bf80,0x3d493f80,0xbe79bf78,0x3e793f78,0xbf7f3dc9,0xbf7f3dc9,0xbf753e95,0xbf753e95,0x3e163f7d,0xbe16bf7d,0x3eac3f71,0xbeacbf71,
0x3f800000,0x3f800000,0xbe48bf7b,0xbe48bf7b,0xbedbbf67,0x3edb3f67,0xbf4e3f18,0x3f4ebf18,0xbf223f46,0xbf223f46,0x3f623ef1,0x3f623ef1,0x3f783e79,0xbf78be79,0x3d49bf80,0xbd493f80,
0x3f800000,0x3f800000,0xbf7b3e48,0xbf7b3e48,0xbf3ebf2c,0x3f3e3f2c,0x3f5c3f04,0xbf5cbf04,0x3dc93f7f,0x3dc93f7f,0xbe95bf75,0xbe95bf75,0x3f18bf4e,0xbf183f4e,0xbedb3f67,0x3edbbf67,
0x3f800000,0x3f800000,0x3e483f7b,0x3e483f7b,0xbf71beac,0x3f713eac,0x3e16bf7d,0xbe163f7d,0x3f463f22,0x3f463f22,0xbef13f62,0xbef13f62,0xbf04bf5c,0x3f043f5c,0x3f3ebf2c,0xbf3e3f2c,
0x3f6dbec4,0x3f6dbec4,0x3f55bf0e,0x3f55bf0e,0x3f67bedb,0xbf673edb,0x3f4ebf18,0xbf4e3f18,0x3f62bef1,0x3f62bef1,0x3f46bf22,0x3f46bf22,0x3f5cbf04,0xbf5c3f04,0x3f3ebf2c,0xbf3e3f2c,
0xbf6d3ec4,0xbf6d3ec4,0x3f0e3f55,0x3f0e3f55,0xbf2c3f3e,0x3f2cbf3e,0x3f5c3f04,0xbf5cbf04,0xbe953f75,0xbe953f75,0x3f7f3dc9,0x3f7f3dc9,0x3e163f7d,0xbe16bf7d,0x3f71beac,0xbf713eac,
0x3f6dbec4,0x3f6dbec4,0xbf553f0e,0xbf553f0e,0x3eacbf71,0xbeac3f71,0xbe163f7d,0x3e16bf7d,0xbef1bf62,0xbef1bf62,0x3f223f46,0x3f223f46,0xbf78be79,0x3f783e79,0x3f803d49,0xbf80bd49,
0xbf6d3ec4,0xbf6d3ec4,0xbf0ebf55,0xbf0ebf55,0x3d493f80,0xbd49bf80,0xbf783e79,0x3f78be79,0x3f753e95,0x3f753e95,0xbdc93f7f,0xbdc93f7f,0x3f18bf4e,0xbf183f4e,0x3f673edb,0xbf67bedb,
0x3f6dbec4,0x3f6dbec4,0x3f55bf0e,0x3f55bf0e,0xbedbbf67,0x3edb3f67,0xbf18bf4e,0x3f183f4e,0xbf623ef1,0xbf623ef1,0xbf463f22,0xbf463f22,0x3f043f5c,0xbf04bf5c,0x3f2c3f3e,0xbf2cbf3e,
0xbf6d3ec4,0xbf6d3ec4,0x3f0e3f55,0x3f0e3f55,0x3f3e3f2c,0xbf3ebf2c,0x3f04bf5c,0xbf043f5c,0x3e95bf75,0x3e95bf75,0xbf7fbdc9,0xbf7fbdc9,0xbf7d3e16,0x3f7dbe16,0x3eac3f71,0xbeacbf71,
0x3f6dbec4,0x3f6dbec4,0xbf553f0e,0xbf553f0e,0xbf71beac,0x3f713eac,0x3f7d3e16,0xbf7dbe16,0x3ef13f62,0x3ef13f62,0xbf22bf46,0xbf22bf46,0x3e79bf78,0xbe793f78,0xbd493f80,0x3d49bf80,
0xbf6d3ec4,0xbf6d3ec4,0xbf0ebf55,0xbf0ebf55,0x3f80bd49,0xbf803d49,0x3e793f78,0xbe79bf78,0xbf75be95,0xbf75be95,0x3dc9bf7f,0x3dc9bf7f,0x3f4e3f18,0xbf4ebf18,0xbedb3f67,0x3edbbf67,
0x3f803f80,0xbf6d3f6d,0x3f803f80,0xbf6d3f6d,0x3f803f80,0xbf6d3f6d,0x3f803f80,0xbf6d3f6d,0x3f803f80,0xbf6d3f6d,0x3f803f80,0xbf6d3f6d,0x3f803f80,0xbf6d3f6d,0x3f803f80,0xbf6d3f6d,
0x3f673f80,0xbf2c3f67,0xbf67bf80,0x3f2cbf67,0x3eac3f2c,0x3d493eac,0xbeacbf2c,0xbd49beac,0xbedbbd49,0x3f3ebedb,0x3edb3d49,0xbf3e3edb,0xbf71bf3e,0x3f80bf71,0x3f713f3e,0xbf803f71,
0x3f223f7f,0xbe953f62,0x3f223f7f,0xbe953f62,0xbf46bdc9,0x3f75bef1,0xbf46bdc9,0x3f75bef1,0xbf22bf7f,0x3e95bf62,0xbf22bf7f,0x3e95bf62,0x3f463dc9,0xbf753ef1,0x3f463dc9,0xbf753ef1,
0x3e793f7d,0x3e163f5c,0xbe79bf7d,0xbe16bf5c,0xbf5cbf4e,0x3f18bf78,0x3f5c3f4e,0xbf183f78,0x3f783e16,0xbf7d3f04,0xbf78be16,0x3f7dbf04,0xbf043f18,0x3f4e3e79,0x3f04bf18,0xbf4ebe79,
0xbe483f7b,0x3f0e3f55,0xbe483f7b,0x3f0e3f55,0x3e48bf7b,0xbf0ebf55,0x3e48bf7b,0xbf0ebf55,0xbe483f7b,0x3f0e3f55,0xbe483f7b,0x3f0e3f55,0x3e48bf7b,0xbf0ebf55,0x3e48bf7b,0xbf0ebf55,
0xbf183f78,0x3f5c3f4e,0x3f18bf78,0xbf5cbf4e,0x3f7dbf04,0xbf78be16,0xbf7d3f04,0x3f783e16,0xbf4ebe79,0x3f04bf18,0x3f4e3e79,0xbf043f18,0x3e163f5c,0x3e793f7d,0xbe16bf5c,0xbe79bf7d,
0xbf623f75,0x3f7f3f46,0xbf623f75,0x3f7f3f46,0x3ef13e95,0xbdc93f22,0x3ef13e95,0xbdc93f22,0x3f62bf75,0xbf7fbf46,0x3f62bf75,0xbf7fbf46,0xbef1be95,0x3dc9bf22,0xbef1be95,0x3dc9bf22,
0xbf803f71,0x3f713f3e,0x3f80bf71,0xbf71bf3e,0xbf2c3f67,0x3f673f80,0x3f2cbf67,0xbf67bf80,0x3d493eac,0x3eac3f2c,0xbd49beac,0xbeacbf2c,0x3f3ebedb,0xbedbbd49,0xbf3e3edb,0x3edb3d49,
0,0xbec43ec4,0,0xbec43ec4,0,0xbec43ec4,0,0xbec43ec4,0,0xbec43ec4,0,0xbec43ec4,0,0xbec43ec4,0,0xbec43ec4,
0x3edb3d49,0xbf3e3edb,0xbedbbd49,0x3f3ebedb,0x3f713f3e,0xbf803f71,0xbf71bf3e,0x3f80bf71,0x3f673f80,0xbf2c3f67,0xbf67bf80,0x3f2cbf67,0x3eac3f2c,0x3d493eac,0xbeacbf2c,0xbd49beac,
0x3f463dc9,0xbf753ef1,0x3f463dc9,0xbf753ef1,0x3f223f7f,0xbe953f62,0x3f223f7f,0xbe953f62,0xbf46bdc9,0x3f75bef1,0xbf46bdc9,0x3f75bef1,0xbf22bf7f,0x3e95bf62,0xbf22bf7f,0x3e95bf62,
0x3f783e16,0xbf7d3f04,0xbf78be16,0x3f7dbf04,0xbf043f18,0x3f4e3e79,0x3f04bf18,0xbf4ebe79,0xbe79bf7d,0xbe16bf5c,0x3e793f7d,0x3e163f5c,0x3f5c3f4e,0xbf183f78,0xbf5cbf4e,0x3f18bf78,
0x3f7b3e48,0xbf553f0e,0x3f7b3e48,0xbf553f0e,0xbf7bbe48,0x3f55bf0e,0xbf7bbe48,0x3f55bf0e,0x3f7b3e48,0xbf553f0e,0x3f7b3e48,0xbf553f0e,0xbf7bbe48,0x3f55bf0e,0xbf7bbe48,0x3f55bf0e,
0x3f4e3e79,0xbf043f18,0xbf4ebe79,0x3f04bf18,0xbe16bf5c,0xbe79bf7d,0x3e163f5c,0x3e793f7d,0xbf183f78,0x3f5c3f4e,0x3f18bf78,0xbf5cbf4e,0x3f7dbf04,0xbf78be16,0xbf7d3f04,0x3f783e16,
0x3ef13e95,0xbdc93f22,0x3ef13e95,0xbdc93f22,0x3f62bf75,0xbf7fbf46,0x3f62bf75,0xbf7fbf46,0xbef1be95,0x3dc9bf22,0xbef1be95,0x3dc9bf22,0xbf623f75,0x3f7f3f46,0xbf623f75,0x3f7f3f46,
0x3d493eac,0x3eac3f2c,0xbd49beac,0xbeacbf2c,0x3f3ebedb,0xbedbbd49,0xbf3e3edb,0x3edb3d49,0x3f80bf71,0xbf71bf3e,0xbf803f71,0x3f713f3e,0x3f2cbf67,0xbf67bf80,0xbf2c3f67,0x3f673f80,
0,0x3ec4bec4,0,0x3ec4bec4,0,0x3ec4bec4,0,0x3ec4bec4,0,0x3ec4bec4,0,0x3ec4bec4,0,0x3ec4bec4,0,0x3ec4bec4,
0xbedbbd49,0x3f3ebedb,0x3edb3d49,0xbf3e3edb,0xbf71bf3e,0x3f80bf71,0x3f713f3e,0xbf803f71,0xbf67bf80,0x3f2cbf67,0x3f673f80,0xbf2c3f67,0xbeacbf2c,0xbd49beac,0x3eac3f2c,0x3d493eac,
0xbf46bdc9,0x3f75bef1,0xbf46bdc9,0x3f75bef1,0xbf22bf7f,0x3e95bf62,0xbf22bf7f,0x3e95bf62,0x3f463dc9,0xbf753ef1,0x3f463dc9,0xbf753ef1,0x3f223f7f,0xbe953f62,0x3f223f7f,0xbe953f62,
0xbf78be16,0x3f7dbf04,0x3f783e16,0xbf7d3f04,0x3f04bf18,0xbf4ebe79,0xbf043f18,0x3f4e3e79,0x3e793f7d,0x3e163f5c,0xbe79bf7d,0xbe16bf5c,0xbf5cbf4e,0x3f18bf78,0x3f5c3f4e,0xbf183f78,
0xbf7bbe48,0x3f55bf0e,0xbf7bbe48,0x3f55bf0e,0x3f7b3e48,0xbf553f0e,0x3f7b3e48,0xbf553f0e,0xbf7bbe48,0x3f55bf0e,0xbf7bbe48,0x3f55bf0e,0x3f7b3e48,0xbf553f0e,0x3f7b3e48,0xbf553f0e,
0xbf4ebe79,0x3f04bf18,0x3f4e3e79,0xbf043f18,0x3e163f5c,0x3e793f7d,0xbe16bf5c,0xbe79bf7d,0x3f18bf78,0xbf5cbf4e,0xbf183f78,0x3f5c3f4e,0xbf7d3f04,0x3f783e16,0x3f7dbf04,0xbf78be16,
0xbef1be95,0x3dc9bf22,0xbef1be95,0x3dc9bf22,0xbf623f75,0x3f7f3f46,0xbf623f75,0x3f7f3f46,0x3ef13e95,0xbdc93f22,0x3ef13e95,0xbdc93f22,0x3f62bf75,0xbf7fbf46,0x3f62bf75,0xbf7fbf46,
0xbd49beac,0xbeacbf2c,0x3d493eac,0x3eac3f2c,0xbf3e3edb,0x3edb3d49,0x3f3ebedb,0xbedbbd49,0xbf803f71,0x3f713f3e,0x3f80bf71,0xbf71bf3e,0xbf2c3f67,0x3f673f80,0x3f2cbf67,0xbf67bf80,
0x3f800000,0x3f7ffec4,0x3f800000,0x3f6be858,0x3f7ffb11,0x3f7ff4e6,0x3f32c8c9,0x3ebb31a0,0x3f7fec43,0x3f7fe129,0xbcc90ab0,0xbed25a09,0x3f7fd397,0x3f7fc38f,0xbf3b8f3b,0xbf708066,
0x3f800000,0x3f7f9c18,0x3f800000,0x3f66becc,0x3f7e70b0,0x3f7c7eb0,0x3f1ff6cb,0x3e667c66,0x3f79c79d,0x3f764d97,0xbe605c13,0xbf1ebc12,0x3f721352,0x3f6d1c1d,0xbf660f88,0xbf7ffec4,
0x3f800000,0x3f7e9bc9,0x3f800000,0x3f6106f2,0x3f7a7302,0x3f73913f,0x3f0b9a6b,0x3da3308c,0x3f6a09a7,0x3f5df6be,0xbecf7bca,0xbf4ac77f,0x3f4f7a1f,0x3f3ebc1b,0xbf7cbfc9,0xbf718f57,
0x3f800000,0x3f7cfe73,0x3f800000,0x3f5ac450,0x3f740bdd,0x3f655e0b,0x3eebcbbb,0xbd8a200a,0x3f514d3d,0x3f385216,0xbf13682a,0xbf6aab7b,0x3f1b02c6,0x3ef41f07,0xbf7dabcc,0xbf46e22a,
0x3f800000,0x3f7ac516,0x3f800000,0x3f53fac3,0x3f6b4b0c,0x3f5233c6,0x3ebe1d4a,0xbe5a3997,0x3f3085bb,0x3f07a136,0xbf396842,0xbf7c7eb0,0x3eb263ef,0x3e1c76de,0xbf68bf3c,0xbf04f484,
0x3f800000,0x3f77f110,0x3f800000,0x3f4cae79,0x3f604621,0x3f3a7ca4,0x3e8e9a22,0xbeb554ec,0x3f08f59b,0x3e9d9e78,0xbf584853,0xbf7f2f9d,0x3d7b2b74,0xbe419b37,0xbf3fc767,0xbe4dee60,
0x3f800000,0x3f748422,0x3f800000,0x3f44e3f5,0x3f531849,0x3f1ebc12,0x3e3b6ecf,0xbef9a02d,0x3eb8442a,0x3d8a200a,0xbf6ed89e,0xbf7294f8,0xbe6c9a7f,0xbf0242b1,0xbf064b82,0x3e1008b7,
0x3f800000,0x3f708066,0x3f800000,0x3f3ca003,0x3f43e200,0x3eff17b2,0x3dafb680,0xbf1c420c,0x3e2f10a2,0xbe354098,0xbf7c3b28,0xbf577026,0xbf00e7e4,0xbf44e3f5,0xbe827dc0,0x3eee9479,
0,0x3bc90f88,0,0x3ec6d529,0x3c490e90,0x3c96c9b6,0x3f373a23,0x3f6e46be,0x3cc90ab0,0x3cfb49ba,0x3f7fec43,0x3f696591,0x3d16c32c,0x3d2fe007,0x3f2e3bde,0x3eaf713a,
0,0x3d621469,0,0x3eddbe79,0x3de1bc2e,0x3e28defc,0x3f47de65,0x3f796e4e,0x3e605c13,0x3e8b9507,0x3f79c79d,0x3f48d8b3,0x3ea68f12,0x3ec1071e,0x3ee0924f,0x3bc90f88,
0,0x3dd53db9,0,0x3ef41f07,0x3e541501,0x3e9d9e78,0x3f5695e5,0x3f7f2f9d,0x3ecf7bca,0x3eff17b2,0x3f6a09a7,0x3f1c420c,0x3f15f6d9,0x3f2ac082,0x3e22abb6,0xbea986c4,
0,0x3e1c76de,0,0x3f04f484,0x3e9aa086,0x3ee363fa,0x3f633c5a,0x3f7f6ac7,0x3f13682a,0x3f31a81d,0x3f514d3d,0x3ecc9b8b,0x3f4bbbf8,0x3f6106f2,0xbe09cf86,0xbf212ff9,
0,0x3e4dee60,0,0x3f0f8784,0x3ec9b953,0x3f121eb0,0x3f6db293,0x3f7a1e84,0x3f396842,0x3f591e6a,0x3f3085bb,0x3e28defc,0x3f6ff573,0x3f7cfe73,0xbed53641,0xbf5ac450,
0,0x3e7ee6e1,0,0x3f19c200,0x3ef6e0cb,0x3f2f61a5,0x3f75dec6,0x3f6f6830,0x3f584853,0x3f73913f,0x3f08f59b,0xbda3308c,0x3f7f84ab,0x3f7b61fc,0xbf299415,0xbf7ac516,
0,0x3e97a117,0,0x3f239da9,0x3f10d3cd,0x3f48d8b3,0x3f7baccd,0x3f5f8327,0x3f6ed89e,0x3f7f6ac7,0x3eb8442a,0xbea395c5,0x3f791298,0x3f5c61c7,0xbf59f26a,0xbf7d7474,
0,0x3eaf713a,0,0x3f2d1469,0x3f24d225,0x3f5df6be,0x3f7f0e58,0x3f4ac77f,0x3f7c3b28,0x3f7bf531,0x3e2f10a2,0xbf0a48ad,0x3f5d2d53,0x3f239da9,0xbf778bc5,0xbf628210,
0x354ccccd,0x354ccccd,0x354ccccd,0x354ccccd,0x354ccccd,0x354ccccd,0x354ccccd,0x354ccccd,0x354ccccd,0x354ccccd,0x354ccccd,0x354ccccd,0x354ccccd,0x354ccccd,0x354ccccd,0x354ccccd,
0x354cbd02,0x3547d2e4,0xb2a0d559,0xb4337cdc,0x353b3aec,0x352770fe,0xb4a5fca2,0xb4ebd9dd,0x350d37c9,0x34db2291,0xb5145368,0xb52d06a9,0x349369bb,0x340c0d4f,0xb53f13b1,0xb549c8ed,
0x354ccbd0,0x354c7ce0,0x353cb9e0,0x353898a3,0x354bafd4,0x354a6529,0x3534058e,0x352f0373,0x35489dab,0x35465a74,0x35299568,0x3523bec8,0x35439ce8,0x354066b8,0x351d832a,0x3516e669,
0x354cb421,0x35450adf,0xb4a84807,0xb4fdf9b6,0x35319232,0x351374de,0xb5223933,0xb53bbc62,0x34d901f0,0x347c30c0,0xb549fef3,0xb54c2618,0x335d000f,0xb411007a,0xb54210c7,0xb52c59b8,
0x354cc8da,0x354b8d5a,0x350f0707,0x34fff144,0x35485c01,0x35433cb1,0x34df5d78,0x34bca2fc,0x353c3c09,0x35336b4e,0x3498176e,0x346429d0,0x3528e03a,0x351cb4cd,0x3415f23f,0x338c9200,
0x354ca946,0x3541a90f,0xb5160c2f,0xb5380c6c,0x3525fb4c,0x34f8046f,0xb54a3307,0xb54aefd6,0x348eb659,0x3348ef90,0xb53a3296,0xb5196c52,0xb43d4866,0xb4ce3fd4,0xb4d6df37,0xb450c934,
0x354cc3eb,0x3549fef3,0x3495c14d,0x34386384,0x3542da99,0x35377e6f,0x33828d3d,0xb35d000f,0x3528296b,0x35153084,0xb42e9479,0xb49110bd,0x34fdf9b6,0x34cc12f5,0xb4c7b357,0xb4fa0347,
0x354c9c72,0x353db017,0xb54066b8,0xb54ccbd0,0x3518967c,0x34c34c06,0xb5413f79,0xb51f1b54,0x33fa57c9,0xb41ae293,0xb4d4ba6c,0xb424beb3,0xb4d06ab5,0xb51d832a,0x33e67457,0x34bedd2d,
0,0,0,0,0,0,0,0,0,0,0,0,0,0,0,0,
0x32a0d559,0x34337cdc,0x354cbd02,0x3547d2e4,0x34a5fca2,0x34ebd9dd,0x353b3aec,0x352770fe,0x35145368,0x352d06a9,0x350d37c9,0x34db2291,0x353f13b1,0x3549c8ed,0x349369bb,0x340c0d4f,
0x31a0d93a,0x3334dd20,0x349f10ee,0x34b1652e,0x33aa97c7,0x33fa57c9,0x34c34c06,0x34d4ba6c,0x3424beb3,0x344bebe7,0x34e5a5a1,0x34f60334,0x34729b58,0x348c5a95,0x3502e487,0x350a76bb,
0x32c907c8,0x345f54d8,0x353ab7a7,0x3520ad5c,0x34cc12f5,0x350e2017,0x34fa0347,0x34a3afa2,0x352db1ef,0x3542da99,0x340718ca,0xb3828d3d,0x354c556c,0x354990f4,0xb482de37,0xb4dd4116,
0x3220d873,0x33b4968b,0x351294e9,0x351fe51e,0x3429aa67,0x3477673d,0x352bab1e,0x3535c9e1,0x34a1610f,0x34c580a2,0x353e2876,0x3544b238,0x34e7b948,0x3503db51,0x3549570a,0x354c0b7a,
0x32f13846,0x34853f42,0x350b6318,0x34b3a83f,0x34eff15b,0x3522fcc6,0x340222f8,0xb3dc7f3e,0x353ff78f,0x354c6a23,0xb4aa91ce,0xb507a9aa,0x35474213,0x3530f10f,0xb52e5b88,0xb546096a,
0x327142bd,0x340718ca,0x353e9eff,0x35478b72,0x347c30c0,0x34b5e995,0x354c2618,0x354c556c,0x34e9cab3,0x350c4e1d,0x3548186a,0x353f868d,0x3520ad5c,0x35319232,0x3532cf52,0x35223933,
0x330cb338,0x349a6c18,0x348c5a95,0x31a0d93a,0x35089a01,0x3534058e,0xb4879f03,0xb500f32d,0x354a6529,0x35491b30,0xb52f0373,0xb5489dab,0x35304e38,0x3502e487,0xb54ac390,0xb53534da,
0x3f80,0x3f80,0x3e953f75,0x3e953f75,0x3d973f7f,0xbd97bf7f,0x3eb83f6f,0xbeb8bf6f,0x3e163f7d,0x3e163f7d,0x3edb3f67,0x3edb3f67,0x3e603f7a,0xbe60bf7a,0x3efc3f5f,0xbefcbf5f,
0x3f80,0x3f80,0x3f75be95,0x3f75be95,0x3ee63f65,0xbee6bf65,0x3f39bf31,0xbf393f31,0x3f4e3f18,0x3f4e3f18,0x3eacbf71,0x3eacbf71,0x3f7c3e2f,0xbf7cbe2f,0xbdfbbf7e,0x3dfb3f7e,
0x3f80,0x3f80,0xbe95bf75,0xbe95bf75,0x3f423f27,0xbf42bf27,0xbf6abecf,0x3f6a3ecf,0x3f7dbe16,0x3f7dbe16,0xbf673edb,0xbf673edb,0x3f09bf58,0xbf093f58,0xbe893f77,0x3e89bf77,
0x3f80,0x3f80,0xbf753e95,0xbf753e95,0x3f733ea1,0xbf73bea1,0xbcc93f80,0x3cc9bf80,0x3f18bf4e,0x3f18bf4e,0x3f713eac,0x3f713eac,0xbf13bf51,0x3f133f51,0x3f1dbf4a,0xbf1d3f4a,
0x3f80,0x3f80,0x3e953f75,0x3e953f75,0x3f7fbd97,0xbf7f3d97,0x3f6fbeb8,0xbf6f3eb8,0xbe16bf7d,0xbe16bf7d,0xbedbbf67,0xbedbbf67,0xbf7a3e60,0x3f7abe60,0xbf5f3efc,0x3f5fbefc,
0x3f80,0x3f80,0x3f75be95,0x3f75be95,0x3f65bee6,0xbf653ee6,0xbf31bf39,0x3f313f39,0xbf4ebf18,0xbf4ebf18,0xbeac3f71,0xbeac3f71,0xbe2f3f7c,0x3e2fbf7c,0x3f7ebdfb,0xbf7e3dfb,
0x3f80,0x3f80,0xbe95bf75,0xbe95bf75,0x3f27bf42,0xbf273f42,0xbecf3f6a,0x3ecfbf6a,0xbf7d3e16,0xbf7d3e16,0x3f67bedb,0x3f67bedb,0x3f583f09,0xbf58bf09,0xbf77be89,0x3f773e89,
0x3f80,0x3f80,0xbf753e95,0xbf753e95,0x3ea1bf73,0xbea13f73,0x3f803cc9,0xbf80bcc9,0xbf183f4e,0xbf183f4e,0xbf71beac,0xbf71beac,0x3f51bf13,0xbf513f13,0x3f4a3f1d,0xbf4abf1d,
0x3f0e3f55,0x3f0e3f55,0x3f463f22,0x3f463f22,0x3f1d3f4a,0xbf1dbf4a,0x3f513f13,0xbf51bf13,0x3f2c3f3e,0x3f2c3f3e,0x3f5c3f04,0x3f5c3f04,0x3f393f31,0xbf39bf31,0x3f653ee6,0xbf65bee6,
0xbf0ebf55,0xbf0ebf55,0xbf223f46,0xbf223f46,0xbf5fbefc,0x3f5f3efc,0xbe603f7a,0x3e60bf7a,0xbf80bd49,0xbf80bd49,0x3e793f78,0x3e793f78,0xbf6a3ecf,0x3f6abecf,0x3f273f42,0xbf27bf42,
0x3f0e3f55,0x3f0e3f55,0xbf46bf22,0xbf46bf22,0x3f7e3dfb,0xbf7ebdfb,0xbf7c3e2f,0x3f7cbe2f,0x3f3ebf2c,0x3f3ebf2c,0xbf043f5c,0xbf043f5c,0xbcc9bf80,0x3cc93f80,0x3ea13f73,0xbea1bf73,
0xbf0ebf55,0xbf0ebf55,0x3f22bf46,0x3f22bf46,0xbf773e89,0x3f77be89,0xbf09bf58,0x3f093f58,0xbd493f80,0xbd493f80,0xbf783e79,0xbf783e79,0x3f6f3eb8,0xbf6fbeb8,0xbd973f7f,0x3d97bf7f,
0x3f0e3f55,0x3f0e3f55,0x3f463f22,0x3f463f22,0x3f4abf1d,0xbf4a3f1d,0x3f13bf51,0xbf133f51,0xbf2cbf3e,0xbf2cbf3e,0xbf5cbf04,0xbf5cbf04,0xbf313f39,0x3f31bf39,0xbee63f65,0x3ee6bf65,
0xbf0ebf55,0xbf0ebf55,0xbf223f46,0xbf223f46,0xbefc3f5f,0x3efcbf5f,0x3f7a3e60,0xbf7abe60,0x3f803d49,0x3f803d49,0xbe79bf78,0xbe79bf78,0xbecfbf6a,0x3ecf3f6a,0xbf423f27,0x3f42bf27,
0x3f0e3f55,0x3f0e3f55,0xbf46bf22,0xbf46bf22,0x3dfbbf7e,0xbdfb3f7e,0x3e2f3f7c,0xbe2fbf7c,0xbf3e3f2c,0xbf3e3f2c,0x3f04bf5c,0x3f04bf5c,0x3f80bcc9,0xbf803cc9,0xbf733ea1,0x3f73bea1,
0xbf0ebf55,0xbf0ebf55,0x3f22bf46,0x3f22bf46,0x3e893f77,0xbe89bf77,0xbf583f09,0x3f58bf09,0x3d49bf80,0x3d49bf80,0x3f78be79,0x3f78be79,0xbeb83f6f,0x3eb8bf6f,0xbf7fbd97,0x3f7f3d97,
0x3f800000,0x3f800000,0x3f75be95,0x3f75be95,0x3f7fbd97,0xbf7f3d97,0x3f6fbeb8,0xbf6f3eb8,0x3f7dbe16,0x3f7dbe16,0x3f67bedb,0x3f67bedb,0x3f7abe60,0xbf7a3e60,0x3f5fbefc,0xbf5f3efc,
0x3f800000,0x3f800000,0xbe95bf75,0xbe95bf75,0x3f65bee6,0xbf653ee6,0xbf31bf39,0x3f313f39,0x3f18bf4e,0x3f18bf4e,0xbf71beac,0xbf71beac,0x3e2fbf7c,0xbe2f3f7c,0xbf7e3dfb,0x3f7ebdfb,
0x3f800000,0x3f800000,0xbf753e95,0xbf753e95,0x3f27bf42,0xbf273f42,0xbecf3f6a,0x3ecfbf6a,0xbe16bf7d,0xbe16bf7d,0x3edb3f67,0x3edb3f67,0xbf58bf09,0x3f583f09,0x3f773e89,0xbf77be89,
0x3f800000,0x3f800000,0x3e953f75,0x3e953f75,0x3ea1bf73,0xbea13f73,0x3f803cc9,0xbf80bcc9,0xbf4ebf18,0xbf4ebf18,0x3eacbf71,0x3eacbf71,0xbf513f13,0x3f51bf13,0xbf4abf1d,0x3f4a3f1d,
0x3f800000,0x3f800000,0x3f75be95,0x3f75be95,0xbd97bf7f,0x3d973f7f,0xbeb8bf6f,0x3eb83f6f,0xbf7d3e16,0xbf7d3e16,0xbf673edb,0xbf673edb,0x3e603f7a,0xbe60bf7a,0x3efc3f5f,0xbefcbf5f,
0x3f800000,0x3f800000,0xbe95bf75,0xbe95bf75,0xbee6bf65,0x3ee63f65,0xbf393f31,0x3f39bf31,0xbf183f4e,0xbf183f4e,0x3f713eac,0x3f713eac,0x3f7c3e2f,0xbf7cbe2f,0xbdfbbf7e,0x3dfb3f7e,
0x3f800000,0x3f800000,0xbf753e95,0xbf753e95,0xbf42bf27,0x3f423f27,0x3f6a3ecf,0xbf6abecf,0x3e163f7d,0x3e163f7d,0xbedbbf67,0xbedbbf67,0x3f09bf58,0xbf093f58,0xbe893f77,0x3e89bf77,
0x3f800000,0x3f800000,0x3e953f75,0x3e953f75,0xbf73bea1,0x3f733ea1,0x3cc9bf80,0xbcc93f80,0x3f4e3f18,0x3f4e3f18,0xbeac3f71,0xbeac3f71,0xbf13bf51,0x3f133f51,0x3f1dbf4a,0xbf1d3f4a,
0x3f55bf0e,0x3f55bf0e,0x3f22bf46,0x3f22bf46,0x3f4abf1d,0xbf4a3f1d,0x3f13bf51,0xbf133f51,0x3f3ebf2c,0x3f3ebf2c,0x3f04bf5c,0x3f04bf5c,0x3f31bf39,0xbf313f39,0x3ee6bf65,0xbee63f65,
0xbf553f0e,0xbf553f0e,0x3f463f22,0x3f463f22,0xbefc3f5f,0x3efcbf5f,0x3f7a3e60,0xbf7abe60,0xbd493f80,0xbd493f80,0x3f78be79,0x3f78be79,0x3ecf3f6a,0xbecfbf6a,0x3f42bf27,0xbf423f27,
0x3f55bf0e,0x3f55bf0e,0xbf223f46,0xbf223f46,0x3dfbbf7e,0xbdfb3f7e,0x3e2f3f7c,0xbe2fbf7c,0xbf2cbf3e,0xbf2cbf3e,0x3f5c3f04,0x3f5c3f04,0xbf803cc9,0x3f80bcc9,0x3f73bea1,0xbf733ea1,
0xbf553f0e,0xbf553f0e,0xbf46bf22,0xbf46bf22,0x3e893f77,0xbe89bf77,0xbf583f09,0x3f58bf09,0x3f803d49,0x3f803d49,0x3e793f78,0x3e793f78,0x3eb8bf6f,0xbeb83f6f,0x3f7f3d97,0xbf7fbd97,
0x3f55bf0e,0x3f55bf0e,0x3f22bf46,0x3f22bf46,0xbf1dbf4a,0x3f1d3f4a,0xbf51bf13,0x3f513f13,0xbf3e3f2c,0xbf3e3f2c,0xbf043f5c,0xbf043f5c,0x3f393f31,0xbf39bf31,0x3f653ee6,0xbf65bee6,
0xbf553f0e,0xbf553f0e,0x3f463f22,0x3f463f22,0x3f5f3efc,0xbf5fbefc,0x3e60bf7a,0xbe603f7a,0x3d49bf80,0x3d49bf80,0xbf783e79,0xbf783e79,0xbf6a3ecf,0x3f6abecf,0x3f273f42,0xbf27bf42,
0x3f55bf0e,0x3f55bf0e,0xbf223f46,0xbf223f46,0xbf7ebdfb,0x3f7e3dfb,0x3f7cbe2f,0xbf7c3e2f,0x3f2c3f3e,0x3f2c3f3e,0xbf5cbf04,0xbf5cbf04,0xbcc9bf80,0x3cc93f80,0x3ea13f73,0xbea1bf73,
0xbf553f0e,0xbf553f0e,0xbf46bf22,0xbf46bf22,0x3f77be89,0xbf773e89,0x3f093f58,0xbf09bf58,0xbf80bd49,0xbf80bd49,0xbe79bf78,0xbe79bf78,0x3f6f3eb8,0xbf6fbeb8,0xbd973f7f,0x3d97bf7f,
0x3f803f80,0xbf553f55,0x3f803f80,0xbf553f55,0x3f803f80,0xbf553f55,0x3f803f80,0xbf553f55,0x3f803f80,0xbf553f55,0x3f803f80,0xbf553f55,0x3f803f80,0xbf553f55,0x3f803f80,0xbf553f55,
0x3f653f7f,0xbefc3f4a,0xbf65bf7f,0x3efcbf4a,0x3ea13f27,0x3e893dfb,0xbea1bf27,0xbe89bdfb,0xbee6bd97,0x3f5fbf1d,0x3ee63d97,0xbf5f3f1d,0xbf73bf42,0x3f77bf7e,0x3f733f42,0xbf773f7e,
0x3f183f7d,0xbd493f3e,0x3f183f7d,0xbd493f3e,0xbf4ebe16,0x3f80bf2c,0xbf4ebe16,0x3f80bf2c,0xbf18bf7d,0x3d49bf3e,0xbf18bf7d,0x3d49bf3e,0x3f4e3e16,0xbf803f2c,0x3f4e3e16,0xbf803f2c,
0x3e2f3f7a,0x3ecf3f31,0xbe2fbf7a,0xbecfbf31,0xbf51bf58,0x3eb8bf80,0x3f513f58,0xbeb83f80,0x3f7c3e60,0xbf6a3f39,0xbf7cbe60,0x3f6abf39,0xbf133f09,0x3f6fbcc9,0x3f13bf09,0xbf6f3cc9,
0xbe953f75,0x3f463f22,0xbe953f75,0x3f463f22,0x3e95bf75,0xbf46bf22,0x3e95bf75,0xbf46bf22,0xbe953f75,0x3f463f22,0xbe953f75,0x3f463f22,0x3e95bf75,0xbf46bf22,0x3e95bf75,0xbf46bf22,
0xbf313f6f,0x3f7a3f13,0x3f31bf6f,0xbf7abf13,0x3f80becf,0xbf583e2f,0xbf803ecf,0x3f58be2f,0xbf39beb8,0x3e60bf51,0x3f393eb8,0xbe603f51,0x3cc93f6a,0x3f093f7c,0xbcc9bf6a,0xbf09bf7c,
0xbf713f67,0x3f783f04,0xbf713f67,0x3f783f04,0x3eac3edb,0x3e793f5c,0x3eac3edb,0x3e793f5c,0x3f71bf67,0xbf78bf04,0x3f71bf67,0xbf78bf04,0xbeacbedb,0xbe79bf5c,0xbeacbedb,0xbe79bf5c,
0xbf7e3f5f,0x3f423ee6,0x3f7ebf5f,0xbf42bee6,0xbf4a3f77,0x3f7f3f73,0x3f4abf77,0xbf7fbf73,0xbdfb3efc,0x3f273f65,0x3dfbbefc,0xbf27bf65,0x3f1dbe89,0xbd973ea1,0xbf1d3e89,0x3d97bea1,
0,0xbf0e3f0e,0,0xbf0e3f0e,0,0xbf0e3f0e,0,0xbf0e3f0e,0,0xbf0e3f0e,0,0xbf0e3f0e,0,0xbf0e3f0e,0,0xbf0e3f0e,
0x3ee63d97,0xbf5f3f1d,0xbee6bd97,0x3f5fbf1d,0x3f733f42,0xbf773f7e,0xbf73bf42,0x3f77bf7e,0x3f653f7f,0xbefc3f4a,0xbf65bf7f,0x3efcbf4a,0x3ea13f27,0x3e893dfb,0xbea1bf27,0xbe89bdfb,
0x3f4e3e16,0xbf803f2c,0x3f4e3e16,0xbf803f2c,0x3f183f7d,0xbd493f3e,0x3f183f7d,0xbd493f3e,0xbf4ebe16,0x3f80bf2c,0xbf4ebe16,0x3f80bf2c,0xbf18bf7d,0x3d49bf3e,0xbf18bf7d,0x3d49bf3e,
0x3f7c3e60,0xbf6a3f39,0xbf7cbe60,0x3f6abf39,0xbf133f09,0x3f6fbcc9,0x3f13bf09,0xbf6f3cc9,0xbe2fbf7a,0xbecfbf31,0x3e2f3f7a,0x3ecf3f31,0x3f513f58,0xbeb83f80,0xbf51bf58,0x3eb8bf80,
0x3f753e95,0xbf223f46,0x3f753e95,0xbf223f46,0xbf75be95,0x3f22bf46,0xbf75be95,0x3f22bf46,0x3f753e95,0xbf223f46,0x3f753e95,0xbf223f46,0xbf75be95,0x3f22bf46,0xbf75be95,0x3f22bf46,
0x3f393eb8,0xbe603f51,0xbf39beb8,0x3e60bf51,0xbcc9bf6a,0xbf09bf7c,0x3cc93f6a,0x3f093f7c,0xbf313f6f,0x3f7a3f13,0x3f31bf6f,0xbf7abf13,0x3f80becf,0xbf583e2f,0xbf803ecf,0x3f58be2f,
0x3eac3edb,0x3e793f5c,0x3eac3edb,0x3e793f5c,0x3f71bf67,0xbf78bf04,0x3f71bf67,0xbf78bf04,0xbeacbedb,0xbe79bf5c,0xbeacbedb,0xbe79bf5c,0xbf713f67,0x3f783f04,0xbf713f67,0x3f783f04,
0xbdfb3efc,0x3f273f65,0x3dfbbefc,0xbf27bf65,0x3f1dbe89,0xbd973ea1,0xbf1d3e89,0x3d97bea1,0x3f7ebf5f,0xbf42bee6,0xbf7e3f5f,0x3f423ee6,0x3f4abf77,0xbf7fbf73,0xbf4a3f77,0x3f7f3f73,
0,0x3f0ebf0e,0,0x3f0ebf0e,0,0x3f0ebf0e,0,0x3f0ebf0e,0,0x3f0ebf0e,0,0x3f0ebf0e,0,0x3f0ebf0e,0,0x3f0ebf0e,
0xbee6bd97,0x3f5fbf1d,0x3ee63d97,0xbf5f3f1d,0xbf73bf42,0x3f77bf7e,0x3f733f42,0xbf773f7e,0xbf65bf7f,0x3efcbf4a,0x3f653f7f,0xbefc3f4a,0xbea1bf27,0xbe89bdfb,0x3ea13f27,0x3e893dfb,
0xbf4ebe16,0x3f80bf2c,0xbf4ebe16,0x3f80bf2c,0xbf18bf7d,0x3d49bf3e,0xbf18bf7d,0x3d49bf3e,0x3f4e3e16,0xbf803f2c,0x3f4e3e16,0xbf803f2c,0x3f183f7d,0xbd493f3e,0x3f183f7d,0xbd493f3e,
0xbf7cbe60,0x3f6abf39,0x3f7c3e60,0xbf6a3f39,0x3f13bf09,0xbf6f3cc9,0xbf133f09,0x3f6fbcc9,0x3e2f3f7a,0x3ecf3f31,0xbe2fbf7a,0xbecfbf31,0xbf51bf58,0x3eb8bf80,0x3f513f58,0xbeb83f80,
0xbf75be95,0x3f22bf46,0xbf75be95,0x3f22bf46,0x3f753e95,0xbf223f46,0x3f753e95,0xbf223f46,0xbf75be95,0x3f22bf46,0xbf75be95,0x3f22bf46,0x3f753e95,0xbf223f46,0x3f753e95,0xbf223f46,
0xbf39beb8,0x3e60bf51,0x3f393eb8,0xbe603f51,0x3cc93f6a,0x3f093f7c,0xbcc9bf6a,0xbf09bf7c,0x3f31bf6f,0xbf7abf13,0xbf313f6f,0x3f7a3f13,0xbf803ecf,0x3f58be2f,0x3f80becf,0xbf583e2f,
0xbeacbedb,0xbe79bf5c,0xbeacbedb,0xbe79bf5c,0xbf713f67,0x3f783f04,0xbf713f67,0x3f783f04,0x3eac3edb,0x3e793f5c,0x3eac3edb,0x3e793f5c,0x3f71bf67,0xbf78bf04,0x3f71bf67,0xbf78bf04,
0x3dfbbefc,0xbf27bf65,0xbdfb3efc,0x3f273f65,0xbf1d3e89,0x3d97bea1,0x3f1dbe89,0xbd973ea1,0xbf7e3f5f,0x3f423ee6,0x3f7ebf5f,0xbf42bee6,0xbf4a3f77,0x3f7f3f73,0x3f4abf77,0xbf7fbf73,
0x3f800000,0x3f7ffd39,0x3f800000,0x3f6b99fb,0x3f7ff4e6,0x3f7fe705,0x3f31a81d,0x3eb6ccc3,0x3f7fd397,0x3f7fba9e,0xbd16c32c,0xbed97cb9,0x3f7f9c18,0x3f7f7808,0xbf3ebc1b,0xbf725470,
0x3f800000,0x3f7f90b1,0x3f800000,0x3f666771,0x3f7e4323,0x3f7c187a,0x3f1ebc12,0x3e5d4b1a,0x3f791298,0x3f75341d,0xbe6c9a7f,0xbf21cbfb,0x3f708066,0x3f6afb8c,0xbf6816a8,0xbf7ff84a,
0x3f800000,0x3f7e868b,0x3f800000,0x3f60a6cf,0x3f7a1e84,0x3f72d4eb,0x3f0a48ad,0x3d9064b4,0x3f68bf3c,0x3f5bfb34,0xbed53641,0xbf4d26fd,0x3f4cae79,0x3f3b0629,0xbf7d7474,0xbf6faf1b,
0x3f800000,0x3f7cdf6c,0x3f800000,0x3f5a5ba0,0x3f73913f,0x3f644fac,0x3ee900b7,0xbd9cecf9,0x3f4f7a1f,0x3f3592e7,0xbf15f6d9,0xbf6c3624,0x3f173c07,0x3eea6681,0xbf7cfe73,0xbf436051,
0x3f800000,0x3f7a9c59,0x3f800000,0x3f5389c7,0x3f6aab7b,0x3f50d937,0x3ebb31a0,0xbe636c83,0x3f2e3bde,0x3f044889,0xbf3b8f3b,0xbf7d1cdd,0x3ea986c4,0x3e06b26e,0xbf66becc,0xbf003a06,
0x3f800000,0x3f77beb7,0x3f800000,0x3f4c3578,0x3f5f8327,0x3f38dd65,0x3e8b9507,0xbeb9bb1e,0x3f064b82,0x3e9620d2,0xbf59f26a,0xbf7ed7d4,0x3d2fe007,0xbe57278f,0xbf3ca003,0xbe3857ec,
0x3f800000,0x3f74484b,0x3f800000,0x3f446337,0x3f5233c6,0x3f1ce11f,0x3e354098,0xbefdbabb,0x3eb263ef,0x3d55880e,0xbf6ff573,0xbf714c7a,0xbe7ee6e1,0xbf06f686,0xbf0242b1,0x3e25c58c,
0x3f800000,0x3f703b37,0x3f800000,0x3f3c17d9,0x3f42de29,0x3efafef7,0x3da3308c,0xbf1e1e22,0x3e22abb6,0xbe44b0b9,0xbf7cbfc9,0xbf554aa4,0xbf04f484,0xbf485bca,0xbe72b651,0x3ef840c8,
0,0x3c16cb58,0,0x3ec8477c,0x3c96c9b6,0x3ce22a7a,0x3f385216,0x3f6f20b0,0x3d16c32c,0x3d3c6dd5,0x3f7fd397,0x3f67c187,0x3d621469,0x3d83db0a,0x3f2ac082,0x3ea5129f,
0,0x3d6ea038,0,0x3edf28a9,0x3dee3876,0x3e3228d4,0x3f48d8b3,0x3f79f35e,0x3e6c9a7f,0x3e931f35,0x3f791298,0x3f466354,0x3eaf713a,0x3ecb2aae,0x3ed8106b,0xbc7b514b,
0,0x3ddb7d37,0,0x3ef58035,0x3e5a3997,0x3ea21887,0x3f577026,0x3f7f5ce9,0x3ed53641,0x3f02ef9f,0x3f68bf3c,0x3f19210f,0x3f19c200,0x3f2ecef7,0x3e1008b7,0xbeb3dca5,
0,0x3e1f917b,0,0x3f05a02c,0x3e9d9e78,0x3ee79a5d,0x3f63f473,0x3f7f3f54,0x3f15f6d9,0x3f34768f,0x3f4f7a1f,0x3ec5625c,0x3f4e8d90,0x3f6398ac,0xbe1c76de,0xbf256bcb,
0,0x3e5101f1,0,0x3f102dd5,0x3ecc9b8b,0x3f140c5f,0x3f6e46be,0x3f799b43,0x3f3b8f3b,0x3f5b2c79,0x3f2e3bde,0x3e195be0,0x3f718f57,0x3f7dc68c,0xbeddbe79,0xbf5d924d,
0,0x3e80f8c0,0,0x3f1a6293,0x3ef9a02d,0x3f311722,0x3f764d97,0x3f6e8ff8,0x3f59f26a,0x3f74bf62,0x3f064b82,0xbdc27c39,0x3f7fc38f,0x3f7a4910,0xbf2d1469,0xbf7bd14d,
0,0x3e9920fe,0,0x3f24381a,0x3f121eb0,0x3f4a4c87,0x3f7bf531,0x3f5e5aa6,0x3f6ff573,0x3f7fa6e3,0x3eb263ef,0xbeab0201,0x3f77f110,0x3f5988ad,0xbf5c61c7,0xbf7c9f8a,
0,0x3eb0eacb,0,0x3f2da859,0x3f26050a,0x3f5f20db,0x3f7f2f9d,0x3f495521,0x3f7cbfc9,0x3f7b3bab,0x3e22abb6,0xbf0d9281,0x3f5ac450,0x3f1f599f,0xbf78b47b,0xbf5fe4e9,
0x354ccccd,0x354ccccd,0x354ccccd,0x354ccccd,0x354ccccd,0x354ccccd,0x354ccccd,0x354ccccd,0x354ccccd,0x354ccccd,0x354ccccd,0x354ccccd,0x354ccccd,0x354ccccd,0x354ccccd,0x354ccccd,
0x354ca946,0x35474213,0xb2f13846,0xb43d4866,0x353a3296,0x3525fb4c,0xb4aa91ce,0xb4eff15b,0x350b6318,0x34d6df37,0xb5160c2f,0xb52e5b88,0x348eb659,0x340222f8,0xb53ff78f,0xb54a3307,
0x354cca94,0x354c73c1,0x353c7b2f,0x353852c1,0x354b9ed5,0x354a4c56,0x3533b8a6,0x352eafb3,0x35487d14,0x3546322c,0x35293b06,0x35235df9,0x35436d09,0x35402f5f,0x351d1c2c,0x3516797a,
0x354c954b,0x354429b0,0xb4adfd61,0xb5016ffc,0x352ffc2a,0x35114253,0xb5241f31,0xb53cf81d,0x34d3a742,0x34703484,0xb54a7d7e,0xb54bdfdd,0x332ad33e,0xb41d5a2e,0xb54109fb,0xb52aa21d,
0x354cc3eb,0x354b68e9,0x350e2017,0x34fdf9b6,0x3548186a,0x3542da99,0x34dd4116,0x34ba66f9,0x353bbc62,0x3532cf52,0x3495c14d,0x345f54d8,0x3528296b,0x351be4ed,0x3411007a,0x33828d3d,
0x354c7ce0,0x354066b8,0xb518967c,0xb539abba,0x3523bec8,0x34f1f9a5,0xb54ac390,0xb54a6529,0x34879f03,0x330cb338,0xb53898a3,0xb516e669,0xb44bebe7,0xb4d4ba6c,0xb4d06ab5,0xb4422b74,
0x354cb8d1,0x3549ad2f,0x34923d69,0x343108e1,0x354243ef,0x3536a623,0x33670786,0xb37b14c1,0x3527142c,0x3513e451,0xb435f068,0xb49495b2,0x34fb01cb,0x34c8cbf9,0xb4cafbc9,0xb4fcfd04,
0x354c6006,0x353bfc70,0xb541dd26,0xb54cc6a2,0x35159e88,0x34bb8534,0xb53fbf49,0xb51c4d0e,0x33d783e3,0xb42c1fa5,0xb4cd29a4,0xb413798a,0xb4d7f0d6,0xb520496e,0x34049e0a,0x34c69a3a,
0,0,0,0,0,0,0,0,0,0,0,0,0,0,0,0,
0x32f13846,0x343d4866,0x354ca946,0x35474213,0x34aa91ce,0x34eff15b,0x353a3296,0x3525fb4c,0x35160c2f,0x352e5b88,0x350b6318,0x34d6df37,0x353ff78f,0x354a3307,0x348eb659,0x340222f8,
0x31f1455a,0x333ee693,0x34a03930,0x34b286ed,0x33af9760,0x33ff4f2b,0x34c46691,0x34d5cd14,0x342734c1,0x344e5acd,0x34e6afbb,0x34f7041e,0x34750196,0x348d88a2,0x35036014,0x350aed14,
0x3316be44,0x346b6521,0x3539679f,0x351eb5dd,0x34d17f65,0x35105ed9,0x34f501b2,0x349de84a,0x352f56c7,0x3543cc4e,0x33f55fcc,0xb39b9694,0x354c8582,0x3548fc89,0xb488ce67,0xb4e28401,
0x327142bd,0x33be9392,0x351374de,0x3520ad5c,0x342e9479,0x347c30c0,0x352c59b8,0x35365d28,0x34a3afa2,0x34c7b357,0x353e9eff,0x35450adf,0x34e9cab3,0x3504d0d5,0x354990f4,0x354c2618,
0x3334dd20,0x348c5a95,0x35089a01,0x34acd9f0,0x34f60334,0x35253e0d,0x33e67457,0xb3fa57c9,0x35413f79,0x354c9c72,0xb4b1652e,0xb50a76bb,0x35465a74,0x352f0373,0xb5304e38,0xb546f6c8,
0x32b4eec8,0x340e8710,0x353f4d5a,0x3547f5e5,0x3481ad39,0x34b9484b,0x354c4a54,0x354c32aa,0x34ece099,0x350dac1c,0x3547af69,0x353ed993,0x3521d6d2,0x353280af,0x3531e21f,0x352110e7,
0x3352f811,0x34a2888b,0x34840ee5,0xb2490dd6,0x350bd8c6,0x353613bd,0xb48fe3b7,0xb504563c,0x354b053d,0x35483a73,0xb53141d7,0xb549743e,0x352e06f1,0x34fef5cc,0xb54a193c,0xb5331d87,
0x3f80,0x3f80,0x3ec43f6d,0x3ec43f6d,0x3dc93f7f,0xbdc9bf7f,0x3ef13f62,0xbef1bf62,0x3e483f7b,0x3e483f7b,0x3f0e3f55,0x3f0e3f55,0x3e953f75,0xbe95bf75,0x3f223f46,0xbf22bf46,
0x3f80,0x3f80,0x3f6dbec4,0x3f6dbec4,0x3ef13f62,0xbef1bf62,0x3f22bf46,0xbf223f46,0x3f553f0e,0x3f553f0e,0x3e48bf7b,0x3e48bf7b,0x3f7f3dc9,0xbf7fbdc9,0xbe95bf75,0x3e953f75,
0x3f80,0x3f80,0xbec4bf6d,0xbec4bf6d,0x3f463f22,0xbf46bf22,0xbf75be95,0x3f753e95,0x3f7bbe48,0x3f7bbe48,0xbf553f0e,0xbf553f0e,0x3ef1bf62,0xbef13f62,0xbdc93f7f,0x3dc9bf7f,
0x3f80,0x3f80,0xbf6d3ec4,0xbf6d3ec4,0x3f753e95,0xbf75be95,0x3dc93f7f,0xbdc9bf7f,0x3f0ebf55,0x3f0ebf55,0x3f7b3e48,0x3f7b3e48,0xbf22bf46,0x3f223f46,0x3ef1bf62,0xbef13f62,
0x3f80,0x3f80,0x3ec43f6d,0x3ec43f6d,0x3f7fbdc9,0xbf7f3dc9,0x3f62bef1,0xbf623ef1,0xbe48bf7b,0xbe48bf7b,0xbf0ebf55,0xbf0ebf55,0xbf753e95,0x3f75be95,0xbf463f22,0x3f46bf22,
0x3f80,0x3f80,0x3f6dbec4,0x3f6dbec4,0x3f62bef1,0xbf623ef1,0xbf46bf22,0x3f463f22,0xbf55bf0e,0xbf55bf0e,0xbe483f7b,0xbe483f7b,0xbdc93f7f,0x3dc9bf7f,0x3f75be95,0xbf753e95,
0x3f80,0x3f80,0xbec4bf6d,0xbec4bf6d,0x3f22bf46,0xbf223f46,0xbe953f75,0x3e95bf75,0xbf7b3e48,0xbf7b3e48,0x3f55bf0e,0x3f55bf0e,0x3f623ef1,0xbf62bef1,0xbf7fbdc9,0x3f7f3dc9,
0x3f80,0x3f80,0xbf6d3ec4,0xbf6d3ec4,0x3e95bf75,0xbe953f75,0x3f7fbdc9,0xbf7f3dc9,0xbf0e3f55,0xbf0e3f55,0xbf7bbe48,0xbf7bbe48,0x3f46bf22,0xbf463f22,0x3f623ef1,0xbf62bef1,
0x3f353f35,0x3f353f35,0x3f6d3ec4,0x3f6d3ec4,0x3f463f22,0xbf46bf22,0x3f753e95,0xbf75be95,0x3f553f0e,0x3f553f0e,0x3f7b3e48,0x3f7b3e48,0x3f623ef1,0xbf62bef1,0x3f7f3dc9,0xbf7fbdc9,
0xbf35bf35,0xbf35bf35,0xbec43f6d,0xbec43f6d,0xbf75be95,0x3f753e95,0x3dc93f7f,0xbdc9bf7f,0xbf7b3e48,0xbf7b3e48,0x3f0e3f55,0x3f0e3f55,0xbf463f22,0x3f46bf22,0x3f623ef1,0xbf62bef1,
0x3f353f35,0x3f353f35,0xbf6dbec4,0xbf6dbec4,0x3f7fbdc9,0xbf7f3dc9,0xbf623ef1,0x3f62bef1,0x3f0ebf55,0x3f0ebf55,0xbe483f7b,0xbe483f7b,0xbe95bf75,0x3e953f75,0x3f223f46,0xbf22bf46,
0xbf35bf35,0xbf35bf35,0x3ec4bf6d,0x3ec4bf6d,0xbf623ef1,0x3f62bef1,0xbf46bf22,0x3f463f22,0x3e483f7b,0x3e483f7b,0xbf553f0e,0xbf553f0e,0x3f7f3dc9,0xbf7fbdc9,0x3e953f75,0xbe95bf75,
0x3f353f35,0x3f353f35,0x3f6d3ec4,0x3f6d3ec4,0x3f22bf46,0xbf223f46,0x3e95bf75,0xbe953f75,0xbf55bf0e,0xbf55bf0e,0xbf7bbe48,0xbf7bbe48,0xbef13f62,0x3ef1bf62,0xbdc93f7f,0x3dc9bf7f,
0xbf35bf35,0xbf35bf35,0xbec43f6d,0xbec43f6d,0xbe953f75,0x3e95bf75,0x3f7fbdc9,0xbf7f3dc9,0x3f7bbe48,0x3f7bbe48,0xbf0ebf55,0xbf0ebf55,0xbf22bf46,0x3f223f46,0xbef13f62,0x3ef1bf62,
0x3f353f35,0x3f353f35,0xbf6dbec4,0xbf6dbec4,0xbdc9bf7f,0x3dc93f7f,0x3ef13f62,0xbef1bf62,0xbf0e3f55,0xbf0e3f55,0x3e48bf7b,0x3e48bf7b,0x3f75be95,0xbf753e95,0xbf463f22,0x3f46bf22,
0xbf35bf35,0xbf35bf35,0x3ec4bf6d,0x3ec4bf6d,0x3ef13f62,0xbef1bf62,0xbf223f46,0x3f22bf46,0xbe48bf7b,0xbe48bf7b,0x3f55bf0e,0x3f55bf0e,0xbdc93f7f,0x3dc9bf7f,0xbf753e95,0x3f75be95,
0x3f800000,0x3f800000,0x3f6dbec4,0x3f6dbec4,0x3f7fbdc9,0xbf7f3dc9,0x3f62bef1,0xbf623ef1,0x3f7bbe48,0x3f7bbe48,0x3f55bf0e,0x3f55bf0e,0x3f75be95,0xbf753e95,0x3f46bf22,0xbf463f22,
0x3f800000,0x3f800000,0xbec4bf6d,0xbec4bf6d,0x3f62bef1,0xbf623ef1,0xbf46bf22,0x3f463f22,0x3f0ebf55,0x3f0ebf55,0xbf7bbe48,0xbf7bbe48,0x3dc9bf7f,0xbdc93f7f,0xbf753e95,0x3f75be95,
0x3f800000,0x3f800000,0xbf6d3ec4,0xbf6d3ec4,0x3f22bf46,0xbf223f46,0xbe953f75,0x3e95bf75,0xbe48bf7b,0xbe48bf7b,0x3f0e3f55,0x3f0e3f55,0xbf62bef1,0x3f623ef1,0x3f7f3dc9,0xbf7fbdc9,
0x3f800000,0x3f800000,0x3ec43f6d,0x3ec43f6d,0x3e95bf75,0xbe953f75,0x3f7fbdc9,0xbf7f3dc9,0xbf55bf0e,0xbf55bf0e,0x3e48bf7b,0x3e48bf7b,0xbf463f22,0x3f46bf22,0xbf62bef1,0x3f623ef1,
0x3f800000,0x3f800000,0x3f6dbec4,0x3f6dbec4,0xbdc9bf7f,0x3dc93f7f,0xbef1bf62,0x3ef13f62,0xbf7b3e48,0xbf7b3e48,0xbf553f0e,0xbf553f0e,0x3e953f75,0xbe95bf75,0x3f223f46,0xbf22bf46,
0x3f800000,0x3f800000,0xbec4bf6d,0xbec4bf6d,0xbef1bf62,0x3ef13f62,0xbf223f46,0x3f22bf46,0xbf0e3f55,0xbf0e3f55,0x3f7b3e48,0x3f7b3e48,0x3f7f3dc9,0xbf7fbdc9,0xbe95bf75,0x3e953f75,
0x3f800000,0x3f800000,0xbf6d3ec4,0xbf6d3ec4,0xbf46bf22,0x3f463f22,0x3f753e95,0xbf75be95,0x3e483f7b,0x3e483f7b,0xbf0ebf55,0xbf0ebf55,0x3ef1bf62,0xbef13f62,0xbdc93f7f,0x3dc9bf7f,
0x3f800000,0x3f800000,0x3ec43f6d,0x3ec43f6d,0xbf75be95,0x3f753e95,0xbdc9bf7f,0x3dc93f7f,0x3f553f0e,0x3f553f0e,0xbe483f7b,0xbe483f7b,0xbf22bf46,0x3f223f46,0x3ef1bf62,0xbef13f62,
0x3f35bf35,0x3f35bf35,0x3ec4bf6d,0x3ec4bf6d,0x3f22bf46,0xbf223f46,0x3e95bf75,0xbe953f75,0x3f0ebf55,0x3f0ebf55,0x3e48bf7b,0x3e48bf7b,0x3ef1bf62,0xbef13f62,0x3dc9bf7f,0xbdc93f7f,
0xbf353f35,0xbf353f35,0x3f6d3ec4,0x3f6d3ec4,0xbe953f75,0x3e95bf75,0x3f7fbdc9,0xbf7f3dc9,0x3e483f7b,0x3e483f7b,0x3f55bf0e,0x3f55bf0e,0x3f223f46,0xbf22bf46,0x3ef1bf62,0xbef13f62,
0x3f35bf35,0x3f35bf35,0xbec43f6d,0xbec43f6d,0xbdc9bf7f,0x3dc93f7f,0x3ef13f62,0xbef1bf62,0xbf55bf0e,0xbf55bf0e,0x3f7b3e48,0x3f7b3e48,0xbf753e95,0x3f75be95,0x3f46bf22,0xbf463f22,
0xbf353f35,0xbf353f35,0xbf6dbec4,0xbf6dbec4,0x3ef13f62,0xbef1bf62,0xbf223f46,0x3f22bf46,0x3f7bbe48,0x3f7bbe48,0x3f0e3f55,0x3f0e3f55,0x3dc9bf7f,0xbdc93f7f,0x3f75be95,0xbf753e95,
0x3f35bf35,0x3f35bf35,0x3ec4bf6d,0x3ec4bf6d,0xbf46bf22,0x3f463f22,0xbf75be95,0x3f753e95,0xbf0e3f55,0xbf0e3f55,0xbe483f7b,0xbe483f7b,0x3f623ef1,0xbf62bef1,0x3f7f3dc9,0xbf7fbdc9,
0xbf353f35,0xbf353f35,0x3f6d3ec4,0x3f6d3ec4,0x3f753e95,0xbf75be95,0xbdc9bf7f,0x3dc93f7f,0xbe48bf7b,0xbe48bf7b,0xbf553f0e,0xbf553f0e,0xbf463f22,0x3f46bf22,0x3f623ef1,0xbf62bef1,
0x3f35bf35,0x3f35bf35,0xbec43f6d,0xbec43f6d,0xbf7f3dc9,0x3f7fbdc9,0x3f62bef1,0xbf623ef1,0x3f553f0e,0x3f553f0e,0xbf7bbe48,0xbf7bbe48,0xbe95bf75,0x3e953f75,0x3f223f46,0xbf22bf46,
0xbf353f35,0xbf353f35,0xbf6dbec4,0xbf6dbec4,0x3f62bef1,0xbf623ef1,0x3f463f22,0xbf46bf22,0xbf7b3e48,0xbf7b3e48,0xbf0ebf55,0xbf0ebf55,0x3f7f3dc9,0xbf7fbdc9,0x3e953f75,0xbe95bf75,
0x3f803f80,0xbf353f35,0x3f803f80,0xbf353f35,0x3f803f80,0xbf353f35,0x3f803f80,0xbf353f35,0x3f803f80,0xbf353f35,0x3f803f80,0xbf353f35,0x3f803f80,0xbf353f35,0x3f803f80,0xbf353f35,
0x3f623f7f,0xbe953f22,0xbf62bf7f,0x3e95bf22,0x3e953f22,0x3ef1bdc9,0xbe95bf22,0xbef13dc9,0xbef1bdc9,0x3f75bf46,0x3ef13dc9,0xbf753f46,0xbf75bf46,0x3f62bf7f,0x3f753f46,0xbf623f7f,
0x3f0e3f7b,0x3e483f0e,0x3f0e3f7b,0x3e483f0e,0xbf55be48,0x3f7bbf55,0xbf55be48,0x3f7bbf55,0xbf0ebf7b,0xbe48bf0e,0xbf0ebf7b,0xbe48bf0e,0x3f553e48,0xbf7b3f55,0x3f553e48,0xbf7b3f55,
0x3dc93f75,0x3f223ef1,0xbdc9bf75,0xbf22bef1,0xbf46bf62,0x3dc9bf75,0x3f463f62,0xbdc93f75,0x3f7f3e95,0xbf463f62,0xbf7fbe95,0x3f46bf62,0xbf223ef1,0x3f7fbe95,0x3f22bef1,0xbf7f3e95,
0xbec43f6d,0x3f6d3ec4,0xbec43f6d,0x3f6d3ec4,0x3ec4bf6d,0xbf6dbec4,0x3ec4bf6d,0xbf6dbec4,0xbec43f6d,0x3f6d3ec4,0xbec43f6d,0x3f6d3ec4,0x3ec4bf6d,0xbf6dbec4,0x3ec4bf6d,0xbf6dbec4,
0xbf463f62,0x3f7f3e95,0x3f46bf62,0xbf7fbe95,0x3f7fbe95,0xbf223ef1,0xbf7f3e95,0x3f22bef1,0xbf22bef1,0xbdc9bf75,0x3f223ef1,0x3dc93f75,0xbdc93f75,0x3f463f62,0x3dc9bf75,0xbf46bf62,
0xbf7b3f55,0x3f553e48,0xbf7b3f55,0x3f553e48,0x3e483f0e,0x3f0e3f7b,0x3e483f0e,0x3f0e3f7b,0x3f7bbf55,0xbf55be48,0x3f7bbf55,0xbf55be48,0xbe48bf0e,0xbf0ebf7b,0xbe48bf0e,0xbf0ebf7b,
0xbf753f46,0x3ef13dc9,0x3f75bf46,0xbef1bdc9,0xbf623f7f,0x3f753f46,0x3f62bf7f,0xbf75bf46,0xbe953f22,0x3f623f7f,0x3e95bf22,0xbf62bf7f,0x3ef1bdc9,0x3e953f22,0xbef13dc9,0xbe95bf22,
0,0xbf353f35,0,0xbf353f35,0,0xbf353f35,0,0xbf353f35,0,0xbf353f35,0,0xbf353f35,0,0xbf353f35,0,0xbf353f35,
0x3ef13dc9,0xbf753f46,0xbef1bdc9,0x3f75bf46,0x3f753f46,0xbf623f7f,0xbf75bf46,0x3f62bf7f,0x3f623f7f,0xbe953f22,0xbf62bf7f,0x3e95bf22,0x3e953f22,0x3ef1bdc9,0xbe95bf22,0xbef13dc9,
0x3f553e48,0xbf7b3f55,0x3f553e48,0xbf7b3f55,0x3f0e3f7b,0x3e483f0e,0x3f0e3f7b,0x3e483f0e,0xbf55be48,0x3f7bbf55,0xbf55be48,0x3f7bbf55,0xbf0ebf7b,0xbe48bf0e,0xbf0ebf7b,0xbe48bf0e,
0x3f7f3e95,0xbf463f62,0xbf7fbe95,0x3f46bf62,0xbf223ef1,0x3f7fbe95,0x3f22bef1,0xbf7f3e95,0xbdc9bf75,0xbf22bef1,0x3dc93f75,0x3f223ef1,0x3f463f62,0xbdc93f75,0xbf46bf62,0x3dc9bf75,
0x3f6d3ec4,0xbec43f6d,0x3f6d3ec4,0xbec43f6d,0xbf6dbec4,0x3ec4bf6d,0xbf6dbec4,0x3ec4bf6d,0x3f6d3ec4,0xbec43f6d,0x3f6d3ec4,0xbec43f6d,0xbf6dbec4,0x3ec4bf6d,0xbf6dbec4,0x3ec4bf6d,
0x3f223ef1,0x3dc93f75,0xbf22bef1,0xbdc9bf75,0x3dc9bf75,0xbf46bf62,0xbdc93f75,0x3f463f62,0xbf463f62,0x3f7f3e95,0x3f46bf62,0xbf7fbe95,0x3f7fbe95,0xbf223ef1,0xbf7f3e95,0x3f22bef1,
0x3e483f0e,0x3f0e3f7b,0x3e483f0e,0x3f0e3f7b,0x3f7bbf55,0xbf55be48,0x3f7bbf55,0xbf55be48,0xbe48bf0e,0xbf0ebf7b,0xbe48bf0e,0xbf0ebf7b,0xbf7b3f55,0x3f553e48,0xbf7b3f55,0x3f553e48,
0xbe953f22,0x3f623f7f,0x3e95bf22,0xbf62bf7f,0x3ef1bdc9,0x3e953f22,0xbef13dc9,0xbe95bf22,0x3f75bf46,0xbef1bdc9,0xbf753f46,0x3ef13dc9,0x3f62bf7f,0xbf75bf46,0xbf623f7f,0x3f753f46,
0,0x3f35bf35,0,0x3f35bf35,0,0x3f35bf35,0,0x3f35bf35,0,0x3f35bf35,0,0x3f35bf35,0,0x3f35bf35,0,0x3f35bf35,
0xbef1bdc9,0x3f75bf46,0x3ef13dc9,0xbf753f46,0xbf75bf46,0x3f62bf7f,0x3f753f46,0xbf623f7f,0xbf62bf7f,0x3e95bf22,0x3f623f7f,0xbe953f22,0xbe95bf22,0xbef13dc9,0x3e953f22,0x3ef1bdc9,
0xbf55be48,0x3f7bbf55,0xbf55be48,0x3f7bbf55,0xbf0ebf7b,0xbe48bf0e,0xbf0ebf7b,0xbe48bf0e,0x3f553e48,0xbf7b3f55,0x3f553e48,0xbf7b3f55,0x3f0e3f7b,0x3e483f0e,0x3f0e3f7b,0x3e483f0e,
0xbf7fbe95,0x3f46bf62,0x3f7f3e95,0xbf463f62,0x3f22bef1,0xbf7f3e95,0xbf223ef1,0x3f7fbe95,0x3dc93f75,0x3f223ef1,0xbdc9bf75,0xbf22bef1,0xbf46bf62,0x3dc9bf75,0x3f463f62,0xbdc93f75,
0xbf6dbec4,0x3ec4bf6d,0xbf6dbec4,0x3ec4bf6d,0x3f6d3ec4,0xbec43f6d,0x3f6d3ec4,0xbec43f6d,0xbf6dbec4,0x3ec4bf6d,0xbf6dbec4,0x3ec4bf6d,0x3f6d3ec4,0xbec43f6d,0x3f6d3ec4,0xbec43f6d,
0xbf22bef1,0xbdc9bf75,0x3f223ef1,0x3dc93f75,0xbdc93f75,0x3f463f62,0x3dc9bf75,0xbf46bf62,0x3f46bf62,0xbf7fbe95,0xbf463f62,0x3f7f3e95,0xbf7f3e95,0x3f22bef1,0x3f7fbe95,0xbf223ef1,
0xbe48bf0e,0xbf0ebf7b,0xbe48bf0e,0xbf0ebf7b,0xbf7b3f55,0x3f553e48,0xbf7b3f55,0x3f553e48,0x3e483f0e,0x3f0e3f7b,0x3e483f0e,0x3f0e3f7b,0x3f7bbf55,0xbf55be48,0x3f7bbf55,0xbf55be48,
0x3e95bf22,0xbf62bf7f,0xbe953f22,0x3f623f7f,0xbef13dc9,0xbe95bf22,0x3ef1bdc9,0x3e953f22,0xbf753f46,0x3ef13dc9,0x3f75bf46,0xbef1bdc9,0xbf623f7f,0x3f753f46,0x3f62bf7f,0xbf75bf46,
0x3f800000,0x3f7ffb11,0x3f800000,0x3f6b4b0c,0x3f7fec43,0x3f7fd397,0x3f3085bb,0x3eb263ef,0x3f7fb10f,0x3f7f84ab,0xbd48fb30,0xbee0924f,0x3f7f4e6d,0x3f7f0e58,0xbf41d870,0xbf740bdd,
0x3f800000,0x3f7f84ab,0x3f800000,0x3f660f88,0x3f7e1324,0x3f7baccd,0x3f1d7fd1,0x3e541501,0x3f7853f8,0x3f740bdd,0xbe78cfcc,0xbf24d225,0x3f6ed89e,0x3f68bf3c,0xbf6a09a7,0xbf7fd397,
0x3f800000,0x3f7e70b0,0x3f800000,0x3f604621,0x3f79c79d,0x3f721352,0x3f08f59b,0x3d7b2b74,0x3f676bd8,0x3f59f26a,0xbedae880,0xbf4f7a1f,0x3f49d112,0x3f373a23,0xbf7e1324,0xbf6db293,
0x3f800000,0x3f7cbfc9,0x3f800000,0x3f59f26a,0x3f731447,0x3f633c5a,0x3ee63375,0xbdafb680,0x3f4d9f02,0x3f32c8c9,0xbf187fc0,0xbf6db293,0x3f13682a,0x3ee0924f,0xbf7c3b28,0xbf3fc767,
0x3f800000,0x3f7a7302,0x3f800000,0x3f531849,0x3f6a09a7,0x3f4f7a1f,0x3eb8442a,0xbe6c9a7f,0x3f2beb4a,0x3f00e7e4,0xbf3daef9,0xbf7dabcc,0x3ea09ae5,0x3de1bc2e,0xbf64aa59,0xbef6e0cb,
0x3f800000,0x3f778bc5,0x3f800000,0x3f4bbbf8,0x3f5ebe05,0x3f373a23,0x3e888e93,0xbebe1d4a,0x3f039c3d,0x3e8e9a22,0xbf5b941a,0xbf7e70b0,0x3cc90ab0,0xbe6c9a7f,0xbf396842,0xbe22abb6,
0x3f800000,0x3f740bdd,0x3f800000,0x3f43e200,0x3f514d3d,0x3f1b02c6,0x3e2f10a2,0xbf00e7e4,0x3eac7cd4,0x3d16c32c,0xbf710908,0xbf6ff573,0xbe888e93,0xbf0b9a6b,0xbefc5d27,0x3e3b6ecf,
0x3f800000,0x3f6ff573,0x3f800000,0x3f3b8f3b,0x3f41d870,0x3ef6e0cb,0x3d96a905,0xbf1ff6cb,0x3e164083,0xbe541501,0xbf7d3aac,0xbf531849,0xbf08f59b,0xbf4bbbf8,0xbe605c13,0x3f00e7e4,
0,0x3c490e90,0,0x3ec9b953,0x3cc90ab0,0x3d16c32c,0x3f396842,0x3f6ff573,0x3d48fb30,0x3d7b2b74,0x3f7fb10f,0x3f660f88,0x3d96a905,0x3dafb680,0x3f273656,0x3e9aa086,
0,0x3d7b2b74,0,0x3ee0924f,0x3dfab273,0x3e3b6ecf,0x3f49d112,0x3f7a7302,0x3e78cfcc,0x3e9aa086,0x3f7853f8,0x3f43e200,0x3eb8442a,0x3ed53641,0x3ecf7bca,0xbd16c32c,
0,0x3de1bc2e,0,0x3ef6e0cb,0x3e605c13,0x3ea68f12,0x3f584853,0x3f7f84ab,0x3edae880,0x3f064b82,0x3f676bd8,0x3f15f6d9,0x3f1d7fd1,0x3f32c8c9,0x3dfab273,0xbebe1d4a,
0,0x3e22abb6,0,0x3f064b82,0x3ea09ae5,0x3eebcbbb,0x3f64aa59,0x3f7f0e58,0x3f187fc0,0x3f373a23,0x3f4d9f02,0x3ebe1d4a,0x3f514d3d,0x3f660f88,0xbe2f10a2,0xbf299415,
0,0x3e541501,0,0x3f10d3cd,0x3ecf7bca,0x3f15f6d9,0x3f6ed89e,0x3f791298,0x3f3daef9,0x3f5d2d53,0x3f2beb4a,0x3e09cf86,0x3f731447,0x3f7e70b0,0xbee63375,0xbf604621,
0,0x3e827dc0,0,0x3f1b02c6,0x3efc5d27,0x3f32c8c9,0x3f76ba07,0x3f6db293,0x3f5b941a,0x3f75dec6,0x3f039c3d,0xbde1bc2e,0x3f7fec43,0x3f791298,0xbf3085bb,0xbf7cbfc9,
0,0x3e9aa086,0,0x3f24d225,0x3f13682a,0x3f4bbbf8,0x3f7c3b28,0x3f5d2d53,0x3f710908,0x3f7fd397,0x3eac7cd4,0xbeb263ef,0x3f76ba07,0x3f5695e5,0xbf5ebe05,0xbf7baccd,
0,0x3eb263ef,0,0x3f2e3bde,0x3f273656,0x3f604621,0x3f7f4e6d,0x3f47de65,0x3f7d3aac,0x3f7a7302,0x3e164083,0xbf10d3cd,0x3f584853,0x3f1b02c6,0xbf79c79d,0xbf5d2d53,
0x354ccccd,0x354ccccd,0x354ccccd,0x354ccccd,0x354ccccd,0x354ccccd,0x354ccccd,0x354ccccd,0x354ccccd,0x354ccccd,0x354ccccd,0x354ccccd,0x354ccccd,0x354ccccd,0x354ccccd,0x354ccccd,
0x354c8da6,0x3546a993,0xb320c8f3,0xb4470ca3,0x35392313,0x35247f35,0xb4af2067,0xb4f3ff99,0x35098908,0x34d29394,0xb517bf2e,0xb52fa9af,0x3489fd76,0x33f06739,0xb540d407,0xb54a9556,
0x354cc8da,0x354c6a23,0x353c3c09,0x35380c6c,0x354b8d5a,0x354a3307,0x35336b4e,0x352e5b88,0x35485c01,0x3546096a,0x3528e03a,0x3522fcc6,0x35433cb1,0x353ff78f,0x351cb4cd,0x35160c2f,
0x354c6a23,0x35433cb1,0xb4b3a83f,0xb503db51,0x352e5b88,0x350f0707,0xb525fb4c,0xb53e2876,0x34ce3fd4,0x346429d0,0xb54aefd6,0xb54b8d5a,0x32f13846,0xb429aa67,0xb53ff78f,0xb528e03a,
0x354cbd02,0x354b4283,0x350d37c9,0x34fbffb5,0x3547d2e4,0x354276a0,0x34db2291,0x34b8292a,0x353b3aec,0x3532319e,0x349369bb,0x345a7db8,0x352770fe,0x351b138d,0x340c0d4f,0x33710e6e,
0x354c3ebe,0x353f13b1,0xb51b138d,0xb53b3aec,0x3521740f,0x34ebd9dd,0xb54b4283,0xb549c8ed,0x34807bea,0x32a0d559,0xb536eeae,0xb5145368,0xb45a7db8,0xb4db2291,0xb4c9e41f,0xb4337cdc,
0x354ca946,0x3549570a,0x348eb659,0x3429aa67,0x3541a90f,0x3535c9e1,0x3348ef90,0xb38c9200,0x3525fb4c,0x351294e9,0xb43d4866,0xb498176e,0x34f8046f,0x34c580a2,0xb4ce3fd4,0xb4fff144,
0x354c0b7a,0x353a3296,0xb5433cb1,0xb54ca946,0x351294e9,0x34b3a83f,0xb53e2876,0xb5196c52,0x33b4968b,0xb43d4866,0xb4c580a2,0xb40222f8,0xb4df5d78,0xb522fcc6,0x3415f23f,0x34ce3fd4,
0,0,0,0,0,0,0,0,0,0,0,0,0,0,0,0,
0x3320c8f3,0x34470ca3,0x354c8da6,0x3546a993,0x34af2067,0x34f3ff99,0x35392313,0x35247f35,0x3517bf2e,0x352fa9af,0x35098908,0x34d29394,0x3540d407,0x354a9556,0x3489fd76,0x33f06739,
0x3220d873,0x3348ef90,0x34a1610f,0x34b3a83f,0x33b4968b,0x340222f8,0x34c580a2,0x34d6df37,0x3429aa67,0x3450c934,0x34e7b948,0x34f8046f,0x3477673d,0x348eb659,0x3503db51,0x350b6318,
0x3348ef90,0x3477673d,0x35380c6c,0x351cb4cd,0x34d6df37,0x351294e9,0x34eff15b,0x3498176e,0x3530f10f,0x3544b238,0x33dc7f3e,0xb3b4968b,0x354ca946,0x35485c01,0xb48eb659,0xb4e7b948,
0x32a0d559,0x33c88ec2,0x35145368,0x3521740f,0x34337cdc,0x34807bea,0x352d06a9,0x3536eeae,0x34a5fca2,0x34c9e41f,0x353f13b1,0x3545619f,0x34ebd9dd,0x3505c511,0x3549c8ed,0x354c3ebe,
0x33710e6e,0x349369bb,0x3505c511,0x34a5fca2,0x34fbffb5,0x352770fe,0x33c88ec2,0xb40c0d4f,0x354276a0,0x354cbd02,0xb4b8292a,0xb50d37c9,0x3545619f,0x352d06a9,0xb532319e,0xb547d2e4,
0x32f13846,0x3415f23f,0x353ff78f,0x35485c01,0x34853f42,0x34bca2fc,0x354c6a23,0x354c0b7a,0x34eff15b,0x350f0707,0x35474213,0x353e2876,0x3522fcc6,0x35336b4e,0x3530f10f,0x351fe51e,
0x338c9200,0x34aa91ce,0x3477673d,0xb2f13846,0x350f0707,0x35380c6c,0xb498176e,0xb507a9aa,0x354b8d5a,0x35474213,0xb5336b4e,0xb54a3307,0x352bab1e,0x34f8046f,0xb549570a,0xb530f10f,
0x3f80,0x3f80,0x3ef13f62,0x3ef13f62,0x3dfb3f7e,0xbdfbbf7e,0x3f133f51,0xbf13bf51,0x3e793f78,0x3e793f78,0x3f2c3f3e,0x3f2c3f3e,0x3eb83f6f,0xbeb8bf6f,0x3f423f27,0xbf42bf27,
0x3f80,0x3f80,0x3f62bef1,0x3f62bef1,0x3efc3f5f,0xbefcbf5f,0x3f09bf58,0xbf093f58,0x3f5c3f04,0x3f5c3f04,0x3d49bf80,0x3d49bf80,0x3f803cc9,0xbf80bcc9,0xbee6bf65,0x3ee63f65,
0x3f80,0x3f80,0xbef1bf62,0xbef1bf62,0x3f4a3f1d,0xbf4abf1d,0xbf7cbe2f,0x3f7c3e2f,0x3f78be79,0x3f78be79,0xbf3e3f2c,0xbf3e3f2c,0x3ecfbf6a,0xbecf3f6a,0x3d973f7f,0xbd97bf7f,
0x3f80,0x3f80,0xbf623ef1,0xbf623ef1,0x3f773e89,0xbf77be89,0x3e603f7a,0xbe60bf7a,0x3f04bf5c,0x3f04bf5c,0x3f803d49,0x3f803d49,0xbf31bf39,0x3f313f39,0x3ea1bf73,0xbea13f73,
0x3f80,0x3f80,0x3ef13f62,0x3ef13f62,0x3f7ebdfb,0xbf7e3dfb,0x3f51bf13,0xbf513f13,0xbe79bf78,0xbe79bf78,0xbf2cbf3e,0xbf2cbf3e,0xbf6f3eb8,0x3f6fbeb8,0xbf273f42,0x3f27bf42,
0x3f80,0x3f80,0x3f62bef1,0x3f62bef1,0x3f5fbefc,0xbf5f3efc,0xbf58bf09,0x3f583f09,0xbf5cbf04,0xbf5cbf04,0xbd493f80,0xbd493f80,0xbcc93f80,0x3cc9bf80,0x3f65bee6,0xbf653ee6,
0x3f80,0x3f80,0xbef1bf62,0xbef1bf62,0x3f1dbf4a,0xbf1d3f4a,0xbe2f3f7c,0x3e2fbf7c,0xbf783e79,0xbf783e79,0x3f3ebf2c,0x3f3ebf2c,0x3f6a3ecf,0xbf6abecf,0xbf7f3d97,0x3f7fbd97,
0x3f80,0x3f80,0xbf623ef1,0xbf623ef1,0x3e89bf77,0xbe893f77,0x3f7abe60,0xbf7a3e60,0xbf043f5c,0xbf043f5c,0xbf80bd49,0xbf80bd49,0x3f39bf31,0xbf393f31,0x3f733ea1,0xbf73bea1,
0x3f553f0e,0x3f553f0e,0x3f7f3dc9,0x3f7f3dc9,0x3f653ee6,0xbf65bee6,0x3f80bcc9,0xbf803cc9,0x3f713eac,0x3f713eac,0x3f7dbe16,0x3f7dbe16,0x3f7a3e60,0xbf7abe60,0x3f77be89,0xbf773e89,
0xbf55bf0e,0xbf55bf0e,0xbdc93f7f,0xbdc93f7f,0xbf7fbd97,0x3f7f3d97,0x3ecf3f6a,0xbecfbf6a,0xbf673edb,0xbf673edb,0x3f4e3f18,0x3f4e3f18,0xbf133f51,0x3f13bf51,0x3f7e3dfb,0xbf7ebdfb,
0x3f553f0e,0x3f553f0e,0xbf7fbdc9,0xbf7fbdc9,0x3f73bea1,0xbf733ea1,0xbf313f39,0x3f31bf39,0x3eacbf71,0x3eacbf71,0x3e163f7d,0x3e163f7d,0xbf09bf58,0x3f093f58,0x3f5f3efc,0xbf5fbefc,
0xbf55bf0e,0xbf55bf0e,0x3dc9bf7f,0x3dc9bf7f,0xbf423f27,0x3f42bf27,0xbf6fbeb8,0x3f6f3eb8,0x3edb3f67,0x3edb3f67,0xbf183f4e,0xbf183f4e,0x3f7cbe2f,0xbf7c3e2f,0x3f1d3f4a,0xbf1dbf4a,
0x3f553f0e,0x3f553f0e,0x3f7f3dc9,0x3f7f3dc9,0x3ee6bf65,0xbee63f65,0xbcc9bf80,0x3cc93f80,0xbf71beac,0xbf71beac,0xbf7d3e16,0xbf7d3e16,0xbe603f7a,0x3e60bf7a,0x3e893f77,0xbe89bf77,
0xbf55bf0e,0xbf55bf0e,0xbdc93f7f,0xbdc93f7f,0xbd973f7f,0x3d97bf7f,0x3f6abecf,0xbf6a3ecf,0x3f67bedb,0x3f67bedb,0xbf4ebf18,0xbf4ebf18,0xbf51bf13,0x3f513f13,0xbdfb3f7e,0x3dfbbf7e,
0x3f553f0e,0x3f553f0e,0xbf7fbdc9,0xbf7fbdc9,0xbea1bf73,0x3ea13f73,0x3f393f31,0xbf39bf31,0xbeac3f71,0xbeac3f71,0xbe16bf7d,0xbe16bf7d,0x3f58bf09,0xbf583f09,0xbefc3f5f,0x3efcbf5f,
0xbf55bf0e,0xbf55bf0e,0x3dc9bf7f,0x3dc9bf7f,0x3f273f42,0xbf27bf42,0xbeb83f6f,0x3eb8bf6f,0xbedbbf67,0xbedbbf67,0x3f18bf4e,0x3f18bf4e,0x3e2f3f7c,0xbe2fbf7c,0xbf4a3f1d,0x3f4abf1d,
0x3f800000,0x3f800000,0x3f62bef1,0x3f62bef1,0x3f7ebdfb,0xbf7e3dfb,0x3f51bf13,0xbf513f13,0x3f78be79,0x3f78be79,0x3f3ebf2c,0x3f3ebf2c,0x3f6fbeb8,0xbf6f3eb8,0x3f27bf42,0xbf273f42,
0x3f800000,0x3f800000,0xbef1bf62,0xbef1bf62,0x3f5fbefc,0xbf5f3efc,0xbf58bf09,0x3f583f09,0x3f04bf5c,0x3f04bf5c,0xbf80bd49,0xbf80bd49,0x3cc9bf80,0xbcc93f80,0xbf653ee6,0x3f65bee6,
0x3f800000,0x3f800000,0xbf623ef1,0xbf623ef1,0x3f1dbf4a,0xbf1d3f4a,0xbe2f3f7c,0x3e2fbf7c,0xbe79bf78,0xbe79bf78,0x3f2c3f3e,0x3f2c3f3e,0xbf6abecf,0x3f6a3ecf,0x3f7fbd97,0xbf7f3d97,
0x3f800000,0x3f800000,0x3ef13f62,0x3ef13f62,0x3e89bf77,0xbe893f77,0x3f7abe60,0xbf7a3e60,0xbf5cbf04,0xbf5cbf04,0x3d49bf80,0x3d49bf80,0xbf393f31,0x3f39bf31,0xbf73bea1,0x3f733ea1,
0x3f800000,0x3f800000,0x3f62bef1,0x3f62bef1,0xbdfbbf7e,0x3dfb3f7e,0xbf13bf51,0x3f133f51,0xbf783e79,0xbf783e79,0xbf3e3f2c,0xbf3e3f2c,0x3eb83f6f,0xbeb8bf6f,0x3f423f27,0xbf42bf27,
0x3f800000,0x3f800000,0xbef1bf62,0xbef1bf62,0xbefcbf5f,0x3efc3f5f,0xbf093f58,0x3f09bf58,0xbf043f5c,0xbf043f5c,0x3f803d49,0x3f803d49,0x3f803cc9,0xbf80bcc9,0xbee6bf65,0x3ee63f65,
0x3f800000,0x3f800000,0xbf623ef1,0xbf623ef1,0xbf4abf1d,0x3f4a3f1d,0x3f7c3e2f,0xbf7cbe2f,0x3e793f78,0x3e793f78,0xbf2cbf3e,0xbf2cbf3e,0x3ecfbf6a,0xbecf3f6a,0x3d973f7f,0xbd97bf7f,
0x3f800000,0x3f800000,0x3ef13f62,0x3ef13f62,0xbf77be89,0x3f773e89,0xbe60bf7a,0x3e603f7a,0x3f5c3f04,0x3f5c3f04,0xbd493f80,0xbd493f80,0xbf31bf39,0x3f313f39,0x3ea1bf73,0xbea13f73,
0x3f0ebf55,0x3f0ebf55,0x3dc9bf7f,0x3dc9bf7f,0x3ee6bf65,0xbee63f65,0xbcc9bf80,0x3cc93f80,0x3eacbf71,0x3eacbf71,0xbe16bf7d,0xbe16bf7d,0x3e60bf7a,0xbe603f7a,0xbe89bf77,0x3e893f77,
0xbf0e3f55,0xbf0e3f55,0x3f7f3dc9,0x3f7f3dc9,0xbd973f7f,0x3d97bf7f,0x3f6abecf,0xbf6a3ecf,0x3edb3f67,0x3edb3f67,0x3f18bf4e,0x3f18bf4e,0x3f513f13,0xbf51bf13,0x3dfbbf7e,0xbdfb3f7e,
0x3f0ebf55,0x3f0ebf55,0xbdc93f7f,0xbdc93f7f,0xbea1bf73,0x3ea13f73,0x3f393f31,0xbf39bf31,0xbf71beac,0xbf71beac,0x3f7dbe16,0x3f7dbe16,0xbf583f09,0x3f58bf09,0x3efcbf5f,0xbefc3f5f,
0xbf0e3f55,0xbf0e3f55,0xbf7fbdc9,0xbf7fbdc9,0x3f273f42,0xbf27bf42,0xbeb83f6f,0x3eb8bf6f,0x3f67bedb,0x3f67bedb,0x3f4e3f18,0x3f4e3f18,0xbe2fbf7c,0x3e2f3f7c,0x3f4abf1d,0xbf4a3f1d,
0x3f0ebf55,0x3f0ebf55,0x3dc9bf7f,0x3dc9bf7f,0xbf65bee6,0x3f653ee6,0xbf803cc9,0x3f80bcc9,0xbeac3f71,0xbeac3f71,0x3e163f7d,0x3e163f7d,0x3f7a3e60,0xbf7abe60,0x3f77be89,0xbf773e89,
0xbf0e3f55,0xbf0e3f55,0x3f7f3dc9,0x3f7f3dc9,0x3f7f3d97,0xbf7fbd97,0xbecfbf6a,0x3ecf3f6a,0xbedbbf67,0xbedbbf67,0xbf183f4e,0xbf183f4e,0xbf133f51,0x3f13bf51,0x3f7e3dfb,0xbf7ebdfb,
0x3f0ebf55,0x3f0ebf55,0xbdc93f7f,0xbdc93f7f,0xbf733ea1,0x3f73bea1,0x3f31bf39,0xbf313f39,0x3f713eac,0x3f713eac,0xbf7d3e16,0xbf7d3e16,0xbf09bf58,0x3f093f58,0x3f5f3efc,0xbf5fbefc,
0xbf0e3f55,0xbf0e3f55,0xbf7fbdc9,0xbf7fbdc9,0x3f42bf27,0xbf423f27,0x3f6f3eb8,0xbf6fbeb8,0xbf673edb,0xbf673edb,0xbf4ebf18,0xbf4ebf18,0x3f7cbe2f,0xbf7c3e2f,0x3f1d3f4a,0xbf1dbf4a,
0x3f803f80,0xbf0e3f0e,0x3f803f80,0xbf0e3f0e,0x3f803f80,0xbf0e3f0e,0x3f803f80,0xbf0e3f0e,0x3f803f80,0xbf0e3f0e,0x3f803f80,0xbf0e3f0e,0x3f803f80,0xbf0e3f0e,0x3f803f80,0xbf0e3f0e,
0x3f5f3f7e,0xbd973ee6,0xbf5fbf7e,0x3d97bee6,0x3e893f1d,0x3f27bea1,0xbe89bf1d,0xbf273ea1,0xbefcbdfb,0x3f7fbf65,0x3efc3dfb,0xbf7f3f65,0xbf77bf4a,0x3f42bf73,0x3f773f4a,0xbf423f73,
0x3f043f78,0x3edb3eac,0x3f043f78,0x3edb3eac,0xbf5cbe79,0x3f67bf71,0xbf5cbe79,0x3f67bf71,0xbf04bf78,0xbedbbeac,0xbf04bf78,0xbedbbeac,0x3f5c3e79,0xbf673f71,0x3f5c3e79,0xbf673f71,
0x3cc93f6f,0x3f513e60,0xbcc9bf6f,0xbf51be60,0xbf39bf6a,0xbe2fbf58,0x3f393f6a,0x3e2f3f58,0x3f803eb8,0xbf133f7a,0xbf80beb8,0x3f13bf7a,0xbf313ecf,0x3f7cbf09,0x3f31becf,0xbf7c3f09,
0xbef13f62,0x3f7f3dc9,0xbef13f62,0x3f7f3dc9,0x3ef1bf62,0xbf7fbdc9,0x3ef1bf62,0xbf7fbdc9,0xbef13f62,0x3f7f3dc9,0xbef13f62,0x3f7f3dc9,0x3ef1bf62,0xbf7fbdc9,0x3ef1bf62,0xbf7fbdc9,
0xbf583f51,0x3f6abcc9,0x3f58bf51,0xbf6a3cc9,0x3f7abe2f,0xbeb83f39,0xbf7a3e2f,0x3eb8bf39,0xbf09bf13,0xbecfbf80,0x3f093f13,0x3ecf3f80,0xbe603f7c,0x3f6f3f31,0x3e60bf7c,0xbf6fbf31,
0xbf803f3e,0x3f18be16,0xbf803f3e,0x3f18be16,0x3d493f2c,0x3f4e3f7d,0x3d493f2c,0x3f4e3f7d,0x3f80bf3e,0xbf183e16,0x3f80bf3e,0xbf183e16,0xbd49bf2c,0xbf4ebf7d,0xbd49bf2c,0xbf4ebf7d,
0xbf653f27,0x3dfbbe89,0x3f65bf27,0xbdfb3e89,0xbf733f7f,0x3f4a3efc,0x3f73bf7f,0xbf4abefc,0xbee63f42,0x3f7e3f77,0x3ee6bf42,0xbf7ebf77,0x3ea13d97,0x3f1d3f5f,0xbea1bd97,0xbf1dbf5f,
0,0xbf553f55,0,0xbf553f55,0,0xbf553f55,0,0xbf553f55,0,0xbf553f55,0,0xbf553f55,0,0xbf553f55,0,0xbf553f55,
0x3efc3dfb,0xbf7f3f65,0xbefcbdfb,0x3f7fbf65,0x3f773f4a,0xbf423f73,0xbf77bf4a,0x3f42bf73,0x3f5f3f7e,0xbd973ee6,0xbf5fbf7e,0x3d97bee6,0x3e893f1d,0x3f27bea1,0xbe89bf1d,0xbf273ea1,
0x3f5c3e79,0xbf673f71,0x3f5c3e79,0xbf673f71,0x3f043f78,0x3edb3eac,0x3f043f78,0x3edb3eac,0xbf5cbe79,0x3f67bf71,0xbf5cbe79,0x3f67bf71,0xbf04bf78,0xbedbbeac,0xbf04bf78,0xbedbbeac,
0x3f803eb8,0xbf133f7a,0xbf80beb8,0x3f13bf7a,0xbf313ecf,0x3f7cbf09,0x3f31becf,0xbf7c3f09,0xbcc9bf6f,0xbf51be60,0x3cc93f6f,0x3f513e60,0x3f393f6a,0x3e2f3f58,0xbf39bf6a,0xbe2fbf58,
0x3f623ef1,0xbdc93f7f,0x3f623ef1,0xbdc93f7f,0xbf62bef1,0x3dc9bf7f,0xbf62bef1,0x3dc9bf7f,0x3f623ef1,0xbdc93f7f,0x3f623ef1,0xbdc93f7f,0xbf62bef1,0x3dc9bf7f,0xbf62bef1,0x3dc9bf7f,
0x3f093f13,0x3ecf3f80,0xbf09bf13,0xbecfbf80,0x3e60bf7c,0xbf6fbf31,0xbe603f7c,0x3f6f3f31,0xbf583f51,0x3f6abcc9,0x3f58bf51,0xbf6a3cc9,0x3f7abe2f,0xbeb83f39,0xbf7a3e2f,0x3eb8bf39,
0x3d493f2c,0x3f4e3f7d,0x3d493f2c,0x3f4e3f7d,0x3f80bf3e,0xbf183e16,0x3f80bf3e,0xbf183e16,0xbd49bf2c,0xbf4ebf7d,0xbd49bf2c,0xbf4ebf7d,0xbf803f3e,0x3f18be16,0xbf803f3e,0x3f18be16,
0xbee63f42,0x3f7e3f77,0x3ee6bf42,0xbf7ebf77,0x3ea13d97,0x3f1d3f5f,0xbea1bd97,0xbf1dbf5f,0x3f65bf27,0xbdfb3e89,0xbf653f27,0x3dfbbe89,0x3f73bf7f,0xbf4abefc,0xbf733f7f,0x3f4a3efc,
0,0x3f55bf55,0,0x3f55bf55,0,0x3f55bf55,0,0x3f55bf55,0,0x3f55bf55,0,0x3f55bf55,0,0x3f55bf55,0,0x3f55bf55,
0xbefcbdfb,0x3f7fbf65,0x3efc3dfb,0xbf7f3f65,0xbf77bf4a,0x3f42bf73,0x3f773f4a,0xbf423f73,0xbf5fbf7e,0x3d97bee6,0x3f5f3f7e,0xbd973ee6,0xbe89bf1d,0xbf273ea1,0x3e893f1d,0x3f27bea1,
0xbf5cbe79,0x3f67bf71,0xbf5cbe79,0x3f67bf71,0xbf04bf78,0xbedbbeac,0xbf04bf78,0xbedbbeac,0x3f5c3e79,0xbf673f71,0x3f5c3e79,0xbf673f71,0x3f043f78,0x3edb3eac,0x3f043f78,0x3edb3eac,
0xbf80beb8,0x3f13bf7a,0x3f803eb8,0xbf133f7a,0x3f31becf,0xbf7c3f09,0xbf313ecf,0x3f7cbf09,0x3cc93f6f,0x3f513e60,0xbcc9bf6f,0xbf51be60,0xbf39bf6a,0xbe2fbf58,0x3f393f6a,0x3e2f3f58,
0xbf62bef1,0x3dc9bf7f,0xbf62bef1,0x3dc9bf7f,0x3f623ef1,0xbdc93f7f,0x3f623ef1,0xbdc93f7f,0xbf62bef1,0x3dc9bf7f,0xbf62bef1,0x3dc9bf7f,0x3f623ef1,0xbdc93f7f,0x3f623ef1,0xbdc93f7f,
0xbf09bf13,0xbecfbf80,0x3f093f13,0x3ecf3f80,0xbe603f7c,0x3f6f3f31,0x3e60bf7c,0xbf6fbf31,0x3f58bf51,0xbf6a3cc9,0xbf583f51,0x3f6abcc9,0xbf7a3e2f,0x3eb8bf39,0x3f7abe2f,0xbeb83f39,
0xbd49bf2c,0xbf4ebf7d,0xbd49bf2c,0xbf4ebf7d,0xbf803f3e,0x3f18be16,0xbf803f3e,0x3f18be16,0x3d493f2c,0x3f4e3f7d,0x3d493f2c,0x3f4e3f7d,0x3f80bf3e,0xbf183e16,0x3f80bf3e,0xbf183e16,
0x3ee6bf42,0xbf7ebf77,0xbee63f42,0x3f7e3f77,0xbea1bd97,0xbf1dbf5f,0x3ea13d97,0x3f1d3f5f,0xbf653f27,0x3dfbbe89,0x3f65bf27,0xbdfb3e89,0xbf733f7f,0x3f4a3efc,0x3f73bf7f,0xbf4abefc,
0x3f800000,0x3f7ff84a,0x3f800000,0x3f6afb8c,0x3f7fe129,0x3f7fba9e,0x3f2f61a5,0x3eadf73c,0x3f7f84ab,0x3f7f3f54,0xbd7b2b74,0xbee79a5d,0x3f7eea9d,0x3f7e868b,0xbf44e3f5,0xbf75a67b,
0x3f800000,0x3f7f7808,0x3f800000,0x3f65b710,0x3f7de0b1,0x3f7b3bab,0x3f1c420c,0x3e4ada4f,0x3f778bc5,0x3f72d4eb,0xbe827dc0,0xbf27ce61,0x3f6d1c1d,0x3f666771,0xbf6be858,0xbf7f90b1,
0x3f800000,0x3f7e5a38,0x3f800000,0x3f5fe4e9,0x3f796e4e,0x3f714c7a,0x3f07a136,0x3d55880e,0x3f660f88,0x3f57dc7f,0xbee0924f,0xbf51c0c2,0x3f46e22a,0x3f33587a,0xbf7e9bc9,0xbf6b99fb,
0x3f800000,0x3f7c9f8a,0x3f800000,0x3f5988ad,0x3f7294f8,0x3f62241a,0x3ee363fa,0xbdc27c39,0x3f4bbbf8,0x3f2ff3e6,0xbf1b02c6,0xbf6f20b0,0x3f0f8784,0x3ed6a399,0xbf7b61fc,0xbf3c17d9,
0x3f800000,0x3f7a4910,0x3f800000,0x3f52a649,0x3f696591,0x3f4e1689,0x3eb554ec,0xbe75c35a,0x3f299415,0x3efafef7,0xbf3fc767,0xbf7e2b72,0x3e97a117,0x3db5f8da,0xbf628210,0xbeed3063,
0x3f800000,0x3f77583a,0x3f800000,0x3f4b41fa,0x3f5df6be,0x3f3592e7,0x3e8586ce,0xbec27b55,0x3f00e7e4,0x3e870ada,0xbf5d2d53,0xbf7dfa38,0x3bc90f88,0xbe80f8c0,0xbf36206c,0xbe0cec4a,
0x3f800000,0x3f73ced9,0x3f800000,0x3f436051,0x3f5064af,0x3f19210f,0x3e28defc,0xbf02ef9f,0x3ea68f12,0x3cafea69,0xbf721352,0xbf6e8ff8,0xbe919ddd,0xbf102dd5,0xbef41f07,0x3e5101f1,
0x3f800000,0x3f6faf1b,0x3f800000,0x3f3b0629,0x3f40d0da,0x3ef2bd43,0x3d8a200a,0xbf21cbfb,0x3e09cf86,0xbe636c83,0xbf7dabcc,0xbf50d937,0xbf0cead0,0xbf4f0417,0xbe4dee60,0x3f05a02c,
0,0x3c7b514b,0,0x3ecb2aae,0x3cfb49ba,0x3d3c6dd5,0x3f3a7ca4,0x3f70c501,0x3d7b2b74,0x3d9cecf9,0x3f7f84ab,0x3f644fac,0x3dbc3ac3,0x3ddb7d37,0x3f239da9,0x3e901c2c,
0,0x3d83db0a,0,0x3ee1fb6a,0x3e039502,0x3e44b0b9,0x3f4ac77f,0x3f7aed37,0x3e827dc0,0x3ea21887,0x3f778bc5,0x3f4154e1,0x3ec1071e,0x3edf28a9,0x3ec6d529,0xbd6ea038,
0,0x3de7fa9a,0,0x3ef840c8,0x3e667c66,0x3eab0201,0x3f591e6a,0x3f7fa6e3,0x3ee0924f,0x3f099f4e,0x3f660f88,0x3f12c39a,0x3f212ff9,0x3f36ad7f,0x3dd53db9,0xbec8477c,
0,0x3e25c58c,0,0x3f06f686,0x3ea395c5,0x3eeff7fb,0x3f655e0b,0x3f7ed7d4,0x3f1b02c6,0x3f39f2ac,0x3f4bbbf8,0x3eb6ccc3,0x3f53fac3,0x3f686b39,0xbe419b37,0xbf2da859,
0,0x3e57278f,0,0x3f11796b,0x3ed25a09,0x3f17de12,0x3f6f6830,0x3f788486,0x3f3fc767,0x3f5f20db,0x3f299415,0x3df475c0,0x3f748422,0x3f7efcc9,0xbeee9479,0xbf62df7b,
0,0x3e840270,0,0x3f1ba299,0x3eff17b2,0x3f34768f,0x3f772417,0x3f6cd007,0x3f5d2d53,0x3f76ef5b,0x3f00e7e4,0xbe007745,0x3f7ffec4,0x3f77beb7,0xbf33e7bc,0xbf7d906e,
0,0x3e9c1faf,0,0x3f256bcb,0x3f14b039,0x3f4d26fd,0x3f7c7eb0,0x3f5bfb34,0x3f721352,0x3f7ff0e3,0x3ea68f12,0xbeb9bb1e,0x3f756d97,0x3f5389c7,0xbf6106f2,0xbf7a9c59,
0,0x3eb3dca5,0,0x3f2ecef7,0x3f286605,0x3f61668a,0x3f7f6ac7,0x3f466354,0x3f7dabcc,0x3f799b43,0x3e09cf86,0xbf140c5f,0x3f55b993,0x3f16999f,0xbf7ac516,0xbf5a5ba0,
0x354ccccd,0x354ccccd,0x354ccccd,0x354ccccd,0x354ccccd,0x354ccccd,0x354ccccd,0x354ccccd,0x354ccccd,0x354ccccd,0x354ccccd,0x354ccccd,0x354ccccd,0x354ccccd,0x354ccccd,0x354ccccd,
0x354c6a23,0x3546096a,0xb348ef90,0xb450c934,0x35380c6c,0x3522fcc6,0xb4b3a83f,0xb4f8046f,0x3507a9aa,0x34ce3fd4,0xb5196c52,0xb530f10f,0x34853f42,0x33dc7f3e,0xb541a90f,0xb54aefd6,
0x354cc6a2,0x354c6006,0x353bfc70,0x3537c5a7,0x354b7b60,0x354a193c,0x35331d87,0x352e06f1,0x35483a73,0x3545e02f,0x35288507,0x35229b2e,0x35430be1,0x353fbf49,0x351c4d0e,0x35159e88,
0x354c32aa,0x354243ef,0xb4b9484b,0xb5063eb4,0x352cb065,0x350cc31e,0xb527cd68,0xb53f4d5a,0x34c8cbf9,0x3458115e,0xb54b55f5,0xb54b2e94,0x328cbb87,0xb435f068,0xb53ed993,0xb527142c,
0x354cb421,0x354b1a27,0x350c4e1d,0x34fa0347,0x35478b72,0x354210c7,0x34d901f0,0x34b5e995,0x353ab7a7,0x35319232,0x349110bd,0x3455a47e,0x3526b6f3,0x351a40ae,0x340718ca,0x335d000f,
0x354beee4,0x353db017,0xb51d832a,0xb53cb9e0,0x351f1b54,0x34e5a5a1,0xb54bafd4,0xb5491b30,0x34729b58,0x31a0d93a,0xb53534da,0xb511b389,0xb468fc95,0xb4e177b4,0xb4c34c06,0xb424beb3,
0x354c954b,0x3548fc89,0x348b2c30,0x3422483f,0x354109fb,0x3534e9ae,0x332ad33e,0xb39b9694,0x3524ded4,0x35114253,0xb4449c48,0xb49b95de,0x34f501b2,0x34c23103,0xb4d17f65,0xb5016ffc,
0x354b9ed5,0x353852c1,0xb544852f,0xb54c73c1,0x350f79fb,0x34abb614,0xb53c7b2f,0xb516797a,0x339193e2,0xb44e5acd,0xb4bdc04f,0xb3e17a10,0xb4e6afbb,0xb5259ce0,0x342734c1,0x34d5cd14,
0,0,0,0,0,0,0,0,0,0,0,0,0,0,0,0,
0x3348ef90,0x3450c934,0x354c6a23,0x3546096a,0x34b3a83f,0x34f8046f,0x35380c6c,0x3522fcc6,0x35196c52,0x3530f10f,0x3507a9aa,0x34ce3fd4,0x3541a90f,0x354aefd6,0x34853f42,0x33dc7f3e,
0x32490dd6,0x3352f811,0x34a2888b,0x34b4c922,0x33b99548,0x34049e0a,0x34c69a3a,0x34d7f0d6,0x342c1fa5,0x3453371a,0x34e8c245,0x34f90428,0x3479cc4b,0x348fe3b7,0x3504563c,0x350bd8c6,
0x337b14c1,0x3481ad39,0x3536a623,0x351aaa4d,0x34dc3217,0x3514c224,0x34ead291,0x34923d69,0x353280af,0x35458c49,0x33c39166,0xb3cd8ba2,0x354cc0b6,0x3547af69,0xb49495b2,0xb4ece099,
0x32c907c8,0x33d28804,0x35153084,0x35223933,0x34386384,0x3482de37,0x352db1ef,0x35377e6f,0x34a84807,0x34cc12f5,0x353f868d,0x3545b679,0x34ede6c2,0x3506b804,0x3549fef3,0x354c556c,
0x33969569,0x349a6c18,0x3502e487,0x349f10ee,0x3500f32d,0x35299568,0x33aa97c7,0xb41ae293,0x35439ce8,0x354ccbd0,0xb4bedd2d,0xb50fec97,0x354457ac,0x352afadc,0xb534058e,0xb5489dab,
0x3316be44,0x341d5a2e,0x35409d9b,0x3548bdc6,0x3488ce67,0x34bff996,0x354c8582,0x354bdfdd,0x34f2fcea,0x35105ed9,0x3546d06b,0x353d7339,0x35241f31,0x35345208,0x352ffc2a,0x351eb5dd,
0x33af9760,0x34b286ed,0x3466937a,0xb33ee693,0x35122466,0x3539ef61,0xb4a03930,0xb50aed14,0x354bfd6e,0x3546322c,0xb5357f95,0xb54ad9f2,0x35293b06,0x34f0f5cb,0xb5487d14,0xb52eafb3,
0x3f80,0x3f80,0x3f0e3f55,0x3f0e3f55,0x3e163f7d,0xbe16bf7d,0x3f2c3f3e,0xbf2cbf3e,0x3e953f75,0x3e953f75,0x3f463f22,0x3f463f22,0x3edb3f67,0xbedbbf67,0x3f5c3f04,0xbf5cbf04,
0x3f80,0x3f80,0x3f55bf0e,0x3f55bf0e,0x3f043f5c,0xbf04bf5c,0x3edbbf67,0xbedb3f67,0x3f623ef1,0x3f623ef1,0xbdc9bf7f,0xbdc9bf7f,0x3f80bd49,0xbf803d49,0xbf18bf4e,0x3f183f4e,
0x3f80,0x3f80,0xbf0ebf55,0xbf0ebf55,0x3f4e3f18,0xbf4ebf18,0xbf80bd49,0x3f803d49,0x3f75be95,0x3f75be95,0xbf223f46,0xbf223f46,0x3eacbf71,0xbeac3f71,0x3e793f78,0xbe79bf78,
0x3f80,0x3f80,0xbf553f0e,0xbf553f0e,0x3f783e79,0xbf78be79,0x3eac3f71,0xbeacbf71,0x3ef1bf62,0x3ef1bf62,0x3f7fbdc9,0x3f7fbdc9,0xbf3ebf2c,0x3f3e3f2c,0x3e16bf7d,0xbe163f7d,
0x3f80,0x3f80,0x3f0e3f55,0x3f0e3f55,0x3f7dbe16,0xbf7d3e16,0x3f3ebf2c,0xbf3e3f2c,0xbe95bf75,0xbe95bf75,0xbf46bf22,0xbf46bf22,0xbf673edb,0x3f67bedb,0xbf043f5c,0x3f04bf5c,
0x3f80,0x3f80,0x3f55bf0e,0x3f55bf0e,0x3f5cbf04,0xbf5c3f04,0xbf67bedb,0x3f673edb,0xbf62bef1,0xbf62bef1,0x3dc93f7f,0x3dc93f7f,0x3d493f80,0xbd49bf80,0x3f4ebf18,0xbf4e3f18,
0x3f80,0x3f80,0xbf0ebf55,0xbf0ebf55,0x3f18bf4e,0xbf183f4e,0xbd493f80,0x3d49bf80,0xbf753e95,0xbf753e95,0x3f22bf46,0x3f22bf46,0x3f713eac,0xbf71beac,0xbf783e79,0x3f78be79,
0x3f80,0x3f80,0xbf553f0e,0xbf553f0e,0x3e79bf78,0xbe793f78,0x3f71beac,0xbf713eac,0xbef13f62,0xbef13f62,0xbf7f3dc9,0xbf7f3dc9,0x3f2cbf3e,0xbf2c3f3e,0x3f7d3e16,0xbf7dbe16,
0x3f6d3ec4,0x3f6d3ec4,0x3f7bbe48,0x3f7bbe48,0x3f783e79,0xbf78be79,0x3f71beac,0xbf713eac,0x3f7f3dc9,0x3f7f3dc9,0x3f62bef1,0x3f62bef1,0x3f80bd49,0xbf803d49,0x3f4ebf18,0xbf4e3f18,
0xbf6dbec4,0xbf6dbec4,0x3e483f7b,0x3e483f7b,0xbf7d3e16,0x3f7dbe16,0x3f2c3f3e,0xbf2cbf3e,0xbf463f22,0xbf463f22,0x3f753e95,0x3f753e95,0xbeac3f71,0x3eacbf71,0x3f78be79,0xbf783e79,
0x3f6d3ec4,0x3f6d3ec4,0xbf7b3e48,0xbf7b3e48,0x3f5cbf04,0xbf5c3f04,0xbedb3f67,0x3edbbf67,0x3dc9bf7f,0x3dc9bf7f,0x3ef13f62,0x3ef13f62,0xbf3ebf2c,0x3f3e3f2c,0x3f7d3e16,0xbf7dbe16,
0xbf6dbec4,0xbf6dbec4,0xbe48bf7b,0xbe48bf7b,0xbf183f4e,0x3f18bf4e,0xbf80bd49,0x3f803d49,0x3f223f46,0x3f223f46,0xbe953f75,0xbe953f75,0x3f67bedb,0xbf673edb,0x3f5c3f04,0xbf5cbf04,
0x3f6d3ec4,0x3f6d3ec4,0x3f7bbe48,0x3f7bbe48,0x3e79bf78,0xbe793f78,0xbeacbf71,0x3eac3f71,0xbf7fbdc9,0xbf7fbdc9,0xbf623ef1,0xbf623ef1,0x3d493f80,0xbd49bf80,0x3f183f4e,0xbf18bf4e,
0xbf6dbec4,0xbf6dbec4,0x3e483f7b,0x3e483f7b,0x3e163f7d,0xbe16bf7d,0x3f3ebf2c,0xbf3e3f2c,0x3f46bf22,0x3f46bf22,0xbf75be95,0xbf75be95,0xbf71beac,0x3f713eac,0x3e793f78,0xbe79bf78,
0x3f6d3ec4,0x3f6d3ec4,0xbf7b3e48,0xbf7b3e48,0xbf04bf5c,0x3f043f5c,0x3f673edb,0xbf67bedb,0xbdc93f7f,0xbdc93f7f,0xbef1bf62,0xbef1bf62,0x3f2cbf3e,0xbf2c3f3e,0xbe163f7d,0x3e16bf7d,
0xbf6dbec4,0xbf6dbec4,0xbe48bf7b,0xbe48bf7b,0x3f4e3f18,0xbf4ebf18,0xbd493f80,0x3d49bf80,0xbf22bf46,0xbf22bf46,0x3e95bf75,0x3e95bf75,0x3edb3f67,0xbedbbf67,0xbf043f5c,0x3f04bf5c,
0x3f800000,0x3f800000,0x3f55bf0e,0x3f55bf0e,0x3f7dbe16,0xbf7d3e16,0x3f3ebf2c,0xbf3e3f2c,0x3f75be95,0x3f75be95,0x3f22bf46,0x3f22bf46,0x3f67bedb,0xbf673edb,0x3f04bf5c,0xbf043f5c,
0x3f800000,0x3f800000,0xbf0ebf55,0xbf0ebf55,0x3f5cbf04,0xbf5c3f04,0xbf67bedb,0x3f673edb,0x3ef1bf62,0x3ef1bf62,0xbf7f3dc9,0xbf7f3dc9,0xbd49bf80,0x3d493f80,0xbf4e3f18,0x3f4ebf18,
0x3f800000,0x3f800000,0xbf553f0e,0xbf553f0e,0x3f18bf4e,0xbf183f4e,0xbd493f80,0x3d49bf80,0xbe95bf75,0xbe95bf75,0x3f463f22,0x3f463f22,0xbf71beac,0x3f713eac,0x3f78be79,0xbf783e79,
0x3f800000,0x3f800000,0x3f0e3f55,0x3f0e3f55,0x3e79bf78,0xbe793f78,0x3f71beac,0xbf713eac,0xbf62bef1,0xbf62bef1,0xbdc9bf7f,0xbdc9bf7f,0xbf2c3f3e,0x3f2cbf3e,0xbf7dbe16,0x3f7d3e16,
0x3f800000,0x3f800000,0x3f55bf0e,0x3f55bf0e,0xbe16bf7d,0x3e163f7d,0xbf2cbf3e,0x3f2c3f3e,0xbf753e95,0xbf753e95,0xbf223f46,0xbf223f46,0x3edb3f67,0xbedbbf67,0x3f5c3f04,0xbf5cbf04,
0x3f800000,0x3f800000,0xbf0ebf55,0xbf0ebf55,0xbf04bf5c,0x3f043f5c,0xbedb3f67,0x3edbbf67,0xbef13f62,0xbef13f62,0x3f7fbdc9,0x3f7fbdc9,0x3f80bd49,0xbf803d49,0xbf18bf4e,0x3f183f4e,
0x3f800000,0x3f800000,0xbf553f0e,0xbf553f0e,0xbf4ebf18,0x3f4e3f18,0x3f803d49,0xbf80bd49,0x3e953f75,0x3e953f75,0xbf46bf22,0xbf46bf22,0x3eacbf71,0xbeac3f71,0x3e793f78,0xbe79bf78,
0x3f800000,0x3f800000,0x3f0e3f55,0x3f0e3f55,0xbf78be79,0x3f783e79,0xbeacbf71,0x3eac3f71,0x3f623ef1,0x3f623ef1,0x3dc93f7f,0x3dc93f7f,0xbf3ebf2c,0x3f3e3f2c,0x3e16bf7d,0xbe163f7d,
0x3ec4bf6d,0x3ec4bf6d,0xbe48bf7b,0xbe48bf7b,0x3e79bf78,0xbe793f78,0xbeacbf71,0x3eac3f71,0x3dc9bf7f,0x3dc9bf7f,0xbef1bf62,0xbef1bf62,0xbd49bf80,0x3d493f80,0xbf18bf4e,0x3f183f4e,
0xbec43f6d,0xbec43f6d,0x3f7bbe48,0x3f7bbe48,0x3e163f7d,0xbe16bf7d,0x3f3ebf2c,0xbf3e3f2c,0x3f223f46,0x3f223f46,0x3e95bf75,0x3e95bf75,0x3f713eac,0xbf71beac,0xbe79bf78,0x3e793f78,
0x3ec4bf6d,0x3ec4bf6d,0x3e483f7b,0x3e483f7b,0xbf04bf5c,0x3f043f5c,0x3f673edb,0xbf67bedb,0xbf7fbdc9,0xbf7fbdc9,0x3f62bef1,0x3f62bef1,0xbf2c3f3e,0x3f2cbf3e,0x3e16bf7d,0xbe163f7d,
0xbec43f6d,0xbec43f6d,0xbf7b3e48,0xbf7b3e48,0x3f4e3f18,0xbf4ebf18,0xbd493f80,0x3d49bf80,0x3f46bf22,0x3f46bf22,0x3f753e95,0x3f753e95,0xbedbbf67,0x3edb3f67,0x3f04bf5c,0xbf043f5c,
0x3ec4bf6d,0x3ec4bf6d,0xbe48bf7b,0xbe48bf7b,0xbf78be79,0x3f783e79,0xbf713eac,0x3f71beac,0xbdc93f7f,0xbdc93f7f,0x3ef13f62,0x3ef13f62,0x3f80bd49,0xbf803d49,0x3f4ebf18,0xbf4e3f18,
0xbec43f6d,0xbec43f6d,0x3f7bbe48,0x3f7bbe48,0x3f7dbe16,0xbf7d3e16,0xbf2cbf3e,0x3f2c3f3e,0xbf22bf46,0xbf22bf46,0xbe953f75,0xbe953f75,0xbeac3f71,0x3eacbf71,0x3f78be79,0xbf783e79,
0x3ec4bf6d,0x3ec4bf6d,0x3e483f7b,0x3e483f7b,0xbf5c3f04,0x3f5cbf04,0x3edbbf67,0xbedb3f67,0x3f7f3dc9,0x3f7f3dc9,0xbf623ef1,0xbf623ef1,0xbf3ebf2c,0x3f3e3f2c,0x3f7d3e16,0xbf7dbe16,
0xbec43f6d,0xbec43f6d,0xbf7b3e48,0xbf7b3e48,0x3f18bf4e,0xbf183f4e,0x3f803d49,0xbf80bd49,0xbf463f22,0xbf463f22,0xbf75be95,0xbf75be95,0x3f67bedb,0xbf673edb,0x3f5c3f04,0xbf5cbf04,
0x3f803f80,0xbec43ec4,0x3f803f80,0xbec43ec4,0x3f803f80,0xbec43ec4,0x3f803f80,0xbec43ec4,0x3f803f80,0xbec43ec4,0x3f803f80,0xbec43ec4,0x3f803f80,0xbec43ec4,0x3f803f80,0xbec43ec4,
0x3f5c3f7d,0x3e163e79,0xbf5cbf7d,0xbe16be79,0x3e793f18,0x3f4ebf04,0xbe79bf18,0xbf4e3f04,0xbf04be16,0x3f7dbf78,0x3f043e16,0xbf7d3f78,0xbf78bf4e,0x3f18bf5c,0x3f783f4e,0xbf183f5c,
0x3ef13f75,0x3f223dc9,0x3ef13f75,0x3f223dc9,0xbf62be95,0x3f46bf7f,0xbf62be95,0x3f46bf7f,0xbef1bf75,0xbf22bdc9,0xbef1bf75,0xbf22bdc9,0x3f623e95,0xbf463f7f,0x3f623e95,0xbf463f7f,
0xbd493f67,0x3f71bd49,0x3d49bf67,0xbf713d49,0xbf2cbf71,0xbedbbf2c,0x3f2c3f71,0x3edb3f2c,0x3f803edb,0xbeac3f80,0xbf80bedb,0x3eacbf80,0xbf3e3eac,0x3f67bf3e,0x3f3ebeac,0xbf673f3e,
0xbf0e3f55,0x3f7bbe48,0xbf0e3f55,0x3f7bbe48,0x3f0ebf55,0xbf7b3e48,0x3f0ebf55,0xbf7b3e48,0xbf0e3f55,0x3f7bbe48,0xbf0e3f55,0x3f7bbe48,0x3f0ebf55,0xbf7b3e48,0x3f0ebf55,0xbf7b3e48,
0xbf673f3e,0x3f3ebeac,0x3f67bf3e,0xbf3e3eac,0x3f71bd49,0xbd493f67,0xbf713d49,0x3d49bf67,0xbedbbf2c,0xbf2cbf71,0x3edb3f2c,0x3f2c3f71,0xbeac3f80,0x3f803edb,0x3eacbf80,0xbf80bedb,
0xbf7f3f22,0x3e95bef1,0xbf7f3f22,0x3e95bef1,0xbdc93f46,0x3f753f62,0xbdc93f46,0x3f753f62,0x3f7fbf22,0xbe953ef1,0x3f7fbf22,0xbe953ef1,0x3dc9bf46,0xbf75bf62,0x3dc9bf46,0xbf75bf62,
0xbf4e3f04,0xbe79bf18,0x3f4ebf04,0x3e793f18,0xbf7d3f78,0x3f043e16,0x3f7dbf78,0xbf04be16,0xbf183f5c,0x3f783f4e,0x3f18bf5c,0xbf78bf4e,0x3e163e79,0x3f5c3f7d,0xbe16be79,0xbf5cbf7d,
0,0xbf6d3f6d,0,0xbf6d3f6d,0,0xbf6d3f6d,0,0xbf6d3f6d,0,0xbf6d3f6d,0,0xbf6d3f6d,0,0xbf6d3f6d,0,0xbf6d3f6d,
0x3f043e16,0xbf7d3f78,0xbf04be16,0x3f7dbf78,0x3f783f4e,0xbf183f5c,0xbf78bf4e,0x3f18bf5c,0x3f5c3f7d,0x3e163e79,0xbf5cbf7d,0xbe16be79,0x3e793f18,0x3f4ebf04,0xbe79bf18,0xbf4e3f04,
0x3f623e95,0xbf463f7f,0x3f623e95,0xbf463f7f,0x3ef13f75,0x3f223dc9,0x3ef13f75,0x3f223dc9,0xbf62be95,0x3f46bf7f,0xbf62be95,0x3f46bf7f,0xbef1bf75,0xbf22bdc9,0xbef1bf75,0xbf22bdc9,
0x3f803edb,0xbeac3f80,0xbf80bedb,0x3eacbf80,0xbf3e3eac,0x3f67bf3e,0x3f3ebeac,0xbf673f3e,0x3d49bf67,0xbf713d49,0xbd493f67,0x3f71bd49,0x3f2c3f71,0x3edb3f2c,0xbf2cbf71,0xbedbbf2c,
0x3f553f0e,0x3e483f7b,0x3f553f0e,0x3e483f7b,0xbf55bf0e,0xbe48bf7b,0xbf55bf0e,0xbe48bf7b,0x3f553f0e,0x3e483f7b,0x3f553f0e,0x3e483f7b,0xbf55bf0e,0xbe48bf7b,0xbf55bf0e,0xbe48bf7b,
0x3edb3f2c,0x3f2c3f71,0xbedbbf2c,0xbf2cbf71,0x3eacbf80,0xbf80bedb,0xbeac3f80,0x3f803edb,0xbf673f3e,0x3f3ebeac,0x3f67bf3e,0xbf3e3eac,0x3f71bd49,0xbd493f67,0xbf713d49,0x3d49bf67,
0xbdc93f46,0x3f753f62,0xbdc93f46,0x3f753f62,0x3f7fbf22,0xbe953ef1,0x3f7fbf22,0xbe953ef1,0x3dc9bf46,0xbf75bf62,0x3dc9bf46,0xbf75bf62,0xbf7f3f22,0x3e95bef1,0xbf7f3f22,0x3e95bef1,
0xbf183f5c,0x3f783f4e,0x3f18bf5c,0xbf78bf4e,0x3e163e79,0x3f5c3f7d,0xbe16be79,0xbf5cbf7d,0x3f4ebf04,0x3e793f18,0xbf4e3f04,0xbe79bf18,0x3f7dbf78,0xbf04be16,0xbf7d3f78,0x3f043e16,
0,0x3f6dbf6d,0,0x3f6dbf6d,0,0x3f6dbf6d,0,0x3f6dbf6d,0,0x3f6dbf6d,0,0x3f6dbf6d,0,0x3f6dbf6d,0,0x3f6dbf6d,
0xbf04be16,0x3f7dbf78,0x3f043e16,0xbf7d3f78,0xbf78bf4e,0x3f18bf5c,0x3f783f4e,0xbf183f5c,0xbf5cbf7d,0xbe16be79,0x3f5c3f7d,0x3e163e79,0xbe79bf18,0xbf4e3f04,0x3e793f18,0x3f4ebf04,
0xbf62be95,0x3f46bf7f,0xbf62be95,0x3f46bf7f,0xbef1bf75,0xbf22bdc9,0xbef1bf75,0xbf22bdc9,0x3f623e95,0xbf463f7f,0x3f623e95,0xbf463f7f,0x3ef13f75,0x3f223dc9,0x3ef13f75,0x3f223dc9,
0xbf80bedb,0x3eacbf80,0x3f803edb,0xbeac3f80,0x3f3ebeac,0xbf673f3e,0xbf3e3eac,0x3f67bf3e,0xbd493f67,0x3f71bd49,0x3d49bf67,0xbf713d49,0xbf2cbf71,0xbedbbf2c,0x3f2c3f71,0x3edb3f2c,
0xbf55bf0e,0xbe48bf7b,0xbf55bf0e,0xbe48bf7b,0x3f553f0e,0x3e483f7b,0x3f553f0e,0x3e483f7b,0xbf55bf0e,0xbe48bf7b,0xbf55bf0e,0xbe48bf7b,0x3f553f0e,0x3e483f7b,0x3f553f0e,0x3e483f7b,
0xbedbbf2c,0xbf2cbf71,0x3edb3f2c,0x3f2c3f71,0xbeac3f80,0x3f803edb,0x3eacbf80,0xbf80bedb,0x3f67bf3e,0xbf3e3eac,0xbf673f3e,0x3f3ebeac,0xbf713d49,0x3d49bf67,0x3f71bd49,0xbd493f67,
0x3dc9bf46,0xbf75bf62,0x3dc9bf46,0xbf75bf62,0xbf7f3f22,0x3e95bef1,0xbf7f3f22,0x3e95bef1,0xbdc93f46,0x3f753f62,0xbdc93f46,0x3f753f62,0x3f7fbf22,0xbe953ef1,0x3f7fbf22,0xbe953ef1,
0x3f18bf5c,0xbf78bf4e,0xbf183f5c,0x3f783f4e,0xbe16be79,0xbf5cbf7d,0x3e163e79,0x3f5c3f7d,0xbf4e3f04,0xbe79bf18,0x3f4ebf04,0x3e793f18,0xbf7d3f78,0x3f043e16,0x3f7dbf78,0xbf04be16,
0x3f800000,0x3f7ff4e6,0x3f800000,0x3f6aab7b,0x3f7fd397,0x3f7f9c18,0x3f2e3bde,0x3ea986c4,0x3f7f4e6d,0x3f7eea9d,0xbd96a905,0xbeee9479,0x3f7e70b0,0x3f7de0b1,0xbf47de65,0xbf772417,
0x3f800000,0x3f7f6ac7,0x3f800000,0x3f655e0b,0x3f7dabcc,0x3f7ac516,0x3f1b02c6,0x3e419b37,0x3f76ba07,0x3f718f57,0xbe888e93,0xbf2ac082,0x3f6b4b0c,0x3f63f473,0xbf6db293,0xbf7f2f9d,
0x3f800000,0x3f7e4323,0x3f800000,0x3f5f8327,0x3f791298,0x3f708066,0x3f064b82,0x3d2fe007,0x3f64aa59,0x3f55b993,0xbee63375,0xbf53fac3,0x3f43e200,0x3f2f61a5,0xbf7f0e58,0xbf696591,
0x3f800000,0x3f7c7eb0,0x3f800000,0x3f591e6a,0x3f721352,0x3f6106f2,0x3ee0924f,0xbdd53db9,0x3f49d112,0x3f2d1469,0xbf1d7fd1,0xbf708066,0x3f0b9a6b,0x3ecc9b8b,0xbf7a7302,0xbf385216,
0x3f800000,0x3f7a1e84,0x3f800000,0x3f5233c6,0x3f68bf3c,0x3f4cae79,0x3eb263ef,0xbe7ee6e1,0x3f273656,0x3ef41f07,0xbf41d870,0xbf7e9bc9,0x3e8e9a22,0x3d8a200a,0xbf604621,0xbee363fa,
0x3f800000,0x3f772417,0x3f800000,0x3f4ac77f,0x3f5d2d53,0x3f33e7bc,0x3e827dc0,0xbec6d529,0x3efc5d27,0x3e7ee6e1,0xbf5ebe05,0xbf7d7474,0xbc490e90,0xbe8b9507,0xbf32c8c9,0xbdee3876,
0x3f800000,0x3f73913f,0x3f800000,0x3f42de29,0x3f4f7a1f,0x3f173c07,0x3e22abb6,0xbf04f484,0x3ea09ae5,0x3bc90f88,0xbf731447,0xbf6d1c1d,0xbe9aa086,0xbf14b039,0xbeebcbbb,0x3e667c66,
0x3f800000,0x3f6f6830,0x3f800000,0x3f3a7ca4,0x3f3fc767,0x3eee9479,0x3d7b2b74,0xbf239da9,0x3dfab273,0xbe72b651,0xbf7e1324,0xbf4e8d90,0xbf10d3cd,0xbf5233c6,0xbe3b6ecf,0x3f0a48ad,
0,0x3c96c9b6,0,0x3ecc9b8b,0x3d16c32c,0x3d621469,0x3f3b8f3b,0x3f718f57,0x3d96a905,0x3dbc3ac3,0x3f7f4e6d,0x3f628210,0x3de1bc2e,0x3e039502,0x3f1ff6cb,0x3e8586ce,
0,0x3d8a200a,0,0x3ee363fa,0x3e09cf86,0x3e4dee60,0x3f4bbbf8,0x3f7b61fc,0x3e888e93,0x3ea986c4,0x3f76ba07,0x3f3ebc1b,0x3ec9b953,0x3ee900b7,0x3ebe1d4a,0xbda3308c,
0,0x3dee3876,0,0x3ef9a02d,0x3e6c9a7f,0x3eaf713a,0x3f59f26a,0x3f7fc38f,0x3ee63375,0x3f0cead0,0x3f64aa59,0x3f0f8784,0x3f24d225,0x3f3a7ca4,0x3dafb680,0xbed25a09,
0,0x3e28defc,0,0x3f07a136,0x3ea68f12,0x3ef41f07,0x3f660f88,0x3f7e9bc9,0x3f1d7fd1,0x3f3ca003,0x3f49d112,0x3eaf713a,0x3f5695e5,0x3f6aab7b,0xbe541501,0xbf31a81d,
0,0x3e5a3997,0,0x3f121eb0,0x3ed53641,0x3f19c200,0x3f6ff573,0x3f77f110,0x3f41d870,0x3f6106f2,0x3f273656,0x3dd53db9,0x3f75dec6,0x3f7f6ac7,0xbef6e0cb,0xbf655e0b,
0,0x3e8586ce,0,0x3f1c420c,0x3f00e7e4,0x3f36206c,0x3f778bc5,0x3f6be858,0x3f5ebe05,0x3f77f110,0x3efc5d27,0xbe1008b7,0x3f7ffb11,0x3f764d97,0xbf373a23,0xbf7e4323,
0,0x3e9d9e78,0,0x3f26050a,0x3f15f6d9,0x3f4e8d90,0x3f7cbfc9,0x3f5ac450,0x3f731447,0x3f7ffec4,0x3ea09ae5,0xbec1071e,0x3f740bdd,0x3f5064af,0xbf633c5a,0xbf796e4e,
0,0x3eb554ec,0,0x3f2f61a5,0x3f299415,0x3f628210,0x3f7f84ab,0x3f44e3f5,0x3f7e1324,0x3f78b47b,0x3dfab273,0xbf173c07,0x3f531849,0x3f121eb0,0xbf7baccd,0xbf577026,
0x354ccccd,0x354ccccd,0x354ccccd,0x354ccccd,0x354ccccd,0x354ccccd,0x354ccccd,0x354ccccd,0x354ccccd,0x354ccccd,0x354ccccd,0x354ccccd,0x354ccccd,0x354ccccd,0x354ccccd,0x354ccccd,
0x354c3ebe,0x3545619f,0xb3710e6e,0xb45a7db8,0x3536eeae,0x3521740f,0xb4b8292a,0xb4fbffb5,0x3505c511,0x34c9e41f,0xb51b138d,0xb532319e,0x34807bea,0x33c88ec2,0xb54276a0,0xb54b4283,
0x354cc3eb,0x354c556c,0x353bbc62,0x35377e6f,0x354b68e9,0x3549fef3,0x3532cf52,0x352db1ef,0x3548186a,0x3545b679,0x3528296b,0x35223933,0x3542da99,0x353f868d,0x351be4ed,0x35153084,
0x354beee4,0x35413f79,0xb4bedd2d,0xb5089a01,0x352afadc,0x350a76bb,0xb5299568,0xb54066b8,0x34c34c06,0x344bebe7,0xb54bafd4,0xb54ac390,0x31a0d93a,0xb4422b74,0xb53db017,0xb5253e0d,
0x354ca946,0x354aefd6,0x350b6318,0x34f8046f,0x35474213,0x3541a90f,0x34d6df37,0x34b3a83f,0x353a3296,0x3530f10f,0x348eb659,0x3450c934,0x3525fb4c,0x35196c52,0x340222f8,0x3348ef90,
0x354b8d5a,0x353c3c09,0xb51fe51e,0xb53e2876,0x351cb4cd,0x34df5d78,0xb54c0b7a,0xb5485c01,0x346429d0,0xb220d873,0xb5336b4e,0xb50f0707,0xb477673d,0xb4e7b948,0xb4bca2fc,0xb415f23f,
0x354c7ce0,0x35489dab,0x34879f03,0x341ae293,0x354066b8,0x3534058e,0x330cb338,0xb3aa97c7,0x3523bec8,0x350fec97,0xb44bebe7,0xb49f10ee,0x34f1f9a5,0x34bedd2d,0xb4d4ba6c,0xb502e487,
0x354b1a27,0x35365d28,0xb545b679,0xb54c2618,0x350c4e1d,0x34a3afa2,0xb53ab7a7,0xb51374de,0x335d000f,0xb45f54d8,0xb4b5e995,0xb3be9392,0xb4ede6c2,0xb528296b,0x34386384,0x34dd4116,
0,0,0,0,0,0,0,0,0,0,0,0,0,0,0,0,
0x33710e6e,0x345a7db8,0x354c3ebe,0x3545619f,0x34b8292a,0x34fbffb5,0x3536eeae,0x3521740f,0x351b138d,0x3532319e,0x3505c511,0x34c9e41f,0x354276a0,0x354b4283,0x34807bea,0x33c88ec2,
0x327142bd,0x335d000f,0x34a3afa2,0x34b5e995,0x33be9392,0x340718ca,0x34c7b357,0x34d901f0,0x342e9479,0x3455a47e,0x34e9cab3,0x34fa0347,0x347c30c0,0x349110bd,0x3504d0d5,0x350c4e1d,
0x33969569,0x34879f03,0x353534da,0x3518967c,0x34e177b4,0x3516e669,0x34e5a5a1,0x348c5a95,0x3534058e,0x35465a74,0x33aa97c7,0xb3e67457,0x354ccbd0,0x3546f6c8,0xb49a6c18,0xb4f1f9a5,
0x32f13846,0x33dc7f3e,0x35160c2f,0x3522fcc6,0x343d4866,0x34853f42,0x352e5b88,0x35380c6c,0x34aa91ce,0x34ce3fd4,0x353ff78f,0x3546096a,0x34eff15b,0x3507a9aa,0x354a3307,0x354c6a23,
0x33b4968b,0x34a1610f,0x34fff144,0x3498176e,0x3503db51,0x352bab1e,0x338c9200,0xb429aa67,0x3544b238,0x354cc8da,0xb4c580a2,0xb51294e9,0x35433cb1,0x3528e03a,0xb535c9e1,0xb549570a,
0x3334dd20,0x3424beb3,0x35413f79,0x35491b30,0x348c5a95,0x34c34c06,0x354c9c72,0x354bafd4,0x34f60334,0x3511b389,0x35465a74,0x353cb9e0,0x35253e0d,0x353534da,0x352f0373,0x351d832a,
0x33d28804,0x34ba66f9,0x3455a47e,0xb3828d3d,0x35153084,0x353bbc62,0xb4a84807,0xb50e2017,0x354c556c,0x35450adf,0xb5377e6f,0xb54b68e9,0x3526b6f3,0x34e9cab3,0xb5478b72,0xb52c59b8,
0x3f80,0x3f80,0x3f223f46,0x3f223f46,0x3e2f3f7c,0xbe2fbf7c,0x3f423f27,0xbf42bf27,0x3eac3f71,0x3eac3f71,0x3f5c3f04,0x3f5c3f04,0x3efc3f5f,0xbefcbf5f,0x3f6f3eb8,0xbf6fbeb8,
0x3f80,0x3f80,0x3f46bf22,0x3f46bf22,0x3f093f58,0xbf09bf58,0x3ea1bf73,0xbea13f73,0x3f673edb,0x3f673edb,0xbe79bf78,0xbe79bf78,0x3f7ebdfb,0xbf7e3dfb,0xbf39bf31,0x3f393f31,
0x3f80,0x3f80,0xbf22bf46,0xbf22bf46,0x3f513f13,0xbf51bf13,0xbf7f3d97,0x3f7fbd97,0x3f71beac,0x3f71beac,0xbf043f5c,0xbf043f5c,0x3e89bf77,0xbe893f77,0x3ecf3f6a,0xbecfbf6a,
0x3f80,0x3f80,0xbf463f22,0xbf463f22,0x3f7a3e60,0xbf7abe60,0x3ee63f65,0xbee6bf65,0x3edbbf67,0x3edbbf67,0x3f78be79,0x3f78be79,0xbf4abf1d,0x3f4a3f1d,0xbcc9bf80,0x3cc93f80,
0x3f80,0x3f80,0x3f223f46,0x3f223f46,0x3f7cbe2f,0xbf7c3e2f,0x3f27bf42,0xbf273f42,0xbeacbf71,0xbeacbf71,0xbf5cbf04,0xbf5cbf04,0xbf5f3efc,0x3f5fbefc,0xbeb83f6f,0x3eb8bf6f,
0x3f80,0x3f80,0x3f46bf22,0x3f46bf22,0x3f58bf09,0xbf583f09,0xbf73bea1,0x3f733ea1,0xbf67bedb,0xbf67bedb,0x3e793f78,0x3e793f78,0x3dfb3f7e,0xbdfbbf7e,0x3f31bf39,0xbf313f39,
0x3f80,0x3f80,0xbf22bf46,0xbf22bf46,0x3f13bf51,0xbf133f51,0x3d973f7f,0xbd97bf7f,0xbf713eac,0xbf713eac,0x3f04bf5c,0x3f04bf5c,0x3f773e89,0xbf77be89,0xbf6a3ecf,0x3f6abecf,
0x3f80,0x3f80,0xbf463f22,0xbf463f22,0x3e60bf7a,0xbe603f7a,0x3f65bee6,0xbf653ee6,0xbedb3f67,0xbedb3f67,0xbf783e79,0xbf783e79,0x3f1dbf4a,0xbf1d3f4a,0x3f80bcc9,0xbf803cc9,
0x3f7b3e48,0x3f7b3e48,0x3f62bef1,0x3f62bef1,0x3f803cc9,0xbf80bcc9,0x3f4abf1d,0xbf4a3f1d,0x3f7dbe16,0x3f7dbe16,0x3f2cbf3e,0x3f2cbf3e,0x3f73bea1,0xbf733ea1,0x3f09bf58,0xbf093f58,
0xbf7bbe48,0xbf7bbe48,0x3ef13f62,0x3ef13f62,0xbf6f3eb8,0x3f6fbeb8,0x3f5f3efc,0xbf5fbefc,0xbf183f4e,0xbf183f4e,0x3f80bd49,0x3f80bd49,0xbd973f7f,0x3d97bf7f,0x3f51bf13,0xbf513f13,
0x3f7b3e48,0x3f7b3e48,0xbf623ef1,0xbf623ef1,0x3f39bf31,0xbf393f31,0xbdfb3f7e,0x3dfbbf7e,0xbe16bf7d,0xbe16bf7d,0x3f3e3f2c,0x3f3e3f2c,0xbf65bee6,0x3f653ee6,0x3f7abe60,0xbf7a3e60,
0xbf7bbe48,0xbf7bbe48,0xbef1bf62,0xbef1bf62,0xbecf3f6a,0x3ecfbf6a,0xbf773e89,0x3f77be89,0x3f4e3f18,0x3f4e3f18,0x3d493f80,0x3d493f80,0x3f42bf27,0xbf423f27,0x3f7c3e2f,0xbf7cbe2f,
0x3f7b3e48,0x3f7b3e48,0x3f62bef1,0x3f62bef1,0x3cc9bf80,0xbcc93f80,0xbf1dbf4a,0x3f1d3f4a,0xbf7d3e16,0xbf7d3e16,0xbf2c3f3e,0xbf2c3f3e,0x3ea13f73,0xbea1bf73,0x3f583f09,0xbf58bf09,
0xbf7bbe48,0xbf7bbe48,0x3ef13f62,0x3ef13f62,0x3eb83f6f,0xbeb8bf6f,0x3efcbf5f,0xbefc3f5f,0x3f18bf4e,0x3f18bf4e,0xbf803d49,0xbf803d49,0xbf7fbd97,0x3f7f3d97,0x3f133f51,0xbf13bf51,
0x3f7b3e48,0x3f7b3e48,0xbf623ef1,0xbf623ef1,0xbf31bf39,0x3f313f39,0x3f7e3dfb,0xbf7ebdfb,0x3e163f7d,0x3e163f7d,0xbf3ebf2c,0xbf3ebf2c,0x3ee6bf65,0xbee63f65,0x3e603f7a,0xbe60bf7a,
0xbf7bbe48,0xbf7bbe48,0xbef1bf62,0xbef1bf62,0x3f6a3ecf,0xbf6abecf,0x3e893f77,0xbe89bf77,0xbf4ebf18,0xbf4ebf18,0xbd49bf80,0xbd49bf80,0x3f273f42,0xbf27bf42,0xbe2f3f7c,0x3e2fbf7c,
0x3f800000,0x3f800000,0x3f46bf22,0x3f46bf22,0x3f7cbe2f,0xbf7c3e2f,0x3f27bf42,0xbf273f42,0x3f71beac,0x3f71beac,0x3f04bf5c,0x3f04bf5c,0x3f5fbefc,0xbf5f3efc,0x3eb8bf6f,0xbeb83f6f,
0x3f800000,0x3f800000,0xbf22bf46,0xbf22bf46,0x3f58bf09,0xbf583f09,0xbf73bea1,0x3f733ea1,0x3edbbf67,0x3edbbf67,0xbf783e79,0xbf783e79,0xbdfbbf7e,0x3dfb3f7e,0xbf313f39,0x3f31bf39,
0x3f800000,0x3f800000,0xbf463f22,0xbf463f22,0x3f13bf51,0xbf133f51,0x3d973f7f,0xbd97bf7f,0xbeacbf71,0xbeacbf71,0x3f5c3f04,0x3f5c3f04,0xbf77be89,0x3f773e89,0x3f6abecf,0xbf6a3ecf,
0x3f800000,0x3f800000,0x3f223f46,0x3f223f46,0x3e60bf7a,0xbe603f7a,0x3f65bee6,0xbf653ee6,0xbf67bedb,0xbf67bedb,0xbe79bf78,0xbe79bf78,0xbf1d3f4a,0x3f1dbf4a,0xbf803cc9,0x3f80bcc9,
0x3f800000,0x3f800000,0x3f46bf22,0x3f46bf22,0xbe2fbf7c,0x3e2f3f7c,0xbf42bf27,0x3f423f27,0xbf713eac,0xbf713eac,0xbf043f5c,0xbf043f5c,0x3efc3f5f,0xbefcbf5f,0x3f6f3eb8,0xbf6fbeb8,
0x3f800000,0x3f800000,0xbf22bf46,0xbf22bf46,0xbf09bf58,0x3f093f58,0xbea13f73,0x3ea1bf73,0xbedb3f67,0xbedb3f67,0x3f78be79,0x3f78be79,0x3f7ebdfb,0xbf7e3dfb,0xbf39bf31,0x3f393f31,
0x3f800000,0x3f800000,0xbf463f22,0xbf463f22,0xbf51bf13,0x3f513f13,0x3f7fbd97,0xbf7f3d97,0x3eac3f71,0x3eac3f71,0xbf5cbf04,0xbf5cbf04,0x3e89bf77,0xbe893f77,0x3ecf3f6a,0xbecfbf6a,
0x3f800000,0x3f800000,0x3f223f46,0x3f223f46,0xbf7abe60,0x3f7a3e60,0xbee6bf65,0x3ee63f65,0x3f673edb,0x3f673edb,0x3e793f78,0x3e793f78,0xbf4abf1d,0x3f4a3f1d,0xbcc9bf80,0x3cc93f80,
0x3e48bf7b,0x3e48bf7b,0xbef1bf62,0xbef1bf62,0x3cc9bf80,0xbcc93f80,0xbf1dbf4a,0x3f1d3f4a,0xbe16bf7d,0xbe16bf7d,0xbf3ebf2c,0xbf3ebf2c,0xbea1bf73,0x3ea13f73,0xbf58bf09,0x3f583f09,
0xbe483f7b,0xbe483f7b,0x3f62bef1,0x3f62bef1,0x3eb83f6f,0xbeb8bf6f,0x3efcbf5f,0xbefc3f5f,0x3f4e3f18,0x3f4e3f18,0xbd49bf80,0xbd49bf80,0x3f7f3d97,0xbf7fbd97,0xbf13bf51,0x3f133f51,
0x3e48bf7b,0x3e48bf7b,0x3ef13f62,0x3ef13f62,0xbf31bf39,0x3f313f39,0x3f7e3dfb,0xbf7ebdfb,0xbf7d3e16,0xbf7d3e16,0x3f2cbf3e,0x3f2cbf3e,0xbee63f65,0x3ee6bf65,0xbe60bf7a,0x3e603f7a,
0xbe483f7b,0xbe483f7b,0xbf623ef1,0xbf623ef1,0x3f6a3ecf,0xbf6abecf,0x3e893f77,0xbe89bf77,0x3f18bf4e,0x3f18bf4e,0x3f80bd49,0x3f80bd49,0xbf27bf42,0x3f273f42,0x3e2fbf7c,0xbe2f3f7c,
0x3e48bf7b,0x3e48bf7b,0xbef1bf62,0xbef1bf62,0xbf80bcc9,0x3f803cc9,0xbf4a3f1d,0x3f4abf1d,0x3e163f7d,0x3e163f7d,0x3f3e3f2c,0x3f3e3f2c,0x3f73bea1,0xbf733ea1,0x3f09bf58,0xbf093f58,
0xbe483f7b,0xbe483f7b,0x3f62bef1,0x3f62bef1,0x3f6fbeb8,0xbf6f3eb8,0xbf5fbefc,0x3f5f3efc,0xbf4ebf18,0xbf4ebf18,0x3d493f80,0x3d493f80,0xbd973f7f,0x3d97bf7f,0x3f51bf13,0xbf513f13,
0x3e48bf7b,0x3e48bf7b,0x3ef13f62,0x3ef13f62,0xbf393f31,0x3f39bf31,0x3dfbbf7e,0xbdfb3f7e,0x3f7dbe16,0x3f7dbe16,0xbf2c3f3e,0xbf2c3f3e,0xbf65bee6,0x3f653ee6,0x3f7abe60,0xbf7a3e60,
0xbe483f7b,0xbe483f7b,0xbf623ef1,0xbf623ef1,0x3ecfbf6a,0xbecf3f6a,0x3f77be89,0xbf773e89,0xbf183f4e,0xbf183f4e,0xbf803d49,0xbf803d49,0x3f42bf27,0xbf423f27,0x3f7c3e2f,0xbf7cbe2f,
0x3f803f80,0xbe483e48,0x3f803f80,0xbe483e48,0x3f803f80,0xbe483e48,0x3f803f80,0xbe483e48,0x3f803f80,0xbe483e48,0x3f803f80,0xbe483e48,0x3f803f80,0xbe483e48,0x3f803f80,0xbe483e48,
0x3f583f7c,0x3eb83cc9,0xbf58bf7c,0xbeb8bcc9,0x3e603f13,0x3f6abf31,0xbe60bf13,0xbf6a3f31,0xbf09be2f,0x3f6fbf80,0x3f093e2f,0xbf6f3f80,0xbf7abf51,0x3ecfbf39,0x3f7a3f51,0xbecf3f39,
0x3edb3f71,0x3f4ebe16,0x3edb3f71,0x3f4ebe16,0xbf67beac,0x3f18bf7d,0xbf67beac,0x3f18bf7d,0xbedbbf71,0xbf4e3e16,0xbedbbf71,0xbf4e3e16,0x3f673eac,0xbf183f7d,0x3f673eac,0xbf183f7d,
0xbdfb3f5f,0x3f7fbea1,0x3dfbbf5f,0xbf7f3ea1,0xbf1dbf77,0xbf27bee6,0x3f1d3f77,0x3f273ee6,0x3f7e3efc,0xbd973f73,0xbf7ebefc,0x3d97bf73,0xbf4a3e89,0x3f42bf65,0x3f4abe89,0xbf423f65,
0xbf223f46,0x3f62bef1,0xbf223f46,0x3f62bef1,0x3f22bf46,0xbf623ef1,0x3f22bf46,0xbf623ef1,0xbf223f46,0x3f62bef1,0xbf223f46,0x3f62bef1,0x3f22bf46,0xbf623ef1,0x3f22bf46,0xbf623ef1,
0xbf733f27,0x3efcbf1d,0x3f73bf27,0xbefc3f1d,0x3f653d97,0x3e893f7e,0xbf65bd97,0xbe89bf7e,0xbea1bf42,0xbf5fbf4a,0x3ea13f42,0x3f5f3f4a,0xbee63f7f,0x3f773dfb,0x3ee6bf7f,0xbf77bdfb,
0xbf783f04,0xbd49bf3e,0xbf783f04,0xbd49bf3e,0xbe793f5c,0x3f803f2c,0xbe793f5c,0x3f803f2c,0x3f78bf04,0x3d493f3e,0x3f78bf04,0x3d493f3e,0x3e79bf5c,0xbf80bf2c,0x3e79bf5c,0xbf80bf2c,
0xbf313eb8,0xbf13bf58,0x3f31beb8,0x3f133f58,0xbf803f6a,0x3e2fbe60,0x3f80bf6a,0xbe2f3e60,0xbf393f6f,0x3f513f09,0x3f39bf6f,0xbf51bf09,0xbcc93ecf,0x3f7c3f7a,0x3cc9becf,0xbf7cbf7a,
0,0xbf7b3f7b,0,0xbf7b3f7b,0,0xbf7b3f7b,0,0xbf7b3f7b,0,0xbf7b3f7b,0,0xbf7b3f7b,0,0xbf7b3f7b,0,0xbf7b3f7b,
0x3f093e2f,0xbf6f3f80,0xbf09be2f,0x3f6fbf80,0x3f7a3f51,0xbecf3f39,0xbf7abf51,0x3ecfbf39,0x3f583f7c,0x3eb83cc9,0xbf58bf7c,0xbeb8bcc9,0x3e603f13,0x3f6abf31,0xbe60bf13,0xbf6a3f31,
0x3f673eac,0xbf183f7d,0x3f673eac,0xbf183f7d,0x3edb3f71,0x3f4ebe16,0x3edb3f71,0x3f4ebe16,0xbf67beac,0x3f18bf7d,0xbf67beac,0x3f18bf7d,0xbedbbf71,0xbf4e3e16,0xbedbbf71,0xbf4e3e16,
0x3f7e3efc,0xbd973f73,0xbf7ebefc,0x3d97bf73,0xbf4a3e89,0x3f42bf65,0x3f4abe89,0xbf423f65,0x3dfbbf5f,0xbf7f3ea1,0xbdfb3f5f,0x3f7fbea1,0x3f1d3f77,0x3f273ee6,0xbf1dbf77,0xbf27bee6,
0x3f463f22,0x3ef13f62,0x3f463f22,0x3ef13f62,0xbf46bf22,0xbef1bf62,0xbf46bf22,0xbef1bf62,0x3f463f22,0x3ef13f62,0x3f463f22,0x3ef13f62,0xbf46bf22,0xbef1bf62,0xbf46bf22,0xbef1bf62,
0x3ea13f42,0x3f5f3f4a,0xbea1bf42,0xbf5fbf4a,0x3ee6bf7f,0xbf77bdfb,0xbee63f7f,0x3f773dfb,0xbf733f27,0x3efcbf1d,0x3f73bf27,0xbefc3f1d,0x3f653d97,0x3e893f7e,0xbf65bd97,0xbe89bf7e,
0xbe793f5c,0x3f803f2c,0xbe793f5c,0x3f803f2c,0x3f78bf04,0x3d493f3e,0x3f78bf04,0x3d493f3e,0x3e79bf5c,0xbf80bf2c,0x3e79bf5c,0xbf80bf2c,0xbf783f04,0xbd49bf3e,0xbf783f04,0xbd49bf3e,
0xbf393f6f,0x3f513f09,0x3f39bf6f,0xbf51bf09,0xbcc93ecf,0x3f7c3f7a,0x3cc9becf,0xbf7cbf7a,0x3f31beb8,0x3f133f58,0xbf313eb8,0xbf13bf58,0x3f80bf6a,0xbe2f3e60,0xbf803f6a,0x3e2fbe60,
0,0x3f7bbf7b,0,0x3f7bbf7b,0,0x3f7bbf7b,0,0x3f7bbf7b,0,0x3f7bbf7b,0,0x3f7bbf7b,0,0x3f7bbf7b,0,0x3f7bbf7b,
0xbf09be2f,0x3f6fbf80,0x3f093e2f,0xbf6f3f80,0xbf7abf51,0x3ecfbf39,0x3f7a3f51,0xbecf3f39,0xbf58bf7c,0xbeb8bcc9,0x3f583f7c,0x3eb83cc9,0xbe60bf13,0xbf6a3f31,0x3e603f13,0x3f6abf31,
0xbf67beac,0x3f18bf7d,0xbf67beac,0x3f18bf7d,0xbedbbf71,0xbf4e3e16,0xbedbbf71,0xbf4e3e16,0x3f673eac,0xbf183f7d,0x3f673eac,0xbf183f7d,0x3edb3f71,0x3f4ebe16,0x3edb3f71,0x3f4ebe16,
0xbf7ebefc,0x3d97bf73,0x3f7e3efc,0xbd973f73,0x3f4abe89,0xbf423f65,0xbf4a3e89,0x3f42bf65,0xbdfb3f5f,0x3f7fbea1,0x3dfbbf5f,0xbf7f3ea1,0xbf1dbf77,0xbf27bee6,0x3f1d3f77,0x3f273ee6,
0xbf46bf22,0xbef1bf62,0xbf46bf22,0xbef1bf62,0x3f463f22,0x3ef13f62,0x3f463f22,0x3ef13f62,0xbf46bf22,0xbef1bf62,0xbf46bf22,0xbef1bf62,0x3f463f22,0x3ef13f62,0x3f463f22,0x3ef13f62,
0xbea1bf42,0xbf5fbf4a,0x3ea13f42,0x3f5f3f4a,0xbee63f7f,0x3f773dfb,0x3ee6bf7f,0xbf77bdfb,0x3f73bf27,0xbefc3f1d,0xbf733f27,0x3efcbf1d,0xbf65bd97,0xbe89bf7e,0x3f653d97,0x3e893f7e,
0x3e79bf5c,0xbf80bf2c,0x3e79bf5c,0xbf80bf2c,0xbf783f04,0xbd49bf3e,0xbf783f04,0xbd49bf3e,0xbe793f5c,0x3f803f2c,0xbe793f5c,0x3f803f2c,0x3f78bf04,0x3d493f3e,0x3f78bf04,0x3d493f3e,
0x3f39bf6f,0xbf51bf09,0xbf393f6f,0x3f513f09,0x3cc9becf,0xbf7cbf7a,0xbcc93ecf,0x3f7c3f7a,0xbf313eb8,0xbf13bf58,0x3f31beb8,0x3f133f58,0xbf803f6a,0x3e2fbe60,0x3f80bf6a,0xbe2f3e60,
0x3f800000,0x3f7ff0e3,0x3f800000,0x3f6a5ad9,0x3f7fc38f,0x3f7f7808,0x3f2d1469,0x3ea5129f,0x3f7f0e58,0x3f7e868b,0xbdafb680,0xbef58035,0x3f7de0b1,0x3f7d1cdd,0xbf4ac77f,0xbf788486,
0x3f800000,0x3f7f5ce9,0x3f800000,0x3f650479,0x3f7d7474,0x3f7a4910,0x3f19c200,0x3e3857ec,0x3f75dec6,0x3f703b37,0xbe8e9a22,0xbf2da859,0x3f696591,0x3f61668a,0xbf6f6830,0xbf7eb069,
0x3f800000,0x3f7e2b72,0x3f800000,0x3f5f20db,0x3f78b47b,0x3f6faf1b,0x3f04f484,0x3d0a342f,0x3f633c5a,0x3f5389c7,0xbeebcbbb,0xbf5627fe,0x3f40d0da,0x3f2b561b,0xbf7f6ac7,0xbf671599,
0x3f800000,0x3f7c5d3a,0x3f800000,0x3f58b3a1,0x3f718f57,0x3f5fe4e9,0x3eddbe79,0xbde7fa9a,0x3f47de65,0x3f2a2a80,0xbf1ff6cb,0xbf71d19f,0x3f07a136,0x3ec27b55,0xbf796e4e,0xbf34768f,
0x3f800000,0x3f79f35e,0x3f800000,0x3f51c0c2,0x3f6816a8,0x3f4b41fa,0x3eaf713a,0xbe840270,0x3f24d225,0x3eed3063,0xbf43e200,0xbf7efcc9,0x3e8586ce,0x3d3c6dd5,0xbf5df6be,0xbed97cb9,
0x3f800000,0x3f76ef5b,0x3f800000,0x3f4a4c87,0x3f5c61c7,0x3f3238aa,0x3e7ee6e1,0xbecb2aae,0x3ef6e0cb,0x3e6fa8b2,0xbf604621,0xbf7cdf6c,0xbcfb49ba,0xbe9620d2,0xbf2f61a5,0xbdc27c39,
0x3f800000,0x3f73530e,0x3f800000,0x3f425b89,0x3f4e8d90,0x3f1553b7,0x3e1c76de,0xbf06f686,0x3e9aa086,0xbc16cb58,0xbf740bdd,0xbf6b99fb,0xbea395c5,0xbf19210f,0xbee363fa,0x3e7bdba4,
0x3f800000,0x3f6f20b0,0x3f800000,0x3f39f2ac,0x3f3ebc1b,0x3eea6681,0x3d621469,0xbf256bcb,0x3de1bc2e,0xbe80f8c0,0xbf7e70b0,0xbf4c3578,0xbf14b039,0xbf554aa4,0xbe28defc,0x3f0ee0db,
0,0x3cafea69,0,0x3ece0bea,0x3d2fe007,0x3d83db0a,0x3f3ca003,0x3f725470,0x3dafb680,0x3ddb7d37,0x3f7f0e58,0x3f60a6cf,0x3e039502,0x3e195be0,0x3f1c420c,0x3e75c35a,
0,0x3d9064b4,0,0x3ee4cbfe,0x3e1008b7,0x3e57278f,0x3f4cae79,0x3f7bd14d,0x3e8e9a22,0x3eb0eacb,0x3f75dec6,0x3f3c17d9,0x3ed25a09,0x3ef2bd43,0x3eb554ec,0xbdcefdb7,
0,0x3df475c0,0,0x3efafef7,0x3e72b651,0x3eb3dca5,0x3f5ac450,0x3f7fdaaf,0x3eebcbbb,0x3f102dd5,0x3f633c5a,0x3f0c42c9,0x3f286605,0x3f3e35c5,0x3d8a200a,0xbedc53c1,
0,0x3e2bf804,0,0x3f084b92,0x3ea986c4,0x3ef840c8,0x3f66becc,0x3f7e5a38,0x3f1ff6cb,0x3f3f41fc,0x3f47de65,0x3ea80b1f,0x3f591e6a,0x3f6cd007,0xbe667c66,0xbf3592e7,
0,0x3e5d4b1a,0,0x3f12c39a,0x3ed8106b,0x3f1ba299,0x3f708066,0x3f77583a,0x3f43e200,0x3f62df7b,0x3f24d225,0x3db5f8da,0x3f772417,0x3f7fba9e,0xbeff17b2,0xbf67c187,
0,0x3e870ada,0,0x3f1ce11f,0x3f0242b1,0x3f37c655,0x3f77f110,0x3f6afb8c,0x3f604621,0x3f78e3d6,0x3ef6e0cb,0xbe1f917b,0x3f7fe129,0x3f74bf62,0xbf3a7ca4,0xbf7ed7d4,
0,0x3e9f1cdf,0,0x3f269de3,0x3f173c07,0x3f4fefa8,0x3f7cfe73,0x3f5988ad,0x3f740bdd,0x3f7ffd39,0x3e9aa086,0xbec8477c,0x3f7294f8,0x3f4d26fd,0xbf655e0b,0xbf7822d1,
0,0x3eb6ccc3,0,0x3f2ff3e6,0x3f2ac082,0x3f6398ac,0x3f7f9c18,0x3f436051,0x3f7e70b0,0x3f77beb7,0x3de1bc2e,0xbf1a6293,0x3f5064af,0x3f0d9281,0xbf7c7eb0,0xbf546b3b,
0x354ccccd,0x354ccccd,0x354ccccd,0x354ccccd,0x354ccccd,0x354ccccd,0x354ccccd,0x354ccccd,0x354ccccd,0x354ccccd,0x354ccccd,0x354ccccd,0x354ccccd,0x354ccccd,0x354ccccd,0x354ccccd,
0x354c0b7a,0x3544b238,0xb38c9200,0xb46429d0,0x3535c9e1,0x351fe51e,0xb4bca2fc,0xb4fff144,0x3503db51,0x34c580a2,0xb51cb4cd,0xb5336b4e,0x3477673d,0x33b4968b,0xb5433cb1,0xb54b8d5a,
0x354cc0b6,0x354c4a54,0x353b7be1,0x353736c7,0x354b55f5,0x3549e42e,0x353280af,0x352d5c81,0x3547f5e5,0x35458c49,0x3527cd68,0x3521d6d2,0x3542a8d8,0x353f4d5a,0x351b7c6d,0x3514c224,
0x354b9ed5,0x35402f5f,0xb4c46691,0xb50aed14,0x35293b06,0x35082200,0xb52b5332,0xb5417480,0x34bdc04f,0x343fba28,0xb54bfd6e,0xb54a4c56,0xb1f1455a,0xb44e5acd,0xb53c7b2f,0xb5235df9,
0x354c9c72,0x354ac390,0x350a76bb,0x34f60334,0x3546f6c8,0x35413f79,0x34d4ba6c,0x34b1652e,0x3539abba,0x35304e38,0x348c5a95,0x344bebe7,0x35253e0d,0x3518967c,0x33fa57c9,0x3334dd20,
0x354b1a27,0x353ab7a7,0xb5223933,0xb53f868d,0x351a40ae,0x34d901f0,0xb54c556c,0xb5478b72,0x3455a47e,0xb2c907c8,0xb5319232,0xb50c4e1d,0xb482de37,0xb4ede6c2,0xb4b5e995,0xb40718ca,
0x354c6006,0x35483a73,0x34840ee5,0x3413798a,0x353fbf49,0x35331d87,0x32dd204b,0xb3b99548,0x35229b2e,0x350e93bb,0xb453371a,0xb4a2888b,0x34eeec58,0x34bb8534,0xb4d7f0d6,0xb504563c,
0x354a7d7e,0x35345208,0xb546d06b,0xb54bc054,0x350911af,0x349b95de,0xb538de14,0xb5105ed9,0x3316be44,0xb4703484,0xb4adfd61,0xb39b9694,0xb4f501b2,0xb52aa21d,0x34497c83,0x34e49af8,
0,0,0,0,0,0,0,0,0,0,0,0,0,0,0,0,
0x338c9200,0x346429d0,0x354c0b7a,0x3544b238,0x34bca2fc,0x34fff144,0x3535c9e1,0x351fe51e,0x351cb4cd,0x35336b4e,0x3503db51,0x34c580a2,0x35433cb1,0x354b8d5a,0x3477673d,0x33b4968b,
0x328cbb87,0x33670786,0x34a4d655,0x34b70998,0x33c39166,0x34099337,0x34c8cbf9,0x34da1284,0x343108e1,0x3458115e,0x34ead291,0x34fb01cb,0x347e9498,0x34923d69,0x35054b1c,0x350cc31e,
0x33af9760,0x348d88a2,0x3533b8a6,0x3516797a,0x34e6afbb,0x35190197,0x34e06adb,0x34866f4c,0x35357f95,0x35471cab,0x339193e2,0xb3ff4f2b,0x354cca94,0x3546322c,0xb4a03930,0xb4f7041e,
0x330cb338,0x33e67457,0x3516e669,0x3523bec8,0x34422b74,0x34879f03,0x352f0373,0x353898a3,0x34acd9f0,0x34d06ab5,0x354066b8,0x35465a74,0x34f1f9a5,0x35089a01,0x354a6529,0x354c7ce0,
0x33d28804,0x34a84807,0x34fa0347,0x349110bd,0x3506b804,0x352db1ef,0x335d000f,0xb4386384,0x3545b679,0x354cb421,0xb4cc12f5,0xb5153084,0x354210c7,0x3526b6f3,0xb5377e6f,0xb549fef3,
0x3352f811,0x342c1fa5,0x3541dd26,0x3549743e,0x348fe3b7,0x34c69a3a,0x354caef3,0x354b7b60,0x34f90428,0x35130511,0x3545e02f,0x353bfc70,0x35265953,0x353613bd,0x352e06f1,0x351c4d0e,
0x33f55fcc,0x34c23103,0x34449c48,0xb3a597c6,0x35182b04,0x353d7339,0xb4b04301,0xb5114253,0x354c954b,0x3543cc4e,0xb539679f,0xb54bdfdd,0x35241f31,0x34e28401,0xb5468241,0xb529ef63,
0x3f80,0x3f80,0x3f353f35,0x3f353f35,0x3e483f7b,0xbe48bf7b,0x3f553f0e,0xbf55bf0e,0x3ec43f6d,0x3ec43f6d,0x3f6d3ec4,0x3f6d3ec4,0x3f0e3f55,0xbf0ebf55,0x3f7b3e48,0xbf7bbe48,
0x3f80,0x3f80,0x3f35bf35,0x3f35bf35,0x3f0e3f55,0xbf0ebf55,0x3e48bf7b,0xbe483f7b,0x3f6d3ec4,0x3f6d3ec4,0xbec4bf6d,0xbec4bf6d,0x3f7bbe48,0xbf7b3e48,0xbf55bf0e,0x3f553f0e,
0x3f80,0x3f80,0xbf35bf35,0xbf35bf35,0x3f553f0e,0xbf55bf0e,0xbf7b3e48,0x3f7bbe48,0x3f6dbec4,0x3f6dbec4,0xbec43f6d,0xbec43f6d,0x3e48bf7b,0xbe483f7b,0x3f0e3f55,0xbf0ebf55,
0x3f80,0x3f80,0xbf353f35,0xbf353f35,0x3f7b3e48,0xbf7bbe48,0x3f0e3f55,0xbf0ebf55,0x3ec4bf6d,0x3ec4bf6d,0x3f6dbec4,0x3f6dbec4,0xbf55bf0e,0x3f553f0e,0xbe48bf7b,0x3e483f7b,
0x3f80,0x3f80,0x3f353f35,0x3f353f35,0x3f7bbe48,0xbf7b3e48,0x3f0ebf55,0xbf0e3f55,0xbec4bf6d,0xbec4bf6d,0xbf6dbec4,0xbf6dbec4,0xbf553f0e,0x3f55bf0e,0xbe483f7b,0x3e48bf7b,
0x3f80,0x3f80,0x3f35bf35,0x3f35bf35,0x3f55bf0e,0xbf553f0e,0xbf7bbe48,0x3f7b3e48,0xbf6dbec4,0xbf6dbec4,0x3ec43f6d,0x3ec43f6d,0x3e483f7b,0xbe48bf7b,0x3f0ebf55,0xbf0e3f55,
0x3f80,0x3f80,0xbf35bf35,0xbf35bf35,0x3f0ebf55,0xbf0e3f55,0x3e483f7b,0xbe48bf7b,0xbf6d3ec4,0xbf6d3ec4,0x3ec4bf6d,0x3ec4bf6d,0x3f7b3e48,0xbf7bbe48,0xbf553f0e,0x3f55bf0e,
0x3f80,0x3f80,0xbf353f35,0xbf353f35,0x3e48bf7b,0xbe483f7b,0x3f55bf0e,0xbf553f0e,0xbec43f6d,0xbec43f6d,0xbf6d3ec4,0xbf6d3ec4,0x3f0ebf55,0xbf0e3f55,0x3f7bbe48,0xbf7b3e48,
0x3f800000,0x3f800000,0x3f35bf35,0x3f35bf35,0x3f7bbe48,0xbf7b3e48,0x3f0ebf55,0xbf0e3f55,0x3f6dbec4,0x3f6dbec4,0x3ec4bf6d,0x3ec4bf6d,0x3f55bf0e,0xbf553f0e,0x3e48bf7b,0xbe483f7b,
0xbf800000,0xbf800000,0x3f353f35,0x3f353f35,0xbf553f0e,0x3f55bf0e,0x3f7b3e48,0xbf7bbe48,0xbec43f6d,0xbec43f6d,0x3f6dbec4,0x3f6dbec4,0x3e483f7b,0xbe48bf7b,0x3f0ebf55,0xbf0e3f55,
0x3f800000,0x3f800000,0xbf353f35,0xbf353f35,0x3f0ebf55,0xbf0e3f55,0x3e483f7b,0xbe48bf7b,0xbec4bf6d,0xbec4bf6d,0x3f6d3ec4,0x3f6d3ec4,0xbf7bbe48,0x3f7b3e48,0x3f55bf0e,0xbf553f0e,
0xbf800000,0xbf800000,0xbf35bf35,0xbf35bf35,0xbe483f7b,0x3e48bf7b,0xbf553f0e,0x3f55bf0e,0x3f6d3ec4,0x3f6d3ec4,0x3ec43f6d,0x3ec43f6d,0x3f0ebf55,0xbf0e3f55,0x3f7bbe48,0xbf7b3e48,
0x3f800000,0x3f800000,0x3f35bf35,0x3f35bf35,0xbe48bf7b,0x3e483f7b,0xbf55bf0e,0x3f553f0e,0xbf6d3ec4,0xbf6d3ec4,0xbec43f6d,0xbec43f6d,0x3f0e3f55,0xbf0ebf55,0x3f7b3e48,0xbf7bbe48,
0xbf800000,0xbf800000,0x3f353f35,0x3f353f35,0x3f0e3f55,0xbf0ebf55,0x3e48bf7b,0xbe483f7b,0x3ec4bf6d,0x3ec4bf6d,0xbf6d3ec4,0xbf6d3ec4,0xbf7b3e48,0x3f7bbe48,0x3f553f0e,0xbf55bf0e,
0x3f800000,0x3f800000,0xbf353f35,0xbf353f35,0xbf55bf0e,0x3f553f0e,0x3f7bbe48,0xbf7b3e48,0x3ec43f6d,0x3ec43f6d,0xbf6dbec4,0xbf6dbec4,0x3e48bf7b,0xbe483f7b,0x3f0e3f55,0xbf0ebf55,
0xbf800000,0xbf800000,0xbf35bf35,0xbf35bf35,0x3f7b3e48,0xbf7bbe48,0x3f0e3f55,0xbf0ebf55,0xbf6dbec4,0xbf6dbec4,0xbec4bf6d,0xbec4bf6d,0x3f553f0e,0xbf55bf0e,0x3e483f7b,0xbe48bf7b,
0x3f800000,0x3f800000,0x3f35bf35,0x3f35bf35,0x3f7bbe48,0xbf7b3e48,0x3f0ebf55,0xbf0e3f55,0x3f6dbec4,0x3f6dbec4,0x3ec4bf6d,0x3ec4bf6d,0x3f55bf0e,0xbf553f0e,0x3e48bf7b,0xbe483f7b,
0x3f800000,0x3f800000,0xbf35bf35,0xbf35bf35,0x3f55bf0e,0xbf553f0e,0xbf7bbe48,0x3f7b3e48,0x3ec4bf6d,0x3ec4bf6d,0xbf6d3ec4,0xbf6d3ec4,0xbe48bf7b,0x3e483f7b,0xbf0e3f55,0x3f0ebf55,
0x3f800000,0x3f800000,0xbf353f35,0xbf353f35,0x3f0ebf55,0xbf0e3f55,0x3e483f7b,0xbe48bf7b,0xbec4bf6d,0xbec4bf6d,0x3f6d3ec4,0x3f6d3ec4,0xbf7bbe48,0x3f7b3e48,0x3f55bf0e,0xbf553f0e,
0x3f800000,0x3f800000,0x3f353f35,0x3f353f35,0x3e48bf7b,0xbe483f7b,0x3f55bf0e,0xbf553f0e,0xbf6dbec4,0xbf6dbec4,0xbec4bf6d,0xbec4bf6d,0xbf0e3f55,0x3f0ebf55,0xbf7b3e48,0x3f7bbe48,
0x3f800000,0x3f800000,0x3f35bf35,0x3f35bf35,0xbe48bf7b,0x3e483f7b,0xbf55bf0e,0x3f553f0e,0xbf6d3ec4,0xbf6d3ec4,0xbec43f6d,0xbec43f6d,0x3f0e3f55,0xbf0ebf55,0x3f7b3e48,0xbf7bbe48,
0x3f800000,0x3f800000,0xbf35bf35,0xbf35bf35,0xbf0ebf55,0x3f0e3f55,0xbe483f7b,0x3e48bf7b,0xbec43f6d,0xbec43f6d,0x3f6dbec4,0x3f6dbec4,0x3f7bbe48,0xbf7b3e48,0xbf55bf0e,0x3f553f0e,
0x3f800000,0x3f800000,0xbf353f35,0xbf353f35,0xbf55bf0e,0x3f553f0e,0x3f7bbe48,0xbf7b3e48,0x3ec43f6d,0x3ec43f6d,0xbf6dbec4,0xbf6dbec4,0x3e48bf7b,0xbe483f7b,0x3f0e3f55,0xbf0ebf55,
0x3f800000,0x3f800000,0x3f353f35,0x3f353f35,0xbf7bbe48,0x3f7b3e48,0xbf0ebf55,0x3f0e3f55,0x3f6d3ec4,0x3f6d3ec4,0x3ec43f6d,0x3ec43f6d,0xbf55bf0e,0x3f553f0e,0xbe48bf7b,0x3e483f7b,
0xbf80,0xbf80,0xbf35bf35,0xbf35bf35,0xbe48bf7b,0x3e483f7b,0xbf55bf0e,0x3f553f0e,0xbec4bf6d,0xbec4bf6d,0xbf6dbec4,0xbf6dbec4,0xbf0ebf55,0x3f0e3f55,0xbf7bbe48,0x3f7b3e48,
0x3f80,0x3f80,0x3f35bf35,0x3f35bf35,0x3f0e3f55,0xbf0ebf55,0x3e48bf7b,0xbe483f7b,0x3f6d3ec4,0x3f6d3ec4,0xbec4bf6d,0xbec4bf6d,0x3f7bbe48,0xbf7b3e48,0xbf55bf0e,0x3f553f0e,
0xbf80,0xbf80,0x3f353f35,0x3f353f35,0xbf55bf0e,0x3f553f0e,0x3f7bbe48,0xbf7b3e48,0xbf6d3ec4,0xbf6d3ec4,0x3ec4bf6d,0x3ec4bf6d,0xbe483f7b,0x3e48bf7b,0xbf0ebf55,0x3f0e3f55,
0x3f80,0x3f80,0xbf353f35,0xbf353f35,0x3f7b3e48,0xbf7bbe48,0x3f0e3f55,0xbf0ebf55,0x3ec4bf6d,0x3ec4bf6d,0x3f6dbec4,0x3f6dbec4,0xbf55bf0e,0x3f553f0e,0xbe48bf7b,0x3e483f7b,
0xbf80,0xbf80,0xbf35bf35,0xbf35bf35,0xbf7b3e48,0x3f7bbe48,0xbf0e3f55,0x3f0ebf55,0x3ec43f6d,0x3ec43f6d,0x3f6d3ec4,0x3f6d3ec4,0x3f55bf0e,0xbf553f0e,0x3e48bf7b,0xbe483f7b,
0x3f80,0x3f80,0x3f35bf35,0x3f35bf35,0x3f55bf0e,0xbf553f0e,0xbf7bbe48,0x3f7b3e48,0xbf6dbec4,0xbf6dbec4,0x3ec43f6d,0x3ec43f6d,0x3e483f7b,0xbe48bf7b,0x3f0ebf55,0xbf0e3f55,
0xbf80,0xbf80,0x3f353f35,0x3f353f35,0xbf0e3f55,0x3f0ebf55,0xbe48bf7b,0x3e483f7b,0x3f6dbec4,0x3f6dbec4,0xbec43f6d,0xbec43f6d,0xbf7bbe48,0x3f7b3e48,0x3f55bf0e,0xbf553f0e,
0x3f80,0x3f80,0xbf353f35,0xbf353f35,0x3e48bf7b,0xbe483f7b,0x3f55bf0e,0xbf553f0e,0xbec43f6d,0xbec43f6d,0xbf6d3ec4,0xbf6d3ec4,0x3f0ebf55,0xbf0e3f55,0x3f7bbe48,0xbf7b3e48,
0x3f803f80,0,0x3f803f80,0,0x3f803f80,0,0x3f803f80,0,0x3f803f80,0,0x3f803f80,0,0x3f803f80,0,0x3f803f80,0,
0x3f553f7b,0x3f0ebe48,0xbf55bf7b,0xbf0e3e48,0x3e483f0e,0x3f7bbf55,0xbe48bf0e,0xbf7b3f55,0xbf0ebe48,0x3f55bf7b,0x3f0e3e48,0xbf553f7b,0xbf7bbf55,0x3e48bf0e,0x3f7b3f55,0xbe483f0e,
0x3ec43f6d,0x3f6dbec4,0x3ec43f6d,0x3f6dbec4,0xbf6dbec4,0x3ec4bf6d,0xbf6dbec4,0x3ec4bf6d,0xbec4bf6d,0xbf6d3ec4,0xbec4bf6d,0xbf6d3ec4,0x3f6d3ec4,0xbec43f6d,0x3f6d3ec4,0xbec43f6d,
0xbe483f55,0x3f7bbf0e,0x3e48bf55,0xbf7b3f0e,0xbf0ebf7b,0xbf55be48,0x3f0e3f7b,0x3f553e48,0x3f7b3f0e,0x3e483f55,0xbf7bbf0e,0xbe48bf55,0xbf553e48,0x3f0ebf7b,0x3f55be48,0xbf0e3f7b,
0xbf353f35,0x3f35bf35,0xbf353f35,0x3f35bf35,0x3f35bf35,0xbf353f35,0x3f35bf35,0xbf353f35,0xbf353f35,0x3f35bf35,0xbf353f35,0x3f35bf35,0x3f35bf35,0xbf353f35,0x3f35bf35,0xbf353f35,
0xbf7b3f0e,0x3e48bf55,0x3f7bbf0e,0xbe483f55,0x3f553e48,0x3f0e3f7b,0xbf55be48,0xbf0ebf7b,0xbe48bf55,0xbf7bbf0e,0x3e483f55,0x3f7b3f0e,0xbf0e3f7b,0x3f55be48,0x3f0ebf7b,0xbf553e48,
0xbf6d3ec4,0xbec4bf6d,0xbf6d3ec4,0xbec4bf6d,0xbec43f6d,0x3f6d3ec4,0xbec43f6d,0x3f6d3ec4,0x3f6dbec4,0x3ec43f6d,0x3f6dbec4,0x3ec43f6d,0x3ec4bf6d,0xbf6dbec4,0x3ec4bf6d,0xbf6dbec4,
0xbf0e3e48,0xbf55bf7b,0x3f0ebe48,0x3f553f7b,0xbf7b3f55,0xbe48bf0e,0x3f7bbf55,0x3e483f0e,0xbf553f7b,0x3f0e3e48,0x3f55bf7b,0xbf0ebe48,0xbe483f0e,0x3f7b3f55,0x3e48bf0e,0xbf7bbf55,
0,0xbf803f80,0,0xbf803f80,0,0xbf803f80,0,0xbf803f80,0,0xbf803f80,0,0xbf803f80,0,0xbf803f80,0,0xbf803f80,
0x3f0e3e48,0xbf553f7b,0xbf0ebe48,0x3f55bf7b,0x3f7b3f55,0xbe483f0e,0xbf7bbf55,0x3e48bf0e,0x3f553f7b,0x3f0ebe48,0xbf55bf7b,0xbf0e3e48,0x3e483f0e,0x3f7bbf55,0xbe48bf0e,0xbf7b3f55,
0x3f6d3ec4,0xbec43f6d,0x3f6d3ec4,0xbec43f6d,0x3ec43f6d,0x3f6dbec4,0x3ec43f6d,0x3f6dbec4,0xbf6dbec4,0x3ec4bf6d,0xbf6dbec4,0x3ec4bf6d,0xbec4bf6d,0xbf6d3ec4,0xbec4bf6d,0xbf6d3ec4,
0x3f7b3f0e,0x3e483f55,0xbf7bbf0e,0xbe48bf55,0xbf553e48,0x3f0ebf7b,0x3f55be48,0xbf0e3f7b,0x3e48bf55,0xbf7b3f0e,0xbe483f55,0x3f7bbf0e,0x3f0e3f7b,0x3f553e48,0xbf0ebf7b,0xbf55be48,
0x3f353f35,0x3f353f35,0x3f353f35,0x3f353f35,0xbf35bf35,0xbf35bf35,0xbf35bf35,0xbf35bf35,0x3f353f35,0x3f353f35,0x3f353f35,0x3f353f35,0xbf35bf35,0xbf35bf35,0xbf35bf35,0xbf35bf35,
0x3e483f55,0x3f7b3f0e,0xbe48bf55,0xbf7bbf0e,0x3f0ebf7b,0xbf553e48,0xbf0e3f7b,0x3f55be48,0xbf7b3f0e,0x3e48bf55,0x3f7bbf0e,0xbe483f55,0x3f553e48,0x3f0e3f7b,0xbf55be48,0xbf0ebf7b,
0xbec43f6d,0x3f6d3ec4,0xbec43f6d,0x3f6d3ec4,0x3f6dbec4,0x3ec43f6d,0x3f6dbec4,0x3ec43f6d,0x3ec4bf6d,0xbf6dbec4,0x3ec4bf6d,0xbf6dbec4,0xbf6d3ec4,0xbec4bf6d,0xbf6d3ec4,0xbec4bf6d,
0xbf553f7b,0x3f0e3e48,0x3f55bf7b,0xbf0ebe48,0xbe483f0e,0x3f7b3f55,0x3e48bf0e,0xbf7bbf55,0x3f0ebe48,0x3f553f7b,0xbf0e3e48,0xbf55bf7b,0x3f7bbf55,0x3e483f0e,0xbf7b3f55,0xbe48bf0e,
0,0x3f80bf80,0,0x3f80bf80,0,0x3f80bf80,0,0x3f80bf80,0,0x3f80bf80,0,0x3f80bf80,0,0x3f80bf80,0,0x3f80bf80,
0xbf0ebe48,0x3f55bf7b,0x3f0e3e48,0xbf553f7b,0xbf7bbf55,0x3e48bf0e,0x3f7b3f55,0xbe483f0e,0xbf55bf7b,0xbf0e3e48,0x3f553f7b,0x3f0ebe48,0xbe48bf0e,0xbf7b3f55,0x3e483f0e,0x3f7bbf55,
0xbf6dbec4,0x3ec4bf6d,0xbf6dbec4,0x3ec4bf6d,0xbec4bf6d,0xbf6d3ec4,0xbec4bf6d,0xbf6d3ec4,0x3f6d3ec4,0xbec43f6d,0x3f6d3ec4,0xbec43f6d,0x3ec43f6d,0x3f6dbec4,0x3ec43f6d,0x3f6dbec4,
0xbf7bbf0e,0xbe48bf55,0x3f7b3f0e,0x3e483f55,0x3f55be48,0xbf0e3f7b,0xbf553e48,0x3f0ebf7b,0xbe483f55,0x3f7bbf0e,0x3e48bf55,0xbf7b3f0e,0xbf0ebf7b,0xbf55be48,0x3f0e3f7b,0x3f553e48,
0xbf35bf35,0xbf35bf35,0xbf35bf35,0xbf35bf35,0x3f353f35,0x3f353f35,0x3f353f35,0x3f353f35,0xbf35bf35,0xbf35bf35,0xbf35bf35,0xbf35bf35,0x3f353f35,0x3f353f35,0x3f353f35,0x3f353f35,
0xbe48bf55,0xbf7bbf0e,0x3e483f55,0x3f7b3f0e,0xbf0e3f7b,0x3f55be48,0x3f0ebf7b,0xbf553e48,0x3f7bbf0e,0xbe483f55,0xbf7b3f0e,0x3e48bf55,0xbf55be48,0xbf0ebf7b,0x3f553e48,0x3f0e3f7b,
0x3ec4bf6d,0xbf6dbec4,0x3ec4bf6d,0xbf6dbec4,0xbf6d3ec4,0xbec4bf6d,0xbf6d3ec4,0xbec4bf6d,0xbec43f6d,0x3f6d3ec4,0xbec43f6d,0x3f6d3ec4,0x3f6dbec4,0x3ec43f6d,0x3f6dbec4,0x3ec43f6d,
0x3f55bf7b,0xbf0ebe48,0xbf553f7b,0x3f0e3e48,0x3e48bf0e,0xbf7bbf55,0xbe483f0e,0x3f7b3f55,0xbf0e3e48,0xbf55bf7b,0x3f0ebe48,0x3f553f7b,0xbf7b3f55,0xbe48bf0e,0x3f7bbf55,0x3e483f0e,
0x3f800000,0x3f7fec43,0x3f800000,0x3f6a09a7,0x3f7fb10f,0x3f7f4e6d,0x3f2beb4a,0x3ea09ae5,0x3f7ec46d,0x3f7e1324,0xbdc8bd36,0xbefc5d27,0x3f7d3aac,0x3f7c3b28,0xbf4d9f02,0xbf79c79d,
0x3f800000,0x3f7f4e6d,0x3f800000,0x3f64aa59,0x3f7d3aac,0x3f79c79d,0x3f187fc0,0x3e2f10a2,0x3f74fa0b,0x3f6ed89e,0xbe94a031,0xbf3085bb,0x3f676bd8,0x3f5ebe05,0xbf710908,0xbf7e1324,
0x3f800000,0x3f7e1324,0x3f800000,0x3f5ebe05,0x3f7853f8,0x3f6ed89e,0x3f039c3d,0x3cc90ab0,0x3f61c598,0x3f514d3d,0xbef15aea,0xbf584853,0x3f3daef9,0x3f273656,0xbf7fb10f,0xbf64aa59,
0x3f800000,0x3f7c3b28,0x3f800000,0x3f584853,0x3f710908,0x3f5ebe05,0x3edae880,0xbdfab273,0x3f45e403,0x3f273656,0xbf226799,0xbf731447,0x3f039c3d,0x3eb8442a,0xbf7853f8,0xbf3085bb,
0x3f800000,0x3f79c79d,0x3f800000,0x3f514d3d,0x3f676bd8,0x3f49d112,0x3eac7cd4,0xbe888e93,0x3f226799,0x3ee63375,0xbf45e403,0xbf7f4e6d,0x3e78cfcc,0x3cc90ab0,0xbf5b941a,0xbecf7bca,
0x3f800000,0x3f76ba07,0x3f800000,0x3f49d112,0x3f5b941a,0x3f3085bb,0x3e78cfcc,0xbecf7bca,0x3ef15aea,0x3e605c13,0xbf61c598,0xbf7c3b28,0xbd48fb30,0xbea09ae5,0xbf2beb4a,0xbd96a905,
0x3f800000,0x3f731447,0x3f800000,0x3f41d870,0x3f4d9f02,0x3f13682a,0x3e164083,0xbf08f59b,0x3e94a031,0xbcc90ab0,0xbf74fa0b,0xbf6a09a7,0xbeac7cd4,0xbf1d7fd1,0xbedae880,0x3e888e93,
0x3f800000,0x3f6ed89e,0x3f800000,0x3f396842,0x3f3daef9,0x3ee63375,0x3d48fb30,0xbf273656,0x3dc8bd36,0xbe888e93,0xbf7ec46d,0xbf49d112,0xbf187fc0,0xbf584853,0xbe164083,0x3f13682a,
0,0x3cc90ab0,0,0x3ecf7bca,0x3d48fb30,0x3d96a905,0x3f3daef9,0x3f731447,0x3dc8bd36,0x3dfab273,0x3f7ec46d,0x3f5ebe05,0x3e164083,0x3e2f10a2,0x3f187fc0,0x3e605c13,
0,0x3d96a905,0,0x3ee63375,0x3e164083,0x3e605c13,0x3f4d9f02,0x3f7c3b28,0x3e94a031,0x3eb8442a,0x3f74fa0b,0x3f396842,0x3edae880,0x3efc5d27,0x3eac7cd4,0xbdfab273,
0,0x3dfab273,0,0x3efc5d27,0x3e78cfcc,0x3eb8442a,0x3f5b941a,0x3f7fec43,0x3ef15aea,0x3f13682a,0x3f61c598,0x3f08f59b,0x3f2beb4a,0x3f41d870,0x3d48fb30,0xbee63375,
0,0x3e2f10a2,0,0x3f08f59b,0x3eac7cd4,0x3efc5d27,0x3f676bd8,0x3f7e1324,0x3f226799,0x3f41d870,0x3f45e403,0x3ea09ae5,0x3f5b941a,0x3f6ed89e,0xbe78cfcc,0xbf396842,
0,0x3e605c13,0,0x3f13682a,0x3edae880,0x3f1d7fd1,0x3f710908,0x3f76ba07,0x3f45e403,0x3f64aa59,0x3f226799,0x3d96a905,0x3f7853f8,0x3f7fec43,0xbf039c3d,0xbf6a09a7,
0,0x3e888e93,0,0x3f1d7fd1,0x3f039c3d,0x3f396842,0x3f7853f8,0x3f6a09a7,0x3f61c598,0x3f79c79d,0x3ef15aea,0xbe2f10a2,0x3f7fb10f,0x3f731447,0xbf3daef9,0xbf7f4e6d,
0,0x3ea09ae5,0,0x3f273656,0x3f187fc0,0x3f514d3d,0x3f7d3aac,0x3f584853,0x3f74fa0b,0x3f7fec43,0x3e94a031,0xbecf7bca,0x3f710908,0x3f49d112,0xbf676bd8,0xbf76ba07,
0,0x3eb8442a,0,0x3f3085bb,0x3f2beb4a,0x3f64aa59,0x3f7fb10f,0x3f41d870,0x3f7ec46d,0x3f76ba07,0x3dc8bd36,0xbf1d7fd1,0x3f4d9f02,0x3f08f59b,0xbf7d3aac,0xbf514d3d,
0x354ccccd,0x354ccccd,0x354ccccd,0x354ccccd,0x354ccccd,0x354ccccd,0x354ccccd,0x354ccccd,0x354ccccd,0x354ccccd,0x354ccccd,0x354ccccd,0x354ccccd,0x354ccccd,0x354ccccd,0x354ccccd,
0x354bd057,0x3543fb3c,0xb3a0975e,0xb46dcd1c,0x35349e13,0x351e5003,0xb4c11588,0xb501ec7b,0x3501ec7b,0x34c11588,0xb51e5003,0xb5349e13,0x346dcd1c,0x33a0975e,0xb543fb3c,0xb54bd057,
0x354cbd02,0x354c3ebe,0x353b3aec,0x3536eeae,0x354b4283,0x3549c8ed,0x3532319e,0x352d06a9,0x3547d2e4,0x3545619f,0x352770fe,0x3521740f,0x354276a0,0x353f13b1,0x351b138d,0x35145368,
0x354b4283,0x353f13b1,0xb4c9e41f,0xb50d37c9,0x352770fe,0x3505c511,0xb52d06a9,0xb54276a0,0x34b8292a,0x34337cdc,0xb54c3ebe,0xb549c8ed,0xb2a0d559,0xb45a7db8,0xb53b3aec,0xb521740f,
0x354c8da6,0x354a9556,0x35098908,0x34f3ff99,0x3546a993,0x3540d407,0x34d29394,0x34af2067,0x35392313,0x352fa9af,0x3489fd76,0x34470ca3,0x35247f35,0x3517bf2e,0x33f06739,0x3320c8f3,
0x354a9556,0x35392313,0xb5247f35,0xb540d407,0x3517bf2e,0x34d29394,0xb54c8da6,0xb546a993,0x34470ca3,0xb320c8f3,0xb52fa9af,0xb5098908,0xb489fd76,0xb4f3ff99,0xb4af2067,0xb3f06739,
0x354c3ebe,0x3547d2e4,0x34807bea,0x340c0d4f,0x353f13b1,0x3532319e,0x32a0d559,0xb3c88ec2,0x3521740f,0x350d37c9,0xb45a7db8,0xb4a5fca2,0x34ebd9dd,0x34b8292a,0xb4db2291,0xb505c511,
0x3549c8ed,0x3532319e,0xb547d2e4,0xb54b4283,0x3505c511,0x349369bb,0xb536eeae,0xb50d37c9,0x32a0d559,0xb4807bea,0xb4a5fca2,0xb3710e6e,0xb4fbffb5,0xb52d06a9,0x345a7db8,0x34ebd9dd,
0,0,0,0,0,0,0,0,0,0,0,0,0,0,0,0,
0x33a0975e,0x346dcd1c,0x354bd057,0x3543fb3c,0x34c11588,0x3501ec7b,0x35349e13,0x351e5003,0x351e5003,0x35349e13,0x3501ec7b,0x34c11588,0x3543fb3c,0x354bd057,0x346dcd1c,0x33a0975e,
0x32a0d559,0x33710e6e,0x34a5fca2,0x34b8292a,0x33c88ec2,0x340c0d4f,0x34c9e41f,0x34db2291,0x34337cdc,0x345a7db8,0x34ebd9dd,0x34fbffb5,0x34807bea,0x349369bb,0x3505c511,0x350d37c9,
0x33c88ec2,0x349369bb,0x3532319e,0x35145368,0x34ebd9dd,0x351b138d,0x34db2291,0x34807bea,0x3536eeae,0x3547d2e4,0x33710e6e,0xb40c0d4f,0x354cbd02,0x3545619f,0xb4a5fca2,0xb4fbffb5,
0x3320c8f3,0x33f06739,0x3517bf2e,0x35247f35,0x34470ca3,0x3489fd76,0x352fa9af,0x35392313,0x34af2067,0x34d29394,0x3540d407,0x3546a993,0x34f3ff99,0x35098908,0x354a9556,0x354c8da6,
0x33f06739,0x34af2067,0x34f3ff99,0x3489fd76,0x35098908,0x352fa9af,0x3320c8f3,0xb4470ca3,0x3546a993,0x354c8da6,0xb4d29394,0xb517bf2e,0x3540d407,0x35247f35,0xb5392313,0xb54a9556,
0x33710e6e,0x34337cdc,0x354276a0,0x3549c8ed,0x349369bb,0x34c9e41f,0x354cbd02,0x354b4283,0x34fbffb5,0x35145368,0x3545619f,0x353b3aec,0x352770fe,0x3536eeae,0x352d06a9,0x351b138d,
0x340c0d4f,0x34c9e41f,0x34337cdc,0xb3c88ec2,0x351b138d,0x353f13b1,0xb4b8292a,0xb5145368,0x354cbd02,0x354276a0,0xb53b3aec,0xb54c3ebe,0x3521740f,0x34db2291,0xb545619f,0xb52770fe,
0x3f80,0x3f80,0x3f463f22,0x3f463f22,0x3e603f7a,0xbe60bf7a,0x3f653ee6,0xbf65bee6,0x3edb3f67,0x3edb3f67,0x3f783e79,0x3f783e79,0x3f1d3f4a,0xbf1dbf4a,0x3f803cc9,0xbf80bcc9,
0x3f80,0x3f80,0x3f22bf46,0x3f22bf46,0x3f133f51,0xbf13bf51,0x3d97bf7f,0xbd973f7f,0x3f713eac,0x3f713eac,0xbf04bf5c,0xbf04bf5c,0x3f77be89,0xbf773e89,0xbf6abecf,0x3f6a3ecf,
0x3f80,0x3f80,0xbf46bf22,0xbf46bf22,0x3f583f09,0xbf58bf09,0xbf733ea1,0x3f73bea1,0x3f67bedb,0x3f67bedb,0xbe793f78,0xbe793f78,0x3dfbbf7e,0xbdfb3f7e,0x3f313f39,0xbf31bf39,
0x3f80,0x3f80,0xbf223f46,0xbf223f46,0x3f7c3e2f,0xbf7cbe2f,0x3f273f42,0xbf27bf42,0x3eacbf71,0x3eacbf71,0x3f5cbf04,0x3f5cbf04,0xbf5fbefc,0x3f5f3efc,0xbeb8bf6f,0x3eb83f6f,
0x3f80,0x3f80,0x3f463f22,0x3f463f22,0x3f7abe60,0xbf7a3e60,0x3ee6bf65,0xbee63f65,0xbedbbf67,0xbedbbf67,0xbf78be79,0xbf78be79,0xbf4a3f1d,0x3f4abf1d,0xbcc93f80,0x3cc9bf80,
0x3f80,0x3f80,0x3f22bf46,0x3f22bf46,0x3f51bf13,0xbf513f13,0xbf7fbd97,0x3f7f3d97,0xbf71beac,0xbf71beac,0x3f043f5c,0x3f043f5c,0x3e893f77,0xbe89bf77,0x3ecfbf6a,0xbecf3f6a,
0x3f80,0x3f80,0xbf46bf22,0xbf46bf22,0x3f09bf58,0xbf093f58,0x3ea13f73,0xbea1bf73,0xbf673edb,0xbf673edb,0x3e79bf78,0x3e79bf78,0x3f7e3dfb,0xbf7ebdfb,0xbf393f31,0x3f39bf31,
0x3f80,0x3f80,0xbf223f46,0xbf223f46,0x3e2fbf7c,0xbe2f3f7c,0x3f42bf27,0xbf423f27,0xbeac3f71,0xbeac3f71,0xbf5c3f04,0xbf5c3f04,0x3efcbf5f,0xbefc3f5f,0x3f6fbeb8,0xbf6f3eb8,
0x3f7bbe48,0x3f7bbe48,0x3ef1bf62,0x3ef1bf62,0x3f6abecf,0xbf6a3ecf,0x3e89bf77,0xbe893f77,0x3f4ebf18,0x3f4ebf18,0x3d49bf80,0x3d49bf80,0x3f27bf42,0xbf273f42,0xbe2fbf7c,0x3e2f3f7c,
0xbf7b3e48,0xbf7b3e48,0x3f623ef1,0x3f623ef1,0xbf313f39,0x3f31bf39,0x3f7ebdfb,0xbf7e3dfb,0xbe163f7d,0xbe163f7d,0x3f3ebf2c,0x3f3ebf2c,0x3ee63f65,0xbee6bf65,0x3e60bf7a,0xbe603f7a,
0x3f7bbe48,0x3f7bbe48,0xbef13f62,0xbef13f62,0x3eb8bf6f,0xbeb83f6f,0x3efc3f5f,0xbefcbf5f,0xbf18bf4e,0xbf18bf4e,0x3f803d49,0x3f803d49,0xbf7f3d97,0x3f7fbd97,0x3f13bf51,0xbf133f51,
0xbf7b3e48,0xbf7b3e48,0xbf62bef1,0xbf62bef1,0x3cc93f80,0xbcc9bf80,0xbf1d3f4a,0x3f1dbf4a,0x3f7d3e16,0x3f7d3e16,0x3f2c3f3e,0x3f2c3f3e,0x3ea1bf73,0xbea13f73,0x3f58bf09,0xbf583f09,
0x3f7bbe48,0x3f7bbe48,0x3ef1bf62,0x3ef1bf62,0xbecfbf6a,0x3ecf3f6a,0xbf77be89,0x3f773e89,0xbf4e3f18,0xbf4e3f18,0xbd493f80,0xbd493f80,0x3f423f27,0xbf42bf27,0x3f7cbe2f,0xbf7c3e2f,
0xbf7b3e48,0xbf7b3e48,0x3f623ef1,0x3f623ef1,0x3f393f31,0xbf39bf31,0xbdfbbf7e,0x3dfb3f7e,0x3e16bf7d,0x3e16bf7d,0xbf3e3f2c,0xbf3e3f2c,0xbf653ee6,0x3f65bee6,0x3f7a3e60,0xbf7abe60,
0x3f7bbe48,0x3f7bbe48,0xbef13f62,0xbef13f62,0xbf6fbeb8,0x3f6f3eb8,0x3f5fbefc,0xbf5f3efc,0x3f183f4e,0x3f183f4e,0xbf80bd49,0xbf80bd49,0xbd97bf7f,0x3d973f7f,0x3f513f13,0xbf51bf13,
0xbf7b3e48,0xbf7b3e48,0xbf62bef1,0xbf62bef1,0x3f80bcc9,0xbf803cc9,0x3f4a3f1d,0xbf4abf1d,0xbf7dbe16,0xbf7dbe16,0xbf2cbf3e,0xbf2cbf3e,0x3f733ea1,0xbf73bea1,0x3f093f58,0xbf09bf58,
0x3f800000,0x3f800000,0x3f22bf46,0x3f22bf46,0x3f7abe60,0xbf7a3e60,0x3ee6bf65,0xbee63f65,0x3f67bedb,0x3f67bedb,0x3e79bf78,0x3e79bf78,0x3f4abf1d,0xbf4a3f1d,0x3cc9bf80,0xbcc93f80,
0x3f800000,0x3f800000,0xbf46bf22,0xbf46bf22,0x3f51bf13,0xbf513f13,0xbf7fbd97,0x3f7f3d97,0x3eacbf71,0x3eacbf71,0xbf5c3f04,0xbf5c3f04,0xbe89bf77,0x3e893f77,0xbecf3f6a,0x3ecfbf6a,
0x3f800000,0x3f800000,0xbf223f46,0xbf223f46,0x3f09bf58,0xbf093f58,0x3ea13f73,0xbea1bf73,0xbedbbf67,0xbedbbf67,0x3f783e79,0x3f783e79,0xbf7ebdfb,0x3f7e3dfb,0x3f39bf31,0xbf393f31,
0x3f800000,0x3f800000,0x3f463f22,0x3f463f22,0x3e2fbf7c,0xbe2f3f7c,0x3f42bf27,0xbf423f27,0xbf71beac,0xbf71beac,0xbf04bf5c,0xbf04bf5c,0xbefc3f5f,0x3efcbf5f,0xbf6f3eb8,0x3f6fbeb8,
0x3f800000,0x3f800000,0x3f22bf46,0x3f22bf46,0xbe60bf7a,0x3e603f7a,0xbf65bee6,0x3f653ee6,0xbf673edb,0xbf673edb,0xbe793f78,0xbe793f78,0x3f1d3f4a,0xbf1dbf4a,0x3f803cc9,0xbf80bcc9,
0x3f800000,0x3f800000,0xbf46bf22,0xbf46bf22,0xbf13bf51,0x3f133f51,0xbd973f7f,0x3d97bf7f,0xbeac3f71,0xbeac3f71,0x3f5cbf04,0x3f5cbf04,0x3f77be89,0xbf773e89,0xbf6abecf,0x3f6a3ecf,
0x3f800000,0x3f800000,0xbf223f46,0xbf223f46,0xbf58bf09,0x3f583f09,0x3f73bea1,0xbf733ea1,0x3edb3f67,0x3edb3f67,0xbf78be79,0xbf78be79,0x3dfbbf7e,0xbdfb3f7e,0x3f313f39,0xbf31bf39,
0x3f800000,0x3f800000,0x3f463f22,0x3f463f22,0xbf7cbe2f,0x3f7c3e2f,0xbf27bf42,0x3f273f42,0x3f713eac,0x3f713eac,0x3f043f5c,0x3f043f5c,0xbf5fbefc,0x3f5f3efc,0xbeb8bf6f,0x3eb83f6f,
0xbe48bf7b,0xbe48bf7b,0xbf62bef1,0xbf62bef1,0xbecfbf6a,0x3ecf3f6a,0xbf77be89,0x3f773e89,0xbf18bf4e,0xbf18bf4e,0xbf80bd49,0xbf80bd49,0xbf42bf27,0x3f423f27,0xbf7c3e2f,0x3f7cbe2f,
0x3e483f7b,0x3e483f7b,0x3ef1bf62,0x3ef1bf62,0x3f393f31,0xbf39bf31,0xbdfbbf7e,0x3dfb3f7e,0x3f7d3e16,0x3f7d3e16,0xbf2cbf3e,0xbf2cbf3e,0x3f65bee6,0xbf653ee6,0xbf7abe60,0x3f7a3e60,
0xbe48bf7b,0xbe48bf7b,0x3f623ef1,0x3f623ef1,0xbf6fbeb8,0x3f6f3eb8,0x3f5fbefc,0xbf5f3efc,0xbf4e3f18,0xbf4e3f18,0x3d49bf80,0x3d49bf80,0x3d973f7f,0xbd97bf7f,0xbf51bf13,0x3f513f13,
0x3e483f7b,0x3e483f7b,0xbef13f62,0xbef13f62,0x3f80bcc9,0xbf803cc9,0x3f4a3f1d,0xbf4abf1d,0x3e16bf7d,0x3e16bf7d,0x3f3ebf2c,0x3f3ebf2c,0xbf73bea1,0x3f733ea1,0xbf09bf58,0x3f093f58,
0xbe48bf7b,0xbe48bf7b,0xbf62bef1,0xbf62bef1,0xbf6a3ecf,0x3f6abecf,0xbe893f77,0x3e89bf77,0x3f183f4e,0x3f183f4e,0x3f803d49,0x3f803d49,0x3f27bf42,0xbf273f42,0xbe2fbf7c,0x3e2f3f7c,
0x3e483f7b,0x3e483f7b,0x3ef1bf62,0x3ef1bf62,0x3f31bf39,0xbf313f39,0xbf7e3dfb,0x3f7ebdfb,0xbf7dbe16,0xbf7dbe16,0x3f2c3f3e,0x3f2c3f3e,0x3ee63f65,0xbee6bf65,0x3e60bf7a,0xbe603f7a,
0xbe48bf7b,0xbe48bf7b,0x3f623ef1,0x3f623ef1,0xbeb83f6f,0x3eb8bf6f,0xbefcbf5f,0x3efc3f5f,0x3f4ebf18,0x3f4ebf18,0xbd493f80,0xbd493f80,0xbf7f3d97,0x3f7fbd97,0x3f13bf51,0xbf133f51,
0x3e483f7b,0x3e483f7b,0xbef13f62,0xbef13f62,0xbcc9bf80,0x3cc93f80,0x3f1dbf4a,0xbf1d3f4a,0xbe163f7d,0xbe163f7d,0xbf3e3f2c,0xbf3e3f2c,0x3ea1bf73,0xbea13f73,0x3f58bf09,0xbf583f09,
0x3f803f80,0x3e48be48,0x3f803f80,0x3e48be48,0x3f803f80,0x3e48be48,0x3f803f80,0x3e48be48,0x3f803f80,0x3e48be48,0x3f803f80,0x3e48be48,0x3f803f80,0x3e48be48,0x3f803f80,0x3e48be48,
0x3f513f7a,0x3f39becf,0xbf51bf7a,0xbf393ecf,0x3e2f3f09,0x3f80bf6f,0xbe2fbf09,0xbf803f6f,0xbf13be60,0x3f31bf6a,0x3f133e60,0xbf313f6a,0xbf7cbf58,0xbcc9beb8,0x3f7c3f58,0x3cc93eb8,
0x3eac3f67,0x3f7dbf18,0x3eac3f67,0x3f7dbf18,0xbf71bedb,0x3e16bf4e,0xbf71bedb,0x3e16bf4e,0xbeacbf67,0xbf7d3f18,0xbeacbf67,0xbf7d3f18,0x3f713edb,0xbe163f4e,0x3f713edb,0xbe163f4e,
0xbe893f4a,0x3f65bf42,0x3e89bf4a,0xbf653f42,0xbefcbf7e,0xbf733d97,0x3efc3f7e,0x3f73bd97,0x3f773f1d,0x3ee63f27,0xbf77bf1d,0xbee6bf27,0xbf5f3dfb,0x3ea1bf7f,0x3f5fbdfb,0xbea13f7f,
0xbf463f22,0x3ef1bf62,0xbf463f22,0x3ef1bf62,0x3f46bf22,0xbef13f62,0x3f46bf22,0xbef13f62,0xbf463f22,0x3ef1bf62,0xbf463f22,0x3ef1bf62,0x3f46bf22,0xbef13f62,0x3f46bf22,0xbef13f62,
0xbf7f3ee6,0xbdfbbf77,0x3f7fbee6,0x3dfb3f77,0x3f423ea1,0x3f4a3f5f,0xbf42bea1,0xbf4abf5f,0xbd97bf65,0xbf7ebe89,0x3d973f65,0x3f7e3e89,0xbf273f73,0x3f1dbefc,0x3f27bf73,0xbf1d3efc,
0xbf5c3e79,0xbf2cbf80,0xbf5c3e79,0xbf2cbf80,0xbf043f78,0x3f3e3d49,0xbf043f78,0x3f3e3d49,0x3f5cbe79,0x3f2c3f80,0x3f5cbe79,0x3f2c3f80,0x3f04bf78,0xbf3ebd49,0x3f04bf78,0xbf3ebd49,
0xbecf3cc9,0xbf7abf7c,0x3ecfbcc9,0x3f7a3f7c,0xbf6f3f39,0xbf09bf51,0x3f6fbf39,0x3f093f51,0xbf6a3f80,0x3e60be2f,0x3f6abf80,0xbe603e2f,0xbeb83f31,0x3f583f13,0x3eb8bf31,0xbf58bf13,
0,0xbf7b3f7b,0,0xbf7b3f7b,0,0xbf7b3f7b,0,0xbf7b3f7b,0,0xbf7b3f7b,0,0xbf7b3f7b,0,0xbf7b3f7b,0,0xbf7b3f7b,
0x3f133e60,0xbf313f6a,0xbf13be60,0x3f31bf6a,0x3f7c3f58,0x3cc93eb8,0xbf7cbf58,0xbcc9beb8,0x3f513f7a,0x3f39becf,0xbf51bf7a,0xbf393ecf,0x3e2f3f09,0x3f80bf6f,0xbe2fbf09,0xbf803f6f,
0x3f713edb,0xbe163f4e,0x3f713edb,0xbe163f4e,0x3eac3f67,0x3f7dbf18,0x3eac3f67,0x3f7dbf18,0xbf71bedb,0x3e16bf4e,0xbf71bedb,0x3e16bf4e,0xbeacbf67,0xbf7d3f18,0xbeacbf67,0xbf7d3f18,
0x3f773f1d,0x3ee63f27,0xbf77bf1d,0xbee6bf27,0xbf5f3dfb,0x3ea1bf7f,0x3f5fbdfb,0xbea13f7f,0x3e89bf4a,0xbf653f42,0xbe893f4a,0x3f65bf42,0x3efc3f7e,0x3f73bd97,0xbefcbf7e,0xbf733d97,
0x3f223f46,0x3f623ef1,0x3f223f46,0x3f623ef1,0xbf22bf46,0xbf62bef1,0xbf22bf46,0xbf62bef1,0x3f223f46,0x3f623ef1,0x3f223f46,0x3f623ef1,0xbf22bf46,0xbf62bef1,0xbf22bf46,0xbf62bef1,
0x3d973f65,0x3f7e3e89,0xbd97bf65,0xbf7ebe89,0x3f27bf73,0xbf1d3efc,0xbf273f73,0x3f1dbefc,0xbf7f3ee6,0xbdfbbf77,0x3f7fbee6,0x3dfb3f77,0x3f423ea1,0x3f4a3f5f,0xbf42bea1,0xbf4abf5f,
0xbf043f78,0x3f3e3d49,0xbf043f78,0x3f3e3d49,0x3f5cbe79,0x3f2c3f80,0x3f5cbe79,0x3f2c3f80,0x3f04bf78,0xbf3ebd49,0x3f04bf78,0xbf3ebd49,0xbf5c3e79,0xbf2cbf80,0xbf5c3e79,0xbf2cbf80,
0xbf6a3f80,0x3e60be2f,0x3f6abf80,0xbe603e2f,0xbeb83f31,0x3f583f13,0x3eb8bf31,0xbf58bf13,0x3ecfbcc9,0x3f7a3f7c,0xbecf3cc9,0xbf7abf7c,0x3f6fbf39,0x3f093f51,0xbf6f3f39,0xbf09bf51,
0,0x3f7bbf7b,0,0x3f7bbf7b,0,0x3f7bbf7b,0,0x3f7bbf7b,0,0x3f7bbf7b,0,0x3f7bbf7b,0,0x3f7bbf7b,0,0x3f7bbf7b,
0xbf13be60,0x3f31bf6a,0x3f133e60,0xbf313f6a,0xbf7cbf58,0xbcc9beb8,0x3f7c3f58,0x3cc93eb8,0xbf51bf7a,0xbf393ecf,0x3f513f7a,0x3f39becf,0xbe2fbf09,0xbf803f6f,0x3e2f3f09,0x3f80bf6f,
0xbf71bedb,0x3e16bf4e,0xbf71bedb,0x3e16bf4e,0xbeacbf67,0xbf7d3f18,0xbeacbf67,0xbf7d3f18,0x3f713edb,0xbe163f4e,0x3f713edb,0xbe163f4e,0x3eac3f67,0x3f7dbf18,0x3eac3f67,0x3f7dbf18,
0xbf77bf1d,0xbee6bf27,0x3f773f1d,0x3ee63f27,0x3f5fbdfb,0xbea13f7f,0xbf5f3dfb,0x3ea1bf7f,0xbe893f4a,0x3f65bf42,0x3e89bf4a,0xbf653f42,0xbefcbf7e,0xbf733d97,0x3efc3f7e,0x3f73bd97,
0xbf22bf46,0xbf62bef1,0xbf22bf46,0xbf62bef1,0x3f223f46,0x3f623ef1,0x3f223f46,0x3f623ef1,0xbf22bf46,0xbf62bef1,0xbf22bf46,0xbf62bef1,0x3f223f46,0x3f623ef1,0x3f223f46,0x3f623ef1,
0xbd97bf65,0xbf7ebe89,0x3d973f65,0x3f7e3e89,0xbf273f73,0x3f1dbefc,0x3f27bf73,0xbf1d3efc,0x3f7fbee6,0x3dfb3f77,0xbf7f3ee6,0xbdfbbf77,0xbf42bea1,0xbf4abf5f,0x3f423ea1,0x3f4a3f5f,
0x3f04bf78,0xbf3ebd49,0x3f04bf78,0xbf3ebd49,0xbf5c3e79,0xbf2cbf80,0xbf5c3e79,0xbf2cbf80,0xbf043f78,0x3f3e3d49,0xbf043f78,0x3f3e3d49,0x3f5cbe79,0x3f2c3f80,0x3f5cbe79,0x3f2c3f80,
0x3f6abf80,0xbe603e2f,0xbf6a3f80,0x3e60be2f,0x3eb8bf31,0xbf58bf13,0xbeb83f31,0x3f583f13,0xbecf3cc9,0xbf7abf7c,0x3ecfbcc9,0x3f7a3f7c,0xbf6f3f39,0xbf09bf51,0x3f6fbf39,0x3f093f51,
0x3f800000,0x3f7fe705,0x3f800000,0x3f69b7e4,0x3f7f9c18,0x3f7f1f49,0x3f2ac082,0x3e9c1faf,0x3f7e70b0,0x3f7d906e,0xbde1bc2e,0xbf019573,0x3f7c7eb0,0x3f7b3bab,0xbf5064af,0xbf7aed37,
0x3f800000,0x3f7f3f54,0x3f800000,0x3f644fac,0x3f7cfe73,0x3f7940c0,0x3f173c07,0x3e25c58c,0x3f740bdd,0x3f6d67a1,0xbe9aa086,0xbf33587a,0x3f655e0b,0x3f5bfb34,0xbf7294f8,0xbf7d57de,
0x3f800000,0x3f7dfa38,0x3f800000,0x3f5e5aa6,0x3f77f110,0x3f6dfcf2,0x3f0242b1,0x3c7b514b,0x3f604621,0x3f4f0417,0xbef6e0cb,0xbf5a5ba0,0x3f3a7ca4,0x3f2302d3,0xbf7fe129,0xbf62241a,
0x3f800000,0x3f7c187a,0x3f800000,0x3f57dc7f,0x3f708066,0x3f5d924d,0x3ed8106b,0xbe06b26e,0x3f43e200,0x3f24381a,0xbf24d225,0xbf74484b,0x3eff17b2,0x3eadf73c,0xbf772417,0xbf2c800f,
0x3f800000,0x3f799b43,0x3f800000,0x3f50d937,0x3f66becc,0x3f485bca,0x3ea986c4,0xbe8d17c0,0x3f1ff6cb,0x3edf28a9,0xbf47de65,0xbf7f90b1,0x3e667c66,0x3b490fc6,0xbf591e6a,0xbec5625c,
0x3f800000,0x3f76841b,0x3f800000,0x3f495521,0x3f5ac450,0x3f2ecef7,0x3e72b651,0xbed3c867,0x3eebcbbb,0x3e5101f1,0xbf633c5a,0xbf7b87b2,0xbd8a200a,0xbeab0201,0xbf286605,0xbd55880e,
0x3f800000,0x3f72d4eb,0x3f800000,0x3f4154e1,0x3f4cae79,0x3f11796b,0x3e1008b7,0xbf0af1b7,0x3e8e9a22,0xbd2351cb,0xbf75dec6,0xbf686b39,0xbeb554ec,0xbf21cbfb,0xbed25a09,0x3e931f35,
0x3f800000,0x3f6e8ff8,0x3f800000,0x3f38dd65,0x3f3ca003,0x3ee1fb6a,0x3d2fe007,0xbf28fd41,0x3dafb680,0xbe901c2c,0xbf7f0e58,0xbf476085,0xbf1c420c,0xbf5b2c79,0xbe039502,0x3f17de12,
0,0x3ce22a7a,0,0x3ed0eb2a,0x3d621469,0x3da973ba,0x3f3ebc1b,0x3f73ced9,0x3de1bc2e,0x3e0cec4a,0x3f7e70b0,0x3f5cc7d1,0x3e28defc,0x3e44b0b9,0x3f14b039,0x3e4ada4f,
0,0x3d9cecf9,0,0x3ee79a5d,0x3e1c76de,0x3e698bba,0x3f4e8d90,0x3f7c9f8a,0x3e9aa086,0x3ebf926f,0x3f740bdd,0x3f36ad7f,0x3ee363fa,0x3f02ef9f,0x3ea395c5,0xbe1324ca,
0,0x3e007745,0,0x3efdbabb,0x3e7ee6e1,0x3ebca7af,0x3f5c61c7,0x3f7ff84a,0x3ef6e0cb,0x3f16999f,0x3f604621,0x3f05a02c,0x3f2f61a5,0x3f456439,0x3cfb49ba,0xbeeff7fb,
0,0x3e3228d4,0,0x3f099f4e,0x3eaf713a,0x3f003a06,0x3f6816a8,0x3f7dc68c,0x3f24d225,0x3f446337,0x3f43e200,0x3e9920fe,0x3f5df6be,0x3f70c501,0xbe8586ce,0xbf3d27b8,
0,0x3e636c83,0,0x3f140c5f,0x3eddbe79,0x3f1f599f,0x3f718f57,0x3f76167a,0x3f47de65,0x3f666771,0x3f1ff6cb,0x3d6ea038,0x3f796e4e,0x3f7fffb1,0xbf07a136,0xbf6c3624,
0,0x3e8a11f7,0,0x3f1e1e22,0x3f04f484,0x3f3b0629,0x3f78b47b,0x3f6912ae,0x3f633c5a,0x3f7a9c59,0x3eebcbbb,0xbe3e853e,0x3f7f6ac7,0x3f714c7a,0xbf40d0da,0xbf7fa6e3,
0,0x3ea21887,0,0x3f27ce61,0x3f19c200,0x3f52a649,0x3f7d7474,0x3f570348,0x3f75dec6,0x3f7fcbe2,0x3e8e9a22,0xbed6a399,0x3f6f6830,0x3f466354,0xbf696591,0xbf75341d,
0,0x3eb9bb1e,0,0x3f311722,0x3f2d1469,0x3f65b710,0x3f7fc38f,0x3f404c5c,0x3f7f0e58,0x3f75a67b,0x3dafb680,0xbf209393,0x3f4ac77f,0x3f044889,0xbf7de0b1,0xbf4e1689,
0x354ccccd,0x354ccccd,0x354ccccd,0x354ccccd,0x354ccccd,0x354ccccd,0x354ccccd,0x354ccccd,0x354ccccd,0x354ccccd,0x354ccccd,0x354ccccd,0x354ccccd,0x354ccccd,0x354ccccd,0x354ccccd,
0x354b8d5a,0x35433cb1,0xb3b4968b,0xb477673d,0x35336b4e,0x351cb4cd,0xb4c580a2,0xb503db51,0x34fff144,0x34bca2fc,0xb51fe51e,0xb535c9e1,0x346429d0,0x338c9200,0xb544b238,0xb54c0b7a,
0x354cb8d1,0x354c32aa,0x353af983,0x3536a623,0x354b2e94,0x3549ad2f,0x3531e21f,0x352cb065,0x3547af69,0x3545367c,0x3527142c,0x352110e7,0x354243ef,0x353ed993,0x351aaa4d,0x3513e451,
0x354ad9f2,0x353dec81,0xb4cf5584,0xb50f79fb,0x35259ce0,0x35036014,0xb52eafb3,0xb5436d09,0x34b286ed,0x342734c1,0xb54c73c1,0xb549395b,0xb302a7d6,0xb466937a,0xb539ef61,0xb51f806a,
0x354c7ce0,0x354a6529,0x35089a01,0x34f1f9a5,0x35465a74,0x354066b8,0x34d06ab5,0x34acd9f0,0x353898a3,0x352f0373,0x34879f03,0x34422b74,0x3523bec8,0x3516e669,0x33e67457,0x330cb338,
0x3549fef3,0x35377e6f,0xb526b6f3,0xb54210c7,0x35153084,0x34cc12f5,0xb54cb421,0xb545b679,0x34386384,0xb35d000f,0xb52db1ef,0xb506b804,0xb49110bd,0xb4fa0347,0xb4a84807,0xb3d28804,
0x354c1907,0x35476700,0x3479cc4b,0x34049e0a,0x353e63f5,0x353141d7,0x32490dd6,0xb3d783e3,0x3520496e,0x350bd8c6,0xb461bf99,0xb4a96d1f,0x34e8c245,0x34b4c922,0xb4de4f8b,0xb5073101,
0x3548fc89,0x352ffc2a,0xb548bdc6,0xb54aacb2,0x350268a9,0x348b2c30,0xb534e9ae,0xb50a000c,0x3120d96b,0xb488ce67,0xb49de84a,0xb32ad33e,0xb5016ffc,0xb52f56c7,0x346b6521,0x34f2fcea,
0,0,0,0,0,0,0,0,0,0,0,0,0,0,0,0,
0x33b4968b,0x3477673d,0x354b8d5a,0x35433cb1,0x34c580a2,0x3503db51,0x35336b4e,0x351cb4cd,0x351fe51e,0x3535c9e1,0x34fff144,0x34bca2fc,0x3544b238,0x354c0b7a,0x346429d0,0x338c9200,
0x32b4eec8,0x337b14c1,0x34a72288,0x34b9484b,0x33cd8ba2,0x340e8710,0x34cafbc9,0x34dc3217,0x3435f068,0x345ce98c,0x34ece099,0x34fcfd04,0x3481ad39,0x349495b2,0x35063eb4,0x350dac1c,
0x33e17a10,0x349941f2,0x35309fda,0x35122466,0x34f0f5cb,0x351d1c2c,0x34d5cd14,0x34750196,0x353852c1,0x35487d14,0x333ee693,0xb4186a98,0x354ca31b,0x3544852f,0xb4abb614,0xb500760f,
0x3334dd20,0x33fa57c9,0x3518967c,0x35253e0d,0x344bebe7,0x348c5a95,0x35304e38,0x3539abba,0x34b1652e,0x34d4ba6c,0x35413f79,0x3546f6c8,0x34f60334,0x350a76bb,0x354ac390,0x354c9c72,
0x340718ca,0x34b5e995,0x34ede6c2,0x3482de37,0x350c4e1d,0x35319232,0x32c907c8,0xb455a47e,0x35478b72,0x354c556c,0xb4d901f0,0xb51a40ae,0x353f868d,0x35223933,0xb53ab7a7,0xb54b1a27,
0x33878fc8,0x343ad62f,0x35430be1,0x354a193c,0x3496ec8c,0x34cd29a4,0x354cc6a2,0x354b053d,0x34fef5cc,0x35159e88,0x3544dec8,0x353a7558,0x35288507,0x3537c5a7,0x352c02a0,0x3519d6b0,
0x341d5a2e,0x34d17f65,0x3422483f,0xb3eb6e11,0x351de9c7,0x35409d9b,0xb4bff996,0xb51752fa,0x354ccc8e,0x354109fb,0xb53cf81d,0xb54c8582,0x351eb5dd,0x34d3a742,0xb54429b0,0xb524ded4,
0x3f80,0x3f80,0x3f553f0e,0x3f553f0e,0x3e793f78,0xbe79bf78,0x3f713eac,0xbf71beac,0x3ef13f62,0x3ef13f62,0x3f7f3dc9,0x3f7f3dc9,0x3f2c3f3e,0xbf2cbf3e,0x3f7dbe16,0xbf7d3e16,
0x3f80,0x3f80,0x3f0ebf55,0x3f0ebf55,0x3f183f4e,0xbf18bf4e,0xbd49bf80,0x3d493f80,0x3f753e95,0x3f753e95,0xbf22bf46,0xbf22bf46,0x3f71beac,0xbf713eac,0xbf78be79,0x3f783e79,
0x3f80,0x3f80,0xbf55bf0e,0xbf55bf0e,0x3f5c3f04,0xbf5cbf04,0xbf673edb,0x3f67bedb,0x3f62bef1,0x3f62bef1,0xbdc93f7f,0xbdc93f7f,0x3d49bf80,0xbd493f80,0x3f4e3f18,0xbf4ebf18,
0x3f80,0x3f80,0xbf0e3f55,0xbf0e3f55,0x3f7d3e16,0xbf7dbe16,0x3f3e3f2c,0xbf3ebf2c,0x3e95bf75,0x3e95bf75,0x3f46bf22,0x3f46bf22,0xbf67bedb,0x3f673edb,0xbf04bf5c,0x3f043f5c,
0x3f80,0x3f80,0x3f553f0e,0x3f553f0e,0x3f78be79,0xbf783e79,0x3eacbf71,0xbeac3f71,0xbef1bf62,0xbef1bf62,0xbf7fbdc9,0xbf7fbdc9,0xbf3e3f2c,0x3f3ebf2c,0x3e163f7d,0xbe16bf7d,
0x3f80,0x3f80,0x3f0ebf55,0x3f0ebf55,0x3f4ebf18,0xbf4e3f18,0xbf803d49,0x3f80bd49,0xbf75be95,0xbf75be95,0x3f223f46,0x3f223f46,0x3eac3f71,0xbeacbf71,0x3e79bf78,0xbe793f78,
0x3f80,0x3f80,0xbf55bf0e,0xbf55bf0e,0x3f04bf5c,0xbf043f5c,0x3edb3f67,0xbedbbf67,0xbf623ef1,0xbf623ef1,0x3dc9bf7f,0x3dc9bf7f,0x3f803d49,0xbf80bd49,0xbf183f4e,0x3f18bf4e,
0x3f80,0x3f80,0xbf0e3f55,0xbf0e3f55,0x3e16bf7d,0xbe163f7d,0x3f2cbf3e,0xbf2c3f3e,0xbe953f75,0xbe953f75,0xbf463f22,0xbf463f22,0x3edbbf67,0xbedb3f67,0x3f5cbf04,0xbf5c3f04,
0x3f6dbec4,0x3f6dbec4,0x3e48bf7b,0x3e48bf7b,0x3f4ebf18,0xbf4e3f18,0xbd49bf80,0x3d493f80,0x3f22bf46,0x3f22bf46,0xbe95bf75,0xbe95bf75,0x3edbbf67,0xbedb3f67,0xbf04bf5c,0x3f043f5c,
0xbf6d3ec4,0xbf6d3ec4,0x3f7b3e48,0x3f7b3e48,0xbf043f5c,0x3f04bf5c,0x3f67bedb,0xbf673edb,0x3dc93f7f,0x3dc93f7f,0x3ef1bf62,0x3ef1bf62,0x3f2c3f3e,0xbf2cbf3e,0xbe16bf7d,0x3e163f7d,
0x3f6dbec4,0x3f6dbec4,0xbe483f7b,0xbe483f7b,0x3e16bf7d,0xbe163f7d,0x3f3e3f2c,0xbf3ebf2c,0xbf46bf22,0xbf46bf22,0x3f75be95,0x3f75be95,0xbf713eac,0x3f71beac,0x3e79bf78,0xbe793f78,
0xbf6d3ec4,0xbf6d3ec4,0xbf7bbe48,0xbf7bbe48,0x3e793f78,0xbe79bf78,0xbeac3f71,0x3eacbf71,0x3f7fbdc9,0x3f7fbdc9,0x3f623ef1,0x3f623ef1,0x3d49bf80,0xbd493f80,0x3f18bf4e,0xbf183f4e,
0x3f6dbec4,0x3f6dbec4,0x3e48bf7b,0x3e48bf7b,0xbf18bf4e,0x3f183f4e,0xbf803d49,0x3f80bd49,0xbf223f46,0xbf223f46,0x3e953f75,0x3e953f75,0x3f673edb,0xbf67bedb,0x3f5cbf04,0xbf5c3f04,
0xbf6d3ec4,0xbf6d3ec4,0x3f7b3e48,0x3f7b3e48,0x3f5c3f04,0xbf5cbf04,0xbedbbf67,0x3edb3f67,0xbdc9bf7f,0xbdc9bf7f,0xbef13f62,0xbef13f62,0xbf3e3f2c,0x3f3ebf2c,0x3f7dbe16,0xbf7d3e16,
0x3f6dbec4,0x3f6dbec4,0xbe483f7b,0xbe483f7b,0xbf7dbe16,0x3f7d3e16,0x3f2cbf3e,0xbf2c3f3e,0x3f463f22,0x3f463f22,0xbf753e95,0xbf753e95,0xbeacbf71,0x3eac3f71,0x3f783e79,0xbf78be79,
0xbf6d3ec4,0xbf6d3ec4,0xbf7bbe48,0xbf7bbe48,0x3f78be79,0xbf783e79,0x3f713eac,0xbf71beac,0xbf7f3dc9,0xbf7f3dc9,0xbf62bef1,0xbf62bef1,0x3f803d49,0xbf80bd49,0x3f4e3f18,0xbf4ebf18,
0x3f800000,0x3f800000,0x3f0ebf55,0x3f0ebf55,0x3f78be79,0xbf783e79,0x3eacbf71,0xbeac3f71,0x3f62bef1,0x3f62bef1,0x3dc9bf7f,0x3dc9bf7f,0x3f3ebf2c,0xbf3e3f2c,0xbe16bf7d,0x3e163f7d,
0x3f800000,0x3f800000,0xbf55bf0e,0xbf55bf0e,0x3f4ebf18,0xbf4e3f18,0xbf803d49,0x3f80bd49,0x3e95bf75,0x3e95bf75,0xbf463f22,0xbf463f22,0xbeacbf71,0x3eac3f71,0xbe793f78,0x3e79bf78,
0x3f800000,0x3f800000,0xbf0e3f55,0xbf0e3f55,0x3f04bf5c,0xbf043f5c,0x3edb3f67,0xbedbbf67,0xbef1bf62,0xbef1bf62,0x3f7f3dc9,0x3f7f3dc9,0xbf80bd49,0x3f803d49,0x3f18bf4e,0xbf183f4e,
0x3f800000,0x3f800000,0x3f553f0e,0x3f553f0e,0x3e16bf7d,0xbe163f7d,0x3f2cbf3e,0xbf2c3f3e,0xbf75be95,0xbf75be95,0xbf22bf46,0xbf22bf46,0xbedb3f67,0x3edbbf67,0xbf5c3f04,0x3f5cbf04,
0x3f800000,0x3f800000,0x3f0ebf55,0x3f0ebf55,0xbe79bf78,0x3e793f78,0xbf71beac,0x3f713eac,0xbf623ef1,0xbf623ef1,0xbdc93f7f,0xbdc93f7f,0x3f2c3f3e,0xbf2cbf3e,0x3f7dbe16,0xbf7d3e16,
0x3f800000,0x3f800000,0xbf55bf0e,0xbf55bf0e,0xbf18bf4e,0x3f183f4e,0x3d493f80,0xbd49bf80,0xbe953f75,0xbe953f75,0x3f46bf22,0x3f46bf22,0x3f71beac,0xbf713eac,0xbf78be79,0x3f783e79,
0x3f800000,0x3f800000,0xbf0e3f55,0xbf0e3f55,0xbf5cbf04,0x3f5c3f04,0x3f67bedb,0xbf673edb,0x3ef13f62,0x3ef13f62,0xbf7fbdc9,0xbf7fbdc9,0x3d49bf80,0xbd493f80,0x3f4e3f18,0xbf4ebf18,
0x3f800000,0x3f800000,0x3f553f0e,0x3f553f0e,0xbf7dbe16,0x3f7d3e16,0xbf3ebf2c,0x3f3e3f2c,0x3f753e95,0x3f753e95,0x3f223f46,0x3f223f46,0xbf67bedb,0x3f673edb,0xbf04bf5c,0x3f043f5c,
0xbec4bf6d,0xbec4bf6d,0xbf7bbe48,0xbf7bbe48,0xbf18bf4e,0x3f183f4e,0xbf803d49,0x3f80bd49,0xbf46bf22,0xbf46bf22,0xbf753e95,0xbf753e95,0xbf67bedb,0x3f673edb,0xbf5c3f04,0x3f5cbf04,
0x3ec43f6d,0x3ec43f6d,0x3e48bf7b,0x3e48bf7b,0x3f5c3f04,0xbf5cbf04,0xbedbbf67,0x3edb3f67,0x3f7fbdc9,0x3f7fbdc9,0xbf62bef1,0xbf62bef1,0x3f3ebf2c,0xbf3e3f2c,0xbf7d3e16,0x3f7dbe16,
0xbec4bf6d,0xbec4bf6d,0x3f7b3e48,0x3f7b3e48,0xbf7dbe16,0x3f7d3e16,0x3f2cbf3e,0xbf2c3f3e,0xbf223f46,0xbf223f46,0xbe95bf75,0xbe95bf75,0x3eac3f71,0xbeacbf71,0xbf78be79,0x3f783e79,
0x3ec43f6d,0x3ec43f6d,0xbe483f7b,0xbe483f7b,0x3f78be79,0xbf783e79,0x3f713eac,0xbf71beac,0xbdc9bf7f,0xbdc9bf7f,0x3ef1bf62,0x3ef1bf62,0xbf80bd49,0x3f803d49,0xbf4ebf18,0x3f4e3f18,
0xbec4bf6d,0xbec4bf6d,0xbf7bbe48,0xbf7bbe48,0xbf4e3f18,0x3f4ebf18,0x3d493f80,0xbd49bf80,0x3f463f22,0x3f463f22,0x3f75be95,0x3f75be95,0x3edbbf67,0xbedb3f67,0xbf04bf5c,0x3f043f5c,
0x3ec43f6d,0x3ec43f6d,0x3e48bf7b,0x3e48bf7b,0x3f04bf5c,0xbf043f5c,0xbf673edb,0x3f67bedb,0xbf7f3dc9,0xbf7f3dc9,0x3f623ef1,0x3f623ef1,0x3f2c3f3e,0xbf2cbf3e,0xbe16bf7d,0x3e163f7d,
0xbec4bf6d,0xbec4bf6d,0x3f7b3e48,0x3f7b3e48,0xbe163f7d,0x3e16bf7d,0xbf3ebf2c,0x3f3e3f2c,0x3f22bf46,0x3f22bf46,0x3e953f75,0x3e953f75,0xbf713eac,0x3f71beac,0x3e79bf78,0xbe793f78,
0x3ec43f6d,0x3ec43f6d,0xbe483f7b,0xbe483f7b,0xbe79bf78,0x3e793f78,0x3eacbf71,0xbeac3f71,0x3dc93f7f,0x3dc93f7f,0xbef13f62,0xbef13f62,0x3d49bf80,0xbd493f80,0x3f18bf4e,0xbf183f4e,
0x3f803f80,0x3ec4bec4,0x3f803f80,0x3ec4bec4,0x3f803f80,0x3ec4bec4,0x3f803f80,0x3ec4bec4,0x3f803f80,0x3ec4bec4,0x3f803f80,0x3ec4bec4,0x3f803f80,0x3ec4bec4,0x3f803f80,0x3ec4bec4,
0x3f4e3f78,0x3f5cbf18,0xbf4ebf78,0xbf5c3f18,0x3e163f04,0x3f78bf7d,0xbe16bf04,0xbf783f7d,0xbf18be79,0x3f04bf4e,0x3f183e79,0xbf043f4e,0xbf7dbf5c,0xbe79be16,0x3f7d3f5c,0x3e793e16,
0x3e953f62,0x3f7fbf46,0x3e953f62,0x3f7fbf46,0xbf75bef1,0xbdc9bf22,0xbf75bef1,0xbdc9bf22,0xbe95bf62,0xbf7f3f46,0xbe95bf62,0xbf7f3f46,0x3f753ef1,0x3dc93f22,0x3f753ef1,0x3dc93f22,
0xbeac3f3e,0x3f3ebf67,0x3eacbf3e,0xbf3e3f67,0xbedbbf80,0xbf803eac,0x3edb3f80,0x3f80beac,0x3f713f2c,0x3f2c3edb,0xbf71bf2c,0xbf2cbedb,0xbf673d49,0x3d49bf71,0x3f67bd49,0xbd493f71,
0xbf553f0e,0x3e48bf7b,0xbf553f0e,0x3e48bf7b,0x3f55bf0e,0xbe483f7b,0x3f55bf0e,0xbe483f7b,0xbf553f0e,0x3e48bf7b,0xbf553f0e,0x3e48bf7b,0x3f55bf0e,0xbe483f7b,0x3f55bf0e,0xbe483f7b,
0xbf803eac,0xbedbbf80,0x3f80beac,0x3edb3f80,0x3f2c3edb,0x3f713f2c,0xbf2cbedb,0xbf71bf2c,0x3d49bf71,0xbf673d49,0xbd493f71,0x3f67bd49,0xbf3e3f67,0x3eacbf3e,0x3f3ebf67,0xbeac3f3e,
0xbf463dc9,0xbf62bf75,0xbf463dc9,0xbf62bf75,0xbf223f7f,0x3ef1be95,0xbf223f7f,0x3ef1be95,0x3f46bdc9,0x3f623f75,0x3f46bdc9,0x3f623f75,0x3f22bf7f,0xbef13e95,0x3f22bf7f,0xbef13e95,
0xbe79be16,0xbf7dbf5c,0x3e793e16,0x3f7d3f5c,0xbf5c3f18,0xbf4ebf78,0x3f5cbf18,0x3f4e3f78,0xbf783f7d,0xbe16bf04,0x3f78bf7d,0x3e163f04,0xbf043f4e,0x3f183e79,0x3f04bf4e,0xbf18be79,
0,0xbf6d3f6d,0,0xbf6d3f6d,0,0xbf6d3f6d,0,0xbf6d3f6d,0,0xbf6d3f6d,0,0xbf6d3f6d,0,0xbf6d3f6d,0,0xbf6d3f6d,
0x3f183e79,0xbf043f4e,0xbf18be79,0x3f04bf4e,0x3f7d3f5c,0x3e793e16,0xbf7dbf5c,0xbe79be16,0x3f4e3f78,0x3f5cbf18,0xbf4ebf78,0xbf5c3f18,0x3e163f04,0x3f78bf7d,0xbe16bf04,0xbf783f7d,
0x3f753ef1,0x3dc93f22,0x3f753ef1,0x3dc93f22,0x3e953f62,0x3f7fbf46,0x3e953f62,0x3f7fbf46,0xbf75bef1,0xbdc9bf22,0xbf75bef1,0xbdc9bf22,0xbe95bf62,0xbf7f3f46,0xbe95bf62,0xbf7f3f46,
0x3f713f2c,0x3f2c3edb,0xbf71bf2c,0xbf2cbedb,0xbf673d49,0x3d49bf71,0x3f67bd49,0xbd493f71,0x3eacbf3e,0xbf3e3f67,0xbeac3f3e,0x3f3ebf67,0x3edb3f80,0x3f80beac,0xbedbbf80,0xbf803eac,
0x3f0e3f55,0x3f7b3e48,0x3f0e3f55,0x3f7b3e48,0xbf0ebf55,0xbf7bbe48,0xbf0ebf55,0xbf7bbe48,0x3f0e3f55,0x3f7b3e48,0x3f0e3f55,0x3f7b3e48,0xbf0ebf55,0xbf7bbe48,0xbf0ebf55,0xbf7bbe48,
0xbd493f71,0x3f67bd49,0x3d49bf71,0xbf673d49,0x3f3ebf67,0xbeac3f3e,0xbf3e3f67,0x3eacbf3e,0xbf803eac,0xbedbbf80,0x3f80beac,0x3edb3f80,0x3f2c3edb,0x3f713f2c,0xbf2cbedb,0xbf71bf2c,
0xbf223f7f,0x3ef1be95,0xbf223f7f,0x3ef1be95,0x3f46bdc9,0x3f623f75,0x3f46bdc9,0x3f623f75,0x3f22bf7f,0xbef13e95,0x3f22bf7f,0xbef13e95,0xbf463dc9,0xbf62bf75,0xbf463dc9,0xbf62bf75,
0xbf783f7d,0xbe16bf04,0x3f78bf7d,0x3e163f04,0xbf043f4e,0x3f183e79,0x3f04bf4e,0xbf18be79,0x3e793e16,0x3f7d3f5c,0xbe79be16,0xbf7dbf5c,0x3f5cbf18,0x3f4e3f78,0xbf5c3f18,0xbf4ebf78,
0,0x3f6dbf6d,0,0x3f6dbf6d,0,0x3f6dbf6d,0,0x3f6dbf6d,0,0x3f6dbf6d,0,0x3f6dbf6d,0,0x3f6dbf6d,0,0x3f6dbf6d,
0xbf18be79,0x3f04bf4e,0x3f183e79,0xbf043f4e,0xbf7dbf5c,0xbe79be16,0x3f7d3f5c,0x3e793e16,0xbf4ebf78,0xbf5c3f18,0x3f4e3f78,0x3f5cbf18,0xbe16bf04,0xbf783f7d,0x3e163f04,0x3f78bf7d,
0xbf75bef1,0xbdc9bf22,0xbf75bef1,0xbdc9bf22,0xbe95bf62,0xbf7f3f46,0xbe95bf62,0xbf7f3f46,0x3f753ef1,0x3dc93f22,0x3f753ef1,0x3dc93f22,0x3e953f62,0x3f7fbf46,0x3e953f62,0x3f7fbf46,
0xbf71bf2c,0xbf2cbedb,0x3f713f2c,0x3f2c3edb,0x3f67bd49,0xbd493f71,0xbf673d49,0x3d49bf71,0xbeac3f3e,0x3f3ebf67,0x3eacbf3e,0xbf3e3f67,0xbedbbf80,0xbf803eac,0x3edb3f80,0x3f80beac,
0xbf0ebf55,0xbf7bbe48,0xbf0ebf55,0xbf7bbe48,0x3f0e3f55,0x3f7b3e48,0x3f0e3f55,0x3f7b3e48,0xbf0ebf55,0xbf7bbe48,0xbf0ebf55,0xbf7bbe48,0x3f0e3f55,0x3f7b3e48,0x3f0e3f55,0x3f7b3e48,
0x3d49bf71,0xbf673d49,0xbd493f71,0x3f67bd49,0xbf3e3f67,0x3eacbf3e,0x3f3ebf67,0xbeac3f3e,0x3f80beac,0x3edb3f80,0xbf803eac,0xbedbbf80,0xbf2cbedb,0xbf71bf2c,0x3f2c3edb,0x3f713f2c,
0x3f22bf7f,0xbef13e95,0x3f22bf7f,0xbef13e95,0xbf463dc9,0xbf62bf75,0xbf463dc9,0xbf62bf75,0xbf223f7f,0x3ef1be95,0xbf223f7f,0x3ef1be95,0x3f46bdc9,0x3f623f75,0x3f46bdc9,0x3f623f75,
0x3f78bf7d,0x3e163f04,0xbf783f7d,0xbe16bf04,0x3f04bf4e,0xbf18be79,0xbf043f4e,0x3f183e79,0xbe79be16,0xbf7dbf5c,0x3e793e16,0x3f7d3f5c,0xbf5c3f18,0xbf4ebf78,0x3f5cbf18,0x3f4e3f78,
0x3f800000,0x3f7fe129,0x3f800000,0x3f696591,0x3f7f84ab,0x3f7eea9d,0x3f299415,0x3e97a117,0x3f7e1324,0x3f7cfe73,0xbdfab273,0xbf04f484,0x3f7baccd,0x3f7a1e84,0xbf531849,0xbf7bf531,
0x3f800000,0x3f7f2f9d,0x3f800000,0x3f63f473,0x3f7cbfc9,0x3f78b47b,0x3f15f6d9,0x3e1c76de,0x3f731447,0x3f6be858,0xbea09ae5,0xbf36206c,0x3f633c5a,0x3f591e6a,0xbf740bdd,0xbf7c7eb0,
0x3f800000,0x3f7de0b1,0x3f800000,0x3f5df6be,0x3f778bc5,0x3f6d1c1d,0x3f00e7e4,0x3bc90f88,0x3f5ebe05,0x3f4cae79,0xbefc5d27,0xbf5c61c7,0x3f373a23,0x3f1ebc12,0xbf7ffb11,0xbf5f8327,
0x3f800000,0x3f7bf531,0x3f800000,0x3f577026,0x3f6ff573,0x3f5c61c7,0x3ed53641,0xbe1008b7,0x3f41d870,0x3f212ff9,0xbf273656,0xbf756d97,0x3ef6e0cb,0x3ea395c5,0xbf75dec6,0xbf286605,
0x3f800000,0x3f796e4e,0x3f800000,0x3f5064af,0x3f660f88,0x3f46e22a,0x3ea68f12,0xbe919ddd,0x3f1d7fd1,0x3ed8106b,0xbf49d112,0xbf7fc38f,0x3e541501,0xbc96c9b6,0xbf5695e5,0xbebb31a0,
0x3f800000,0x3f764d97,0x3f800000,0x3f48d8b3,0x3f59f26a,0x3f2d1469,0x3e6c9a7f,0xbed8106b,0x3ee63375,0x3e419b37,0xbf64aa59,0xbf7ac516,0xbdafb680,0xbeb554ec,0xbf24d225,0xbcfb49ba,
0x3f800000,0x3f7294f8,0x3f800000,0x3f40d0da,0x3f4bbbf8,0x3f0f8784,0x3e09cf86,0xbf0cead0,0x3e888e93,0xbd621469,0xbf76ba07,0xbf66becc,0xbebe1d4a,0xbf26050a,0xbec9b953,0x3e9d9e78,
0x3f800000,0x3f6e46be,0x3f800000,0x3f385216,0x3f3b8f3b,0x3eddbe79,0x3d16c32c,0xbf2ac082,0x3d96a905,0xbe97a117,0xbf7f4e6d,0xbf44e3f5,0xbf1ff6cb,0xbf5df6be,0xbde1bc2e,0x3f1c420c,
0,0x3cfb49ba,0,0x3ed25a09,0x3d7b2b74,0x3dbc3ac3,0x3f3fc767,0x3f748422,0x3dfab273,0x3e1c76de,0x3f7e1324,0x3f5ac450,0x3e3b6ecf,0x3e5a3997,0x3f10d3cd,0x3e354098,
0,0x3da3308c,0,0x3ee900b7,0x3e22abb6,0x3e72b651,0x3f4f7a1f,0x3f7cfe73,0x3ea09ae5,0x3ec6d529,0x3f731447,0x3f33e7bc,0x3eebcbbb,0x3f07a136,0x3e9aa086,0xbe28defc,
0,0x3e039502,0,0x3eff17b2,0x3e827dc0,0x3ec1071e,0x3f5d2d53,0x3f7ffec4,0x3efc5d27,0x3f19c200,0x3f5ebe05,0x3f0242b1,0x3f32c8c9,0x3f48d8b3,0x3c490e90,0xbef9a02d,
0,0x3e354098,0,0x3f0a48ad,0x3eb263ef,0x3f0242b1,0x3f68bf3c,0x3f7d7474,0x3f273656,0x3f46e22a,0x3f41d870,0x3e919ddd,0x3f604621,0x3f7294f8,0xbe8e9a22,0xbf40d0da,
0,0x3e667c66,0,0x3f14b039,0x3ee0924f,0x3f212ff9,0x3f721352,0x3f756d97,0x3f49d112,0x3f6816a8,0x3f1d7fd1,0x3d2fe007,0x3f7a7302,0x3f7ff4e6,0xbf0b9a6b,0xbf6e46be,
0,0x3e8b9507,0,0x3f1ebc12,0x3f064b82,0x3f3ca003,0x3f791298,0x3f6816a8,0x3f64aa59,0x3f7b61fc,0x3ee63375,0xbe4dee60,0x3f7f0e58,0x3f6f6830,0xbf43e200,0xbf7fe129,
0,0x3ea395c5,0,0x3f286605,0x3f1b02c6,0x3f53fac3,0x3f7dabcc,0x3f55b993,0x3f76ba07,0x3f7f9c18,0x3e888e93,0xbeddbe79,0x3f6db293,0x3f42de29,0xbf6b4b0c,0xbf73913f,
0,0x3ebb31a0,0,0x3f31a81d,0x3f2e3bde,0x3f66becc,0x3f7fd397,0x3f3ebc1b,0x3f7f4e6d,0x3f748422,0x3d96a905,0xbf239da9,0x3f47de65,0x3eff17b2,0xbf7e70b0,0xbf4ac77f,
0x354ccccd,0x354ccccd,0x354ccccd,0x354ccccd,0x354ccccd,0x354ccccd,0x354ccccd,0x354ccccd,0x354ccccd,0x354ccccd,0x354ccccd,0x354ccccd,0x354ccccd,0x354ccccd,0x354ccccd,0x354ccccd,
0x354b4283,0x354276a0,0xb3c88ec2,0xb4807bea,0x3532319e,0x351b138d,0xb4c9e41f,0xb505c511,0x34fbffb5,0x34b8292a,0xb521740f,0xb536eeae,0x345a7db8,0x33710e6e,0xb545619f,0xb54c3ebe,
0x354cb421,0x354c2618,0x353ab7a7,0x35365d28,0x354b1a27,0x354990f4,0x35319232,0x352c59b8,0x35478b72,0x35450adf,0x3526b6f3,0x3520ad5c,0x354210c7,0x353e9eff,0x351a40ae,0x351374de,
0x354a6529,0x353cb9e0,0xb4d4ba6c,0xb511b389,0x3523bec8,0x3500f32d,0xb5304e38,0xb54457ac,0x34acd9f0,0x341ae293,0xb54c9c72,0xb5489dab,0xb334dd20,0xb4729b58,0xb53898a3,0xb51d832a,
0x354c6a23,0x354a3307,0x3507a9aa,0x34eff15b,0x3546096a,0x353ff78f,0x34ce3fd4,0x34aa91ce,0x35380c6c,0x352e5b88,0x34853f42,0x343d4866,0x3522fcc6,0x35160c2f,0x33dc7f3e,0x32f13846,
0x3549570a,0x3535c9e1,0xb528e03a,0xb5433cb1,0x351294e9,0x34c580a2,0xb54cc8da,0xb544b238,0x3429aa67,0xb38c9200,0xb52bab1e,0xb503db51,0xb498176e,0xb4fff144,0xb4a1610f,0xb3b4968b,
0x354beee4,0x3546f6c8,0x34729b58,0x33fa57c9,0x353db017,0x35304e38,0x31a0d93a,0xb3e67457,0x351f1b54,0x350a76bb,0xb468fc95,0xb4acd9f0,0x34e5a5a1,0x34b1652e,0xb4e177b4,0xb5089a01,
0x3548186a,0x352db1ef,0xb54990f4,0xb549fef3,0x34fdf9b6,0x3482de37,0xb532cf52,0xb506b804,0xb27142bd,0xb49110bd,0xb495c14d,0xb2c907c8,0xb504d0d5,0xb5319232,0x347c30c0,0x34fa0347,
0,0,0,0,0,0,0,0,0,0,0,0,0,0,0,0,
0x33c88ec2,0x34807bea,0x354b4283,0x354276a0,0x34c9e41f,0x3505c511,0x3532319e,0x351b138d,0x3521740f,0x3536eeae,0x34fbffb5,0x34b8292a,0x3545619f,0x354c3ebe,0x345a7db8,0x33710e6e,
0x32c907c8,0x33828d3d,0x34a84807,0x34ba66f9,0x33d28804,0x3411007a,0x34cc12f5,0x34dd4116,0x34386384,0x345f54d8,0x34ede6c2,0x34fdf9b6,0x3482de37,0x3495c14d,0x3506b804,0x350e2017,
0x33fa57c9,0x349f10ee,0x352f0373,0x350fec97,0x34f60334,0x351f1b54,0x34d06ab5,0x3468fc95,0x3539abba,0x35491b30,0x330cb338,0xb424beb3,0x354c7ce0,0x35439ce8,0xb4b1652e,0xb502e487,
0x3348ef90,0x340222f8,0x35196c52,0x3525fb4c,0x3450c934,0x348eb659,0x3530f10f,0x353a3296,0x34b3a83f,0x34d6df37,0x3541a90f,0x35474213,0x34f8046f,0x350b6318,0x354aefd6,0x354ca946,
0x3415f23f,0x34bca2fc,0x34e7b948,0x3477673d,0x350f0707,0x35336b4e,0x3220d873,0xb46429d0,0x35485c01,0x354c0b7a,0xb4df5d78,0xb51cb4cd,0x353e2876,0x351fe51e,0xb53c3c09,0xb54b8d5a,
0x33969569,0x34422b74,0x35439ce8,0x354a6529,0x349a6c18,0x34d06ab5,0x354ccbd0,0x354ac390,0x3500f32d,0x3516e669,0x354457ac,0x3539abba,0x35299568,0x353898a3,0x352afadc,0x3518967c,
0x342e9479,0x34d901f0,0x3411007a,0xb40718ca,0x3520ad5c,0x354210c7,0xb4c7b357,0xb51a40ae,0x354cc3eb,0x353f868d,0xb53e9eff,0xb54cb421,0x351be4ed,0x34cc12f5,0xb542da99,0xb5223933,
0x3f80,0x3f80,0x3f623ef1,0x3f623ef1,0x3e893f77,0xbe89bf77,0x3f7a3e60,0xbf7abe60,0x3f043f5c,0x3f043f5c,0x3f80bd49,0x3f80bd49,0x3f393f31,0xbf39bf31,0x3f73bea1,0xbf733ea1,
0x3f80,0x3f80,0x3ef1bf62,0x3ef1bf62,0x3f1d3f4a,0xbf1dbf4a,0xbe2fbf7c,0x3e2f3f7c,0x3f783e79,0x3f783e79,0xbf3ebf2c,0xbf3ebf2c,0x3f6abecf,0xbf6a3ecf,0xbf7fbd97,0x3f7f3d97,
0x3f80,0x3f80,0xbf62bef1,0xbf62bef1,0x3f5f3efc,0xbf5fbefc,0xbf583f09,0x3f58bf09,0x3f5cbf04,0x3f5cbf04,0x3d493f80,0x3d493f80,0xbcc9bf80,0x3cc93f80,0x3f653ee6,0xbf65bee6,
0x3f80,0x3f80,0xbef13f62,0xbef13f62,0x3f7e3dfb,0xbf7ebdfb,0x3f513f13,0xbf51bf13,0x3e79bf78,0x3e79bf78,0x3f2cbf3e,0x3f2cbf3e,0xbf6fbeb8,0x3f6f3eb8,0xbf27bf42,0x3f273f42,
0x3f80,0x3f80,0x3f623ef1,0x3f623ef1,0x3f77be89,0xbf773e89,0x3e60bf7a,0xbe603f7a,0xbf04bf5c,0xbf04bf5c,0xbf803d49,0xbf803d49,0xbf313f39,0x3f31bf39,0x3ea13f73,0xbea1bf73,
0x3f80,0x3f80,0x3ef1bf62,0x3ef1bf62,0x3f4abf1d,0xbf4a3f1d,0xbf7c3e2f,0x3f7cbe2f,0xbf78be79,0xbf78be79,0x3f3e3f2c,0x3f3e3f2c,0x3ecf3f6a,0xbecfbf6a,0x3d97bf7f,0xbd973f7f,
0x3f80,0x3f80,0xbf62bef1,0xbf62bef1,0x3efcbf5f,0xbefc3f5f,0x3f093f58,0xbf09bf58,0xbf5c3f04,0xbf5c3f04,0xbd49bf80,0xbd49bf80,0x3f80bcc9,0xbf803cc9,0xbee63f65,0x3ee6bf65,
0x3f80,0x3f80,0xbef13f62,0xbef13f62,0x3dfbbf7e,0xbdfb3f7e,0x3f13bf51,0xbf133f51,0xbe793f78,0xbe793f78,0xbf2c3f3e,0xbf2c3f3e,0x3eb8bf6f,0xbeb83f6f,0x3f42bf27,0xbf423f27,
0x3f55bf0e,0x3f55bf0e,0xbdc9bf7f,0xbdc9bf7f,0x3f27bf42,0xbf273f42,0xbeb8bf6f,0x3eb83f6f,0x3edbbf67,0x3edbbf67,0xbf18bf4e,0xbf18bf4e,0x3e2fbf7c,0xbe2f3f7c,0xbf4abf1d,0x3f4a3f1d,
0xbf553f0e,0xbf553f0e,0x3f7fbdc9,0x3f7fbdc9,0xbea13f73,0x3ea1bf73,0x3f39bf31,0xbf393f31,0x3eac3f71,0x3eac3f71,0x3e16bf7d,0x3e16bf7d,0x3f583f09,0xbf58bf09,0xbefcbf5f,0x3efc3f5f,
0x3f55bf0e,0x3f55bf0e,0x3dc93f7f,0x3dc93f7f,0xbd97bf7f,0x3d973f7f,0x3f6a3ecf,0xbf6abecf,0xbf67bedb,0xbf67bedb,0x3f4ebf18,0x3f4ebf18,0xbf513f13,0x3f51bf13,0xbdfbbf7e,0x3dfb3f7e,
0xbf553f0e,0xbf553f0e,0xbf7f3dc9,0xbf7f3dc9,0x3ee63f65,0xbee6bf65,0xbcc93f80,0x3cc9bf80,0x3f71beac,0x3f71beac,0x3f7d3e16,0x3f7d3e16,0xbe60bf7a,0x3e603f7a,0x3e89bf77,0xbe893f77,
0x3f55bf0e,0x3f55bf0e,0xbdc9bf7f,0xbdc9bf7f,0xbf42bf27,0x3f423f27,0xbf6f3eb8,0x3f6fbeb8,0xbedb3f67,0xbedb3f67,0x3f183f4e,0x3f183f4e,0x3f7c3e2f,0xbf7cbe2f,0x3f1dbf4a,0xbf1d3f4a,
0xbf553f0e,0xbf553f0e,0x3f7fbdc9,0x3f7fbdc9,0x3f733ea1,0xbf73bea1,0xbf31bf39,0x3f313f39,0xbeacbf71,0xbeacbf71,0xbe163f7d,0xbe163f7d,0xbf093f58,0x3f09bf58,0x3f5fbefc,0xbf5f3efc,
0x3f55bf0e,0x3f55bf0e,0x3dc93f7f,0x3dc93f7f,0xbf7f3d97,0x3f7fbd97,0x3ecfbf6a,0xbecf3f6a,0x3f673edb,0x3f673edb,0xbf4e3f18,0xbf4e3f18,0xbf13bf51,0x3f133f51,0x3f7ebdfb,0xbf7e3dfb,
0xbf553f0e,0xbf553f0e,0xbf7f3dc9,0xbf7f3dc9,0x3f65bee6,0xbf653ee6,0x3f803cc9,0xbf80bcc9,0xbf713eac,0xbf713eac,0xbf7dbe16,0xbf7dbe16,0x3f7abe60,0xbf7a3e60,0x3f773e89,0xbf77be89,
0x3f800000,0x3f800000,0x3ef1bf62,0x3ef1bf62,0x3f77be89,0xbf773e89,0x3e60bf7a,0xbe603f7a,0x3f5cbf04,0x3f5cbf04,0xbd49bf80,0xbd49bf80,0x3f31bf39,0xbf313f39,0xbea1bf73,0x3ea13f73,
0x3f800000,0x3f800000,0xbf62bef1,0xbf62bef1,0x3f4abf1d,0xbf4a3f1d,0xbf7c3e2f,0x3f7cbe2f,0x3e79bf78,0x3e79bf78,0xbf2c3f3e,0xbf2c3f3e,0xbecfbf6a,0x3ecf3f6a,0xbd973f7f,0x3d97bf7f,
0x3f800000,0x3f800000,0xbef13f62,0xbef13f62,0x3efcbf5f,0xbefc3f5f,0x3f093f58,0xbf09bf58,0xbf04bf5c,0xbf04bf5c,0x3f80bd49,0x3f80bd49,0xbf803cc9,0x3f80bcc9,0x3ee6bf65,0xbee63f65,
0x3f800000,0x3f800000,0x3f623ef1,0x3f623ef1,0x3dfbbf7e,0xbdfb3f7e,0x3f13bf51,0xbf133f51,0xbf78be79,0xbf78be79,0xbf3ebf2c,0xbf3ebf2c,0xbeb83f6f,0x3eb8bf6f,0xbf423f27,0x3f42bf27,
0x3f800000,0x3f800000,0x3ef1bf62,0x3ef1bf62,0xbe89bf77,0x3e893f77,0xbf7abe60,0x3f7a3e60,0xbf5c3f04,0xbf5c3f04,0x3d493f80,0x3d493f80,0x3f393f31,0xbf39bf31,0x3f73bea1,0xbf733ea1,
0x3f800000,0x3f800000,0xbf62bef1,0xbf62bef1,0xbf1dbf4a,0x3f1d3f4a,0x3e2f3f7c,0xbe2fbf7c,0xbe793f78,0xbe793f78,0x3f2cbf3e,0x3f2cbf3e,0x3f6abecf,0xbf6a3ecf,0xbf7fbd97,0x3f7f3d97,
0x3f800000,0x3f800000,0xbef13f62,0xbef13f62,0xbf5fbefc,0x3f5f3efc,0x3f58bf09,0xbf583f09,0x3f043f5c,0x3f043f5c,0xbf803d49,0xbf803d49,0xbcc9bf80,0x3cc93f80,0x3f653ee6,0xbf65bee6,
0x3f800000,0x3f800000,0x3f623ef1,0x3f623ef1,0xbf7ebdfb,0x3f7e3dfb,0xbf51bf13,0x3f513f13,0x3f783e79,0x3f783e79,0x3f3e3f2c,0x3f3e3f2c,0xbf6fbeb8,0x3f6f3eb8,0xbf27bf42,0x3f273f42,
0xbf0ebf55,0xbf0ebf55,0xbf7f3dc9,0xbf7f3dc9,0xbf42bf27,0x3f423f27,0xbf6f3eb8,0x3f6fbeb8,0xbf67bedb,0xbf67bedb,0xbf4e3f18,0xbf4e3f18,0xbf7cbe2f,0x3f7c3e2f,0xbf1d3f4a,0x3f1dbf4a,
0x3f0e3f55,0x3f0e3f55,0xbdc9bf7f,0xbdc9bf7f,0x3f733ea1,0xbf73bea1,0xbf31bf39,0x3f313f39,0x3f71beac,0x3f71beac,0xbf7dbe16,0xbf7dbe16,0x3f09bf58,0xbf093f58,0xbf5f3efc,0x3f5fbefc,
0xbf0ebf55,0xbf0ebf55,0x3f7fbdc9,0x3f7fbdc9,0xbf7f3d97,0x3f7fbd97,0x3ecfbf6a,0xbecf3f6a,0xbedb3f67,0xbedb3f67,0xbf18bf4e,0xbf18bf4e,0x3f133f51,0xbf13bf51,0xbf7e3dfb,0x3f7ebdfb,
0x3f0e3f55,0x3f0e3f55,0x3dc93f7f,0x3dc93f7f,0x3f65bee6,0xbf653ee6,0x3f803cc9,0xbf80bcc9,0xbeacbf71,0xbeacbf71,0x3e16bf7d,0x3e16bf7d,0xbf7a3e60,0x3f7abe60,0xbf77be89,0x3f773e89,
0xbf0ebf55,0xbf0ebf55,0xbf7f3dc9,0xbf7f3dc9,0xbf273f42,0x3f27bf42,0x3eb83f6f,0xbeb8bf6f,0x3f673edb,0x3f673edb,0x3f4ebf18,0x3f4ebf18,0x3e2fbf7c,0xbe2f3f7c,0xbf4abf1d,0x3f4a3f1d,
0x3f0e3f55,0x3f0e3f55,0xbdc9bf7f,0xbdc9bf7f,0x3ea1bf73,0xbea13f73,0xbf393f31,0x3f39bf31,0xbf713eac,0xbf713eac,0x3f7d3e16,0x3f7d3e16,0x3f583f09,0xbf58bf09,0xbefcbf5f,0x3efc3f5f,
0xbf0ebf55,0xbf0ebf55,0x3f7fbdc9,0x3f7fbdc9,0x3d973f7f,0xbd97bf7f,0xbf6abecf,0x3f6a3ecf,0x3edbbf67,0x3edbbf67,0x3f183f4e,0x3f183f4e,0xbf513f13,0x3f51bf13,0xbdfbbf7e,0x3dfb3f7e,
0x3f0e3f55,0x3f0e3f55,0x3dc93f7f,0x3dc93f7f,0xbee6bf65,0x3ee63f65,0x3cc9bf80,0xbcc93f80,0x3eac3f71,0x3eac3f71,0xbe163f7d,0xbe163f7d,0xbe60bf7a,0x3e603f7a,0x3e89bf77,0xbe893f77,
0x3f803f80,0x3f0ebf0e,0x3f803f80,0x3f0ebf0e,0x3f803f80,0x3f0ebf0e,0x3f803f80,0x3f0ebf0e,0x3f803f80,0x3f0ebf0e,0x3f803f80,0x3f0ebf0e,0x3f803f80,0x3f0ebf0e,0x3f803f80,0x3f0ebf0e,
0x3f4a3f77,0x3f73bf42,0xbf4abf77,0xbf733f42,0x3dfb3efc,0x3f65bf7f,0xbdfbbefc,0xbf653f7f,0xbf1dbe89,0x3ea1bf27,0x3f1d3e89,0xbea13f27,0xbf7ebf5f,0xbee63d97,0x3f7e3f5f,0x3ee6bd97,
0x3e793f5c,0x3f71bf67,0x3e793f5c,0x3f71bf67,0xbf78bf04,0xbeacbedb,0xbf78bf04,0xbeacbedb,0xbe79bf5c,0xbf713f67,0xbe79bf5c,0xbf713f67,0x3f783f04,0x3eac3edb,0x3f783f04,0x3eac3edb,
0xbecf3f31,0x3f09bf7c,0x3ecfbf31,0xbf093f7c,0xbeb8bf80,0xbf7a3f13,0x3eb83f80,0x3f7abf13,0x3f6a3f39,0x3f583e2f,0xbf6abf39,0xbf58be2f,0xbf6fbcc9,0xbe60bf51,0x3f6f3cc9,0x3e603f51,
0xbf623ef1,0xbdc9bf7f,0xbf623ef1,0xbdc9bf7f,0x3f62bef1,0x3dc93f7f,0x3f62bef1,0x3dc93f7f,0xbf623ef1,0xbdc9bf7f,0xbf623ef1,0xbdc9bf7f,0x3f62bef1,0x3dc93f7f,0x3f62bef1,0x3dc93f7f,
0xbf7c3e60,0xbf31bf6f,0x3f7cbe60,0x3f313f6f,0x3f133f09,0x3f803ecf,0xbf13bf09,0xbf80becf,0x3e2fbf7a,0xbf393eb8,0xbe2f3f7a,0x3f39beb8,0xbf513f58,0x3cc9bf6a,0x3f51bf58,0xbcc93f6a,
0xbf2cbd49,0xbf7dbf4e,0xbf2cbd49,0xbf7dbf4e,0xbf3e3f80,0x3e16bf18,0xbf3e3f80,0x3e16bf18,0x3f2c3d49,0x3f7d3f4e,0x3f2c3d49,0x3f7d3f4e,0x3f3ebf80,0xbe163f18,0x3f3ebf80,0xbe163f18,
0xbd97bea1,0xbf5fbf1d,0x3d973ea1,0x3f5f3f1d,0xbf423ee6,0xbf77bf7e,0x3f42bee6,0x3f773f7e,0xbf7f3f73,0xbefcbf4a,0x3f7fbf73,0x3efc3f4a,0xbf273f65,0x3e89bdfb,0x3f27bf65,0xbe893dfb,
0,0xbf553f55,0,0xbf553f55,0,0xbf553f55,0,0xbf553f55,0,0xbf553f55,0,0xbf553f55,0,0xbf553f55,0,0xbf553f55,
0x3f1d3e89,0xbea13f27,0xbf1dbe89,0x3ea1bf27,0x3f7e3f5f,0x3ee6bd97,0xbf7ebf5f,0xbee63d97,0x3f4a3f77,0x3f73bf42,0xbf4abf77,0xbf733f42,0x3dfb3efc,0x3f65bf7f,0xbdfbbefc,0xbf653f7f,
0x3f783f04,0x3eac3edb,0x3f783f04,0x3eac3edb,0x3e793f5c,0x3f71bf67,0x3e793f5c,0x3f71bf67,0xbf78bf04,0xbeacbedb,0xbf78bf04,0xbeacbedb,0xbe79bf5c,0xbf713f67,0xbe79bf5c,0xbf713f67,
0x3f6a3f39,0x3f583e2f,0xbf6abf39,0xbf58be2f,0xbf6fbcc9,0xbe60bf51,0x3f6f3cc9,0x3e603f51,0x3ecfbf31,0xbf093f7c,0xbecf3f31,0x3f09bf7c,0x3eb83f80,0x3f7abf13,0xbeb8bf80,0xbf7a3f13,
0x3ef13f62,0x3f7fbdc9,0x3ef13f62,0x3f7fbdc9,0xbef1bf62,0xbf7f3dc9,0xbef1bf62,0xbf7f3dc9,0x3ef13f62,0x3f7fbdc9,0x3ef13f62,0x3f7fbdc9,0xbef1bf62,0xbf7f3dc9,0xbef1bf62,0xbf7f3dc9,
0xbe2f3f7a,0x3f39beb8,0x3e2fbf7a,0xbf393eb8,0x3f51bf58,0xbcc93f6a,0xbf513f58,0x3cc9bf6a,0xbf7c3e60,0xbf31bf6f,0x3f7cbe60,0x3f313f6f,0x3f133f09,0x3f803ecf,0xbf13bf09,0xbf80becf,
0xbf3e3f80,0x3e16bf18,0xbf3e3f80,0x3e16bf18,0x3f2c3d49,0x3f7d3f4e,0x3f2c3d49,0x3f7d3f4e,0x3f3ebf80,0xbe163f18,0x3f3ebf80,0xbe163f18,0xbf2cbd49,0xbf7dbf4e,0xbf2cbd49,0xbf7dbf4e,
0xbf7f3f73,0xbefcbf4a,0x3f7fbf73,0x3efc3f4a,0xbf273f65,0x3e89bdfb,0x3f27bf65,0xbe893dfb,0x3d973ea1,0x3f5f3f1d,0xbd97bea1,0xbf5fbf1d,0x3f42bee6,0x3f773f7e,0xbf423ee6,0xbf77bf7e,
0,0x3f55bf55,0,0x3f55bf55,0,0x3f55bf55,0,0x3f55bf55,0,0x3f55bf55,0,0x3f55bf55,0,0x3f55bf55,0,0x3f55bf55,
0xbf1dbe89,0x3ea1bf27,0x3f1d3e89,0xbea13f27,0xbf7ebf5f,0xbee63d97,0x3f7e3f5f,0x3ee6bd97,0xbf4abf77,0xbf733f42,0x3f4a3f77,0x3f73bf42,0xbdfbbefc,0xbf653f7f,0x3dfb3efc,0x3f65bf7f,
0xbf78bf04,0xbeacbedb,0xbf78bf04,0xbeacbedb,0xbe79bf5c,0xbf713f67,0xbe79bf5c,0xbf713f67,0x3f783f04,0x3eac3edb,0x3f783f04,0x3eac3edb,0x3e793f5c,0x3f71bf67,0x3e793f5c,0x3f71bf67,
0xbf6abf39,0xbf58be2f,0x3f6a3f39,0x3f583e2f,0x3f6f3cc9,0x3e603f51,0xbf6fbcc9,0xbe60bf51,0xbecf3f31,0x3f09bf7c,0x3ecfbf31,0xbf093f7c,0xbeb8bf80,0xbf7a3f13,0x3eb83f80,0x3f7abf13,
0xbef1bf62,0xbf7f3dc9,0xbef1bf62,0xbf7f3dc9,0x3ef13f62,0x3f7fbdc9,0x3ef13f62,0x3f7fbdc9,0xbef1bf62,0xbf7f3dc9,0xbef1bf62,0xbf7f3dc9,0x3ef13f62,0x3f7fbdc9,0x3ef13f62,0x3f7fbdc9,
0x3e2fbf7a,0xbf393eb8,0xbe2f3f7a,0x3f39beb8,0xbf513f58,0x3cc9bf6a,0x3f51bf58,0xbcc93f6a,0x3f7cbe60,0x3f313f6f,0xbf7c3e60,0xbf31bf6f,0xbf13bf09,0xbf80becf,0x3f133f09,0x3f803ecf,
0x3f3ebf80,0xbe163f18,0x3f3ebf80,0xbe163f18,0xbf2cbd49,0xbf7dbf4e,0xbf2cbd49,0xbf7dbf4e,0xbf3e3f80,0x3e16bf18,0xbf3e3f80,0x3e16bf18,0x3f2c3d49,0x3f7d3f4e,0x3f2c3d49,0x3f7d3f4e,
0x3f7fbf73,0x3efc3f4a,0xbf7f3f73,0xbefcbf4a,0x3f27bf65,0xbe893dfb,0xbf273f65,0x3e89bdfb,0xbd97bea1,0xbf5fbf1d,0x3d973ea1,0x3f5f3f1d,0xbf423ee6,0xbf77bf7e,0x3f42bee6,0x3f773f7e,
0x3f800000,0x3f7fdaaf,0x3f800000,0x3f6912ae,0x3f7f6ac7,0x3f7eb069,0x3f286605,0x3e931f35,0x3f7dabcc,0x3f7c5d3a,0xbe09cf86,0xbf084b92,0x3f7ac516,0x3f78e3d6,0xbf55b993,0xbf7cdf6c,
0x3f800000,0x3f7f1f49,0x3f800000,0x3f6398ac,0x3f7c7eb0,0x3f7822d1,0x3f14b039,0x3e1324ca,0x3f721352,0x3f6a5ad9,0xbea68f12,0xbf38dd65,0x3f6106f2,0x3f5627fe,0xbf756d97,0xbf7b87b2,
0x3f800000,0x3f7dc68c,0x3f800000,0x3f5d924d,0x3f772417,0x3f6c3624,0x3eff17b2,0xbb490fc6,0x3f5d2d53,0x3f4a4c87,0xbf00e7e4,0xbf5e5aa6,0x3f33e7bc,0x3f1a6293,0xbf7ffec4,0xbf5cc7d1,
0x3f800000,0x3f7bd14d,0x3f800000,0x3f570348,0x3f6f6830,0x3f5b2c79,0x3ed25a09,0xbe195be0,0x3f3fc767,0x3f1e1e22,0xbf299415,0xbf76841b,0x3eee9479,0x3e9920fe,0xbf748422,0xbf24381a,
0x3f800000,0x3f7940c0,0x3f800000,0x3f4fefa8,0x3f655e0b,0x3f456439,0x3ea395c5,0xbe9620d2,0x3f1b02c6,0x3ed0eb2a,0xbf4bbbf8,0xbf7fe705,0x3e419b37,0xbd2351cb,0xbf53fac3,0xbeb0eacb,
0x3f800000,0x3f76167a,0x3f800000,0x3f485bca,0x3f591e6a,0x3f2b561b,0x3e667c66,0xbedc53c1,0x3ee0924f,0x3e3228d4,0xbf660f88,0xbf79f35e,0xbdd53db9,0xbebf926f,0xbf212ff9,0xbc16cb58,
0x3f800000,0x3f725470,0x3f800000,0x3f404c5c,0x3f4ac77f,0x3f0d9281,0x3e039502,0xbf0ee0db,0x3e827dc0,0xbd9064b4,0xbf778bc5,0xbf650479,0xbec6d529,0xbf2a2a80,0xbec1071e,0x3ea80b1f,
0x3f800000,0x3f6dfcf2,0x3f800000,0x3f37c655,0x3f3a7ca4,0x3ed97cb9,0x3cfb49ba,0xbf2c800f,0x3d7b2b74,0xbe9f1cdf,0xbf7f84ab,0xbf425b89,0xbf239da9,0xbf60a6cf,0xbdbc3ac3,0x3f209393,
0,0x3d0a342f,0,0x3ed3c867,0x3d8a200a,0x3dcefdb7,0x3f40d0da,0x3f75341d,0x3e09cf86,0x3e2bf804,0x3f7dabcc,0x3f58b3a1,0x3e4dee60,0x3e6fa8b2,0x3f0cead0,0x3e1f917b,
0,0x3da973ba,0,0x3eea6681,0x3e28defc,0x3e7bdba4,0x3f5064af,0x3f7d57de,0x3ea68f12,0x3ece0bea,0x3f721352,0x3f311722,0x3ef41f07,0x3f0c42c9,0x3e919ddd,0xbe3e853e,
0,0x3e06b26e,0,0x3f003a06,0x3e8586ce,0x3ec5625c,0x3f5df6be,0x3f7fffb1,0x3f00e7e4,0x3f1ce11f,0x3f5d2d53,0x3efdbabb,0x3f36206c,0x3f4c3578,0xbbc90f88,0xbf019573,
0,0x3e3857ec,0,0x3f0af1b7,0x3eb554ec,0x3f044889,0x3f696591,0x3f7d1cdd,0x3f299415,0x3f495521,0x3f3fc767,0x3e8a11f7,0x3f628210,0x3f74484b,0xbe97a117,0xbf446337,
0,0x3e698bba,0,0x3f1553b7,0x3ee363fa,0x3f2302d3,0x3f7294f8,0x3f74bf62,0x3f4bbbf8,0x3f69b7e4,0x3f1b02c6,0x3ce22a7a,0x3f7b61fc,0x3f7fcbe2,0xbf0f8784,0xbf703b37,
0,0x3e8d17c0,0,0x3f1f599f,0x3f07a136,0x3f3e35c5,0x3f796e4e,0x3f671599,0x3f660f88,0x3f7c187a,0x3ee0924f,0xbe5d4b1a,0x3f7e9bc9,0x3f6d67a1,0xbf46e22a,0xbf7ffd39,
0,0x3ea5129f,0,0x3f28fd41,0x3f1c420c,0x3f554aa4,0x3f7de0b1,0x3f546b3b,0x3f778bc5,0x3f7f5ce9,0x3e827dc0,0xbee4cbfe,0x3f6be858,0x3f3f41fc,0xbf6d1c1d,0xbf71d19f,
0,0x3ebca7af,0,0x3f3238aa,0x3f2f61a5,0x3f67c187,0x3f7fe129,0x3f3d27b8,0x3f7f84ab,0x3f73530e,0x3d7b2b74,0xbf269de3,0x3f44e3f5,0x3ef58035,0xbf7eea9d,0xbf476085,
0x354ccccd,0x354ccccd,0x354ccccd,0x354ccccd,0x354ccccd,0x354ccccd,0x354ccccd,0x354ccccd,0x354ccccd,0x354ccccd,0x354ccccd,0x354ccccd,0x354ccccd,0x354ccccd,0x354ccccd,0x354ccccd,
0x354aefd6,0x3541a90f,0xb3dc7f3e,0xb4853f42,0x3530f10f,0x35196c52,0xb4ce3fd4,0xb507a9aa,0x34f8046f,0x34b3a83f,0xb522fcc6,0xb5380c6c,0x3450c934,0x3348ef90,0xb546096a,0xb54c6a23,
0x354caef3,0x354c1907,0x353a7558,0x353613bd,0x354b053d,0x3549743e,0x353141d7,0x352c02a0,0x35476700,0x3544dec8,0x35265953,0x3520496e,0x3541dd26,0x353e63f5,0x3519d6b0,0x35130511,
0x3549e42e,0x353b7be1,0xb4da1284,0xb513e451,0x3521d6d2,0x34fcfd04,0xb531e21f,0xb545367c,0x34a72288,0x340e8710,0xb54cb8d1,0xb547f5e5,0xb3670786,0xb47e9498,0xb53736c7,0xb51b7c6d,
0x354c556c,0x3549fef3,0x3506b804,0x34ede6c2,0x3545b679,0x353f868d,0x34cc12f5,0x34a84807,0x35377e6f,0x352db1ef,0x3482de37,0x34386384,0x35223933,0x35153084,0x33d28804,0x32c907c8,
0x35489dab,0x3534058e,0xb52afadc,0xb54457ac,0x350fec97,0x34bedd2d,0xb54ccbd0,0xb5439ce8,0x341ae293,0xb3aa97c7,0xb5299568,0xb500f32d,0xb49f10ee,0xb502e487,0xb49a6c18,0xb3969569,
0x354bc054,0x35468241,0x346b6521,0x33eb6e11,0x353cf81d,0x352f56c7,0xb120d96b,0xb3f55fcc,0x351de9c7,0x350911af,0xb4703484,0xb4b04301,0x34e28401,0x34adfd61,0xb4e49af8,0xb50a000c,
0x35471cab,0x352b5332,0xb54a4c56,0xb549395b,0x34f7041e,0x34750196,0xb5309fda,0xb5036014,0xb302a7d6,0xb49941f2,0xb48d88a2,0xb1f1455a,0xb5082200,0xb533b8a6,0x34866f4c,0x3500760f,
0,0,0,0,0,0,0,0,0,0,0,0,0,0,0,0,
0x33dc7f3e,0x34853f42,0x354aefd6,0x3541a90f,0x34ce3fd4,0x3507a9aa,0x3530f10f,0x35196c52,0x3522fcc6,0x35380c6c,0x34f8046f,0x34b3a83f,0x3546096a,0x354c6a23,0x3450c934,0x3348ef90,
0x32dd204b,0x33878fc8,0x34a96d1f,0x34bb8534,0x33d783e3,0x3413798a,0x34cd29a4,0x34de4f8b,0x343ad62f,0x3461bf99,0x34eeec58,0x34fef5cc,0x34840ee5,0x3496ec8c,0x35073101,0x350e93bb,
0x34099337,0x34a4d655,0x352d5c81,0x350dac1c,0x34fb01cb,0x352110e7,0x34cafbc9,0x345ce98c,0x353af983,0x3549ad2f,0x32b4eec8,0xb43108e1,0x354c4a54,0x3542a8d8,0xb4b70998,0xb5054b1c,
0x335d000f,0x340718ca,0x351a40ae,0x3526b6f3,0x3455a47e,0x349110bd,0x35319232,0x353ab7a7,0x34b5e995,0x34d901f0,0x354210c7,0x35478b72,0x34fa0347,0x350c4e1d,0x354b1a27,0x354cb421,
0x3424beb3,0x34c34c06,0x34e177b4,0x3468fc95,0x3511b389,0x353534da,0xb1a0d93a,0xb4729b58,0x35491b30,0x354bafd4,0xb4e5a5a1,0xb51f1b54,0x353cb9e0,0x351d832a,0xb53db017,0xb54beee4,
0x33a597c6,0x34497c83,0x354429b0,0x354aacb2,0x349de84a,0x34d3a742,0x354ccc8e,0x354a7d7e,0x350268a9,0x35182b04,0x3543cc4e,0x3538de14,0x352aa21d,0x3539679f,0x3529ef63,0x351752fa,
0x343fba28,0x34e06adb,0x33ff4f2b,0xb4186a98,0x35235df9,0x35436d09,0xb4cf5584,0xb51d1c2c,0x354ca31b,0x353dec81,0xb5402f5f,0xb54cca94,0x35190197,0x34c46691,0xb5417480,0xb51f806a,
0x3f80,0x3f80,0x3f6d3ec4,0x3f6d3ec4,0x3e953f75,0xbe95bf75,0x3f7f3dc9,0xbf7fbdc9,0x3f0e3f55,0x3f0e3f55,0x3f7bbe48,0x3f7bbe48,0x3f463f22,0xbf46bf22,0x3f62bef1,0xbf623ef1,
0x3f80,0x3f80,0x3ec4bf6d,0x3ec4bf6d,0x3f223f46,0xbf22bf46,0xbe95bf75,0x3e953f75,0x3f7b3e48,0x3f7b3e48,0xbf55bf0e,0xbf55bf0e,0x3f62bef1,0xbf623ef1,0xbf7f3dc9,0x3f7fbdc9,
0x3f80,0x3f80,0xbf6dbec4,0xbf6dbec4,0x3f623ef1,0xbf62bef1,0xbf463f22,0x3f46bf22,0x3f55bf0e,0x3f55bf0e,0x3e483f7b,0x3e483f7b,0xbdc9bf7f,0x3dc93f7f,0x3f753e95,0xbf75be95,
0x3f80,0x3f80,0xbec43f6d,0xbec43f6d,0x3f7f3dc9,0xbf7fbdc9,0x3f623ef1,0xbf62bef1,0x3e48bf7b,0x3e48bf7b,0x3f0ebf55,0x3f0ebf55,0xbf75be95,0x3f753e95,0xbf46bf22,0x3f463f22,
0x3f80,0x3f80,0x3f6d3ec4,0x3f6d3ec4,0x3f75be95,0xbf753e95,0x3dc9bf7f,0xbdc93f7f,0xbf0ebf55,0xbf0ebf55,0xbf7b3e48,0xbf7b3e48,0xbf223f46,0x3f22bf46,0x3ef13f62,0xbef1bf62,
0x3f80,0x3f80,0x3ec4bf6d,0x3ec4bf6d,0x3f46bf22,0xbf463f22,0xbf753e95,0x3f75be95,0xbf7bbe48,0xbf7bbe48,0x3f553f0e,0x3f553f0e,0x3ef13f62,0xbef1bf62,0xbdc9bf7f,0x3dc93f7f,
0x3f80,0x3f80,0xbf6dbec4,0xbf6dbec4,0x3ef1bf62,0xbef13f62,0x3f223f46,0xbf22bf46,0xbf553f0e,0xbf553f0e,0xbe48bf7b,0xbe48bf7b,0x3f7fbdc9,0xbf7f3dc9,0xbe953f75,0x3e95bf75,
0x3f80,0x3f80,0xbec43f6d,0xbec43f6d,0x3dc9bf7f,0xbdc93f7f,0x3ef1bf62,0xbef13f62,0xbe483f7b,0xbe483f7b,0xbf0e3f55,0xbf0e3f55,0x3e95bf75,0xbe953f75,0x3f22bf46,0xbf223f46,
0x3f35bf35,0x3f35bf35,0xbec4bf6d,0xbec4bf6d,0x3ef1bf62,0xbef13f62,0xbf22bf46,0x3f223f46,0x3e48bf7b,0x3e48bf7b,0xbf55bf0e,0xbf55bf0e,0xbdc9bf7f,0x3dc93f7f,0xbf75be95,0x3f753e95,
0xbf353f35,0xbf353f35,0x3f6dbec4,0x3f6dbec4,0xbdc93f7f,0x3dc9bf7f,0x3ef1bf62,0xbef13f62,0x3f0e3f55,0x3f0e3f55,0xbe48bf7b,0xbe48bf7b,0x3f753e95,0xbf75be95,0xbf46bf22,0x3f463f22,
0x3f35bf35,0x3f35bf35,0x3ec43f6d,0x3ec43f6d,0xbe95bf75,0x3e953f75,0x3f7f3dc9,0xbf7fbdc9,0xbf7bbe48,0xbf7bbe48,0x3f0ebf55,0x3f0ebf55,0xbf223f46,0x3f22bf46,0xbef1bf62,0x3ef13f62,
0xbf353f35,0xbf353f35,0xbf6d3ec4,0xbf6d3ec4,0x3f223f46,0xbf22bf46,0x3e953f75,0xbe95bf75,0x3f55bf0e,0x3f55bf0e,0x3f7bbe48,0x3f7bbe48,0xbef1bf62,0x3ef13f62,0xbdc9bf7f,0x3dc93f7f,
0x3f35bf35,0x3f35bf35,0xbec4bf6d,0xbec4bf6d,0xbf62bef1,0x3f623ef1,0xbf463f22,0x3f46bf22,0xbe483f7b,0xbe483f7b,0x3f553f0e,0x3f553f0e,0x3f7fbdc9,0xbf7f3dc9,0x3e95bf75,0xbe953f75,
0xbf353f35,0xbf353f35,0x3f6dbec4,0x3f6dbec4,0x3f7f3dc9,0xbf7fbdc9,0xbf62bef1,0x3f623ef1,0xbf0ebf55,0xbf0ebf55,0x3e483f7b,0x3e483f7b,0xbe953f75,0x3e95bf75,0x3f22bf46,0xbf223f46,
0x3f35bf35,0x3f35bf35,0x3ec43f6d,0x3ec43f6d,0xbf753e95,0x3f75be95,0x3dc9bf7f,0xbdc93f7f,0x3f7b3e48,0x3f7b3e48,0xbf0e3f55,0xbf0e3f55,0xbf46bf22,0x3f463f22,0x3f62bef1,0xbf623ef1,
0xbf353f35,0xbf353f35,0xbf6d3ec4,0xbf6d3ec4,0x3f46bf22,0xbf463f22,0x3f75be95,0xbf753e95,0xbf553f0e,0xbf553f0e,0xbf7b3e48,0xbf7b3e48,0x3f62bef1,0xbf623ef1,0x3f7fbdc9,0xbf7f3dc9,
0x3f800000,0x3f800000,0x3ec4bf6d,0x3ec4bf6d,0x3f75be95,0xbf753e95,0x3dc9bf7f,0xbdc93f7f,0x3f55bf0e,0x3f55bf0e,0xbe48bf7b,0xbe48bf7b,0x3f22bf46,0xbf223f46,0xbef1bf62,0x3ef13f62,
0x3f800000,0x3f800000,0xbf6dbec4,0xbf6dbec4,0x3f46bf22,0xbf463f22,0xbf753e95,0x3f75be95,0x3e48bf7b,0x3e48bf7b,0xbf0e3f55,0xbf0e3f55,0xbef1bf62,0x3ef13f62,0x3dc93f7f,0xbdc9bf7f,
0x3f800000,0x3f800000,0xbec43f6d,0xbec43f6d,0x3ef1bf62,0xbef13f62,0x3f223f46,0xbf22bf46,0xbf0ebf55,0xbf0ebf55,0x3f7bbe48,0x3f7bbe48,0xbf7f3dc9,0x3f7fbdc9,0x3e95bf75,0xbe953f75,
0x3f800000,0x3f800000,0x3f6d3ec4,0x3f6d3ec4,0x3dc9bf7f,0xbdc93f7f,0x3ef1bf62,0xbef13f62,0xbf7bbe48,0xbf7bbe48,0xbf55bf0e,0xbf55bf0e,0xbe953f75,0x3e95bf75,0xbf223f46,0x3f22bf46,
0x3f800000,0x3f800000,0x3ec4bf6d,0x3ec4bf6d,0xbe95bf75,0x3e953f75,0xbf7fbdc9,0x3f7f3dc9,0xbf553f0e,0xbf553f0e,0x3e483f7b,0x3e483f7b,0x3f463f22,0xbf46bf22,0x3f62bef1,0xbf623ef1,
0x3f800000,0x3f800000,0xbf6dbec4,0xbf6dbec4,0xbf22bf46,0x3f223f46,0x3e953f75,0xbe95bf75,0xbe483f7b,0xbe483f7b,0x3f0ebf55,0x3f0ebf55,0x3f62bef1,0xbf623ef1,0xbf7f3dc9,0x3f7fbdc9,
0x3f800000,0x3f800000,0xbec43f6d,0xbec43f6d,0xbf62bef1,0x3f623ef1,0x3f46bf22,0xbf463f22,0x3f0e3f55,0x3f0e3f55,0xbf7b3e48,0xbf7b3e48,0xbdc9bf7f,0x3dc93f7f,0x3f753e95,0xbf75be95,
0x3f800000,0x3f800000,0x3f6d3ec4,0x3f6d3ec4,0xbf7fbdc9,0x3f7f3dc9,0xbf62bef1,0x3f623ef1,0x3f7b3e48,0x3f7b3e48,0x3f553f0e,0x3f553f0e,0xbf75be95,0x3f753e95,0xbf46bf22,0x3f463f22,
0xbf35bf35,0xbf35bf35,0xbf6d3ec4,0xbf6d3ec4,0xbf62bef1,0x3f623ef1,0xbf463f22,0x3f46bf22,0xbf7bbe48,0xbf7bbe48,0xbf0e3f55,0xbf0e3f55,0xbf7f3dc9,0x3f7fbdc9,0xbe953f75,0x3e95bf75,
0x3f353f35,0x3f353f35,0xbec4bf6d,0xbec4bf6d,0x3f7f3dc9,0xbf7fbdc9,0xbf62bef1,0x3f623ef1,0x3f55bf0e,0x3f55bf0e,0xbf7b3e48,0xbf7b3e48,0x3e95bf75,0xbe953f75,0xbf223f46,0x3f22bf46,
0xbf35bf35,0xbf35bf35,0x3f6dbec4,0x3f6dbec4,0xbf753e95,0x3f75be95,0x3dc9bf7f,0xbdc93f7f,0xbe483f7b,0xbe483f7b,0xbf55bf0e,0xbf55bf0e,0x3f463f22,0xbf46bf22,0xbf623ef1,0x3f62bef1,
0x3f353f35,0x3f353f35,0x3ec43f6d,0x3ec43f6d,0x3f46bf22,0xbf463f22,0x3f75be95,0xbf753e95,0xbf0ebf55,0xbf0ebf55,0xbe48bf7b,0xbe48bf7b,0xbf623ef1,0x3f62bef1,0xbf7f3dc9,0x3f7fbdc9,
0xbf35bf35,0xbf35bf35,0xbf6d3ec4,0xbf6d3ec4,0xbef13f62,0x3ef1bf62,0x3f223f46,0xbf22bf46,0x3f7b3e48,0x3f7b3e48,0x3f0ebf55,0x3f0ebf55,0xbdc9bf7f,0x3dc93f7f,0xbf75be95,0x3f753e95,
0x3f353f35,0x3f353f35,0xbec4bf6d,0xbec4bf6d,0x3dc9bf7f,0xbdc93f7f,0xbef13f62,0x3ef1bf62,0xbf553f0e,0xbf553f0e,0x3f7bbe48,0x3f7bbe48,0x3f753e95,0xbf75be95,0xbf46bf22,0x3f463f22,
0xbf35bf35,0xbf35bf35,0x3f6dbec4,0x3f6dbec4,0x3e953f75,0xbe95bf75,0xbf7fbdc9,0x3f7f3dc9,0x3e48bf7b,0x3e48bf7b,0x3f553f0e,0x3f553f0e,0xbf223f46,0x3f22bf46,0xbef1bf62,0x3ef13f62,
0x3f353f35,0x3f353f35,0x3ec43f6d,0x3ec43f6d,0xbf22bf46,0x3f223f46,0xbe95bf75,0x3e953f75,0x3f0e3f55,0x3f0e3f55,0x3e483f7b,0x3e483f7b,0xbef1bf62,0x3ef13f62,0xbdc9bf7f,0x3dc93f7f,
0x3f803f80,0x3f35bf35,0x3f803f80,0x3f35bf35,0x3f803f80,0x3f35bf35,0x3f803f80,0x3f35bf35,0x3f803f80,0x3f35bf35,0x3f803f80,0x3f35bf35,0x3f803f80,0x3f35bf35,0x3f803f80,0x3f35bf35,
0x3f463f75,0x3f7fbf62,0xbf46bf75,0xbf7f3f62,0x3dc93ef1,0x3f46bf75,0xbdc9bef1,0xbf463f75,0xbf22be95,0x3dc9bef1,0x3f223e95,0xbdc93ef1,0xbf7fbf62,0xbf223e95,0x3f7f3f62,0x3f22be95,
0x3e483f55,0x3f55bf7b,0x3e483f55,0x3f55bf7b,0xbf7bbf0e,0xbf0ebe48,0xbf7bbf0e,0xbf0ebe48,0xbe48bf55,0xbf553f7b,0xbe48bf55,0xbf553f7b,0x3f7b3f0e,0x3f0e3e48,0x3f7b3f0e,0x3f0e3e48,
0xbef13f22,0x3e95bf7f,0x3ef1bf22,0xbe953f7f,0xbe95bf7f,0xbf623f46,0x3e953f7f,0x3f62bf46,0x3f623f46,0x3f75bdc9,0xbf62bf46,0xbf753dc9,0xbf75bdc9,0xbef1bf22,0x3f753dc9,0x3ef13f22,
0xbf6d3ec4,0xbec4bf6d,0xbf6d3ec4,0xbec4bf6d,0x3f6dbec4,0x3ec43f6d,0x3f6dbec4,0x3ec43f6d,0xbf6d3ec4,0xbec4bf6d,0xbf6d3ec4,0xbec4bf6d,0x3f6dbec4,0x3ec43f6d,0x3f6dbec4,0x3ec43f6d,
0xbf753dc9,0xbf62bf46,0x3f75bdc9,0x3f623f46,0x3ef13f22,0x3f753dc9,0xbef1bf22,0xbf75bdc9,0x3e95bf7f,0xbef13f22,0xbe953f7f,0x3ef1bf22,0xbf623f46,0xbe95bf7f,0x3f62bf46,0x3e953f7f,
0xbf0ebe48,0xbf7bbf0e,0xbf0ebe48,0xbf7bbf0e,0xbf553f7b,0xbe48bf55,0xbf553f7b,0xbe48bf55,0x3f0e3e48,0x3f7b3f0e,0x3f0e3e48,0x3f7b3f0e,0x3f55bf7b,0x3e483f55,0x3f55bf7b,0x3e483f55,
0x3dc9bef1,0xbf22be95,0xbdc93ef1,0x3f223e95,0xbf223e95,0xbf7fbf62,0x3f22be95,0x3f7f3f62,0xbf7f3f62,0xbf46bf75,0x3f7fbf62,0x3f463f75,0xbf463f75,0xbdc9bef1,0x3f46bf75,0x3dc93ef1,
0,0xbf353f35,0,0xbf353f35,0,0xbf353f35,0,0xbf353f35,0,0xbf353f35,0,0xbf353f35,0,0xbf353f35,0,0xbf353f35,
0x3f223e95,0xbdc93ef1,0xbf22be95,0x3dc9bef1,0x3f7f3f62,0x3f22be95,0xbf7fbf62,0xbf223e95,0x3f463f75,0x3f7fbf62,0xbf46bf75,0xbf7f3f62,0x3dc93ef1,0x3f46bf75,0xbdc9bef1,0xbf463f75,
0x3f7b3f0e,0x3f0e3e48,0x3f7b3f0e,0x3f0e3e48,0x3e483f55,0x3f55bf7b,0x3e483f55,0x3f55bf7b,0xbf7bbf0e,0xbf0ebe48,0xbf7bbf0e,0xbf0ebe48,0xbe48bf55,0xbf553f7b,0xbe48bf55,0xbf553f7b,
0x3f623f46,0x3f75bdc9,0xbf62bf46,0xbf753dc9,0xbf75bdc9,0xbef1bf22,0x3f753dc9,0x3ef13f22,0x3ef1bf22,0xbe953f7f,0xbef13f22,0x3e95bf7f,0x3e953f7f,0x3f62bf46,0xbe95bf7f,0xbf623f46,
0x3ec43f6d,0x3f6dbec4,0x3ec43f6d,0x3f6dbec4,0xbec4bf6d,0xbf6d3ec4,0xbec4bf6d,0xbf6d3ec4,0x3ec43f6d,0x3f6dbec4,0x3ec43f6d,0x3f6dbec4,0xbec4bf6d,0xbf6d3ec4,0xbec4bf6d,0xbf6d3ec4,
0xbe953f7f,0x3ef1bf22,0x3e95bf7f,0xbef13f22,0x3f62bf46,0x3e953f7f,0xbf623f46,0xbe95bf7f,0xbf753dc9,0xbf62bf46,0x3f75bdc9,0x3f623f46,0x3ef13f22,0x3f753dc9,0xbef1bf22,0xbf75bdc9,
0xbf553f7b,0xbe48bf55,0xbf553f7b,0xbe48bf55,0x3f0e3e48,0x3f7b3f0e,0x3f0e3e48,0x3f7b3f0e,0x3f55bf7b,0x3e483f55,0x3f55bf7b,0x3e483f55,0xbf0ebe48,0xbf7bbf0e,0xbf0ebe48,0xbf7bbf0e,
0xbf7f3f62,0xbf46bf75,0x3f7fbf62,0x3f463f75,0xbf463f75,0xbdc9bef1,0x3f46bf75,0x3dc93ef1,0xbdc93ef1,0x3f223e95,0x3dc9bef1,0xbf22be95,0x3f22be95,0x3f7f3f62,0xbf223e95,0xbf7fbf62,
0,0x3f35bf35,0,0x3f35bf35,0,0x3f35bf35,0,0x3f35bf35,0,0x3f35bf35,0,0x3f35bf35,0,0x3f35bf35,0,0x3f35bf35,
0xbf22be95,0x3dc9bef1,0x3f223e95,0xbdc93ef1,0xbf7fbf62,0xbf223e95,0x3f7f3f62,0x3f22be95,0xbf46bf75,0xbf7f3f62,0x3f463f75,0x3f7fbf62,0xbdc9bef1,0xbf463f75,0x3dc93ef1,0x3f46bf75,
0xbf7bbf0e,0xbf0ebe48,0xbf7bbf0e,0xbf0ebe48,0xbe48bf55,0xbf553f7b,0xbe48bf55,0xbf553f7b,0x3f7b3f0e,0x3f0e3e48,0x3f7b3f0e,0x3f0e3e48,0x3e483f55,0x3f55bf7b,0x3e483f55,0x3f55bf7b,
0xbf62bf46,0xbf753dc9,0x3f623f46,0x3f75bdc9,0x3f753dc9,0x3ef13f22,0xbf75bdc9,0xbef1bf22,0xbef13f22,0x3e95bf7f,0x3ef1bf22,0xbe953f7f,0xbe95bf7f,0xbf623f46,0x3e953f7f,0x3f62bf46,
0xbec4bf6d,0xbf6d3ec4,0xbec4bf6d,0xbf6d3ec4,0x3ec43f6d,0x3f6dbec4,0x3ec43f6d,0x3f6dbec4,0xbec4bf6d,0xbf6d3ec4,0xbec4bf6d,0xbf6d3ec4,0x3ec43f6d,0x3f6dbec4,0x3ec43f6d,0x3f6dbec4,
0x3e95bf7f,0xbef13f22,0xbe953f7f,0x3ef1bf22,0xbf623f46,0xbe95bf7f,0x3f62bf46,0x3e953f7f,0x3f75bdc9,0x3f623f46,0xbf753dc9,0xbf62bf46,0xbef1bf22,0xbf75bdc9,0x3ef13f22,0x3f753dc9,
0x3f55bf7b,0x3e483f55,0x3f55bf7b,0x3e483f55,0xbf0ebe48,0xbf7bbf0e,0xbf0ebe48,0xbf7bbf0e,0xbf553f7b,0xbe48bf55,0xbf553f7b,0xbe48bf55,0x3f0e3e48,0x3f7b3f0e,0x3f0e3e48,0x3f7b3f0e,
0x3f7fbf62,0x3f463f75,0xbf7f3f62,0xbf46bf75,0x3f46bf75,0x3dc93ef1,0xbf463f75,0xbdc9bef1,0x3dc9bef1,0xbf22be95,0xbdc93ef1,0x3f223e95,0xbf223e95,0xbf7fbf62,0x3f22be95,0x3f7f3f62,
0x3f800000,0x3f7fd397,0x3f800000,0x3f68bf3c,0x3f7f4e6d,0x3f7e70b0,0x3f273656,0x3e8e9a22,0x3f7d3aac,0x3f7baccd,0xbe164083,0xbf0b9a6b,0x3f79c79d,0x3f778bc5,0xbf584853,0xbf7dabcc,
0x3f800000,0x3f7f0e58,0x3f800000,0x3f633c5a,0x3f7c3b28,0x3f778bc5,0x3f13682a,0x3e09cf86,0x3f710908,0x3f68bf3c,0xbeac7cd4,0xbf3b8f3b,0x3f5ebe05,0x3f531849,0xbf76ba07,0xbf7a7302,
0x3f800000,0x3f7dabcc,0x3f800000,0x3f5d2d53,0x3f76ba07,0x3f6b4b0c,0x3efc5d27,0xbc490e90,0x3f5b941a,0x3f47de65,0xbf039c3d,0xbf604621,0x3f3085bb,0x3f15f6d9,0xbf7fec43,0xbf59f26a,
0x3f800000,0x3f7baccd,0x3f800000,0x3f5695e5,0x3f6ed89e,0x3f59f26a,0x3ecf7bca,0xbe22abb6,0x3f3daef9,0x3f1b02c6,0xbf2beb4a,0xbf778bc5,0x3ee63375,0x3e8e9a22,0xbf731447,0xbf1ff6cb,
0x3f800000,0x3f791298,0x3f800000,0x3f4f7a1f,0x3f64aa59,0x3f43e200,0x3ea09ae5,0xbe9aa086,0x3f187fc0,0x3ec9b953,0xbf4d9f02,0xbf7ffb11,0x3e2f10a2,0xbd7b2b74,0xbf514d3d,0xbea68f12,
0x3f800000,0x3f75dec6,0x3f800000,0x3f47de65,0x3f584853,0x3f299415,0x3e605c13,0xbee0924f,0x3edae880,0x3e22abb6,0xbf676bd8,0xbf791298,0xbdfab273,0xbec9b953,0xbf1d7fd1,0x3c490e90,
0x3f800000,0x3f721352,0x3f800000,0x3f3fc767,0x3f49d112,0x3f0b9a6b,0x3dfab273,0xbf10d3cd,0x3e78cfcc,0xbdafb680,0xbf7853f8,0xbf633c5a,0xbecf7bca,0xbf2e3bde,0xbeb8442a,0x3eb263ef,
0x3f800000,0x3f6db293,0x3f800000,0x3f373a23,0x3f396842,0x3ed53641,0x3cc90ab0,0xbf2e3bde,0x3d48fb30,0xbea68f12,0xbf7fb10f,0xbf3fc767,0xbf273656,0xbf633c5a,0xbd96a905,0x3f24d225,
0,0x3d16c32c,0,0x3ed53641,0x3d96a905,0x3de1bc2e,0x3f41d870,0x3f75dec6,0x3e164083,0x3e3b6ecf,0x3f7d3aac,0x3f5695e5,0x3e605c13,0x3e827dc0,0x3f08f59b,0x3e09cf86,
0,0x3dafb680,0,0x3eebcbbb,0x3e2f10a2,0x3e827dc0,0x3f514d3d,0x3f7dabcc,0x3eac7cd4,0x3ed53641,0x3f710908,0x3f2e3bde,0x3efc5d27,0x3f10d3cd,0x3e888e93,0xbe541501,
0,0x3e09cf86,0,0x3f00e7e4,0x3e888e93,0x3ec9b953,0x3f5ebe05,0x3f7ffb11,0x3f039c3d,0x3f1ff6cb,0x3f5b941a,0x3ef6e0cb,0x3f396842,0x3f4f7a1f,0xbcc90ab0,0xbf064b82,
0,0x3e3b6ecf,0,0x3f0b9a6b,0x3eb8442a,0x3f064b82,0x3f6a09a7,0x3f7cbfc9,0x3f2beb4a,0x3f4bbbf8,0x3f3daef9,0x3e827dc0,0x3f64aa59,0x3f75dec6,0xbea09ae5,0xbf47de65,
0,0x3e6c9a7f,0,0x3f15f6d9,0x3ee63375,0x3f24d225,0x3f731447,0x3f740bdd,0x3f4d9f02,0x3f6b4b0c,0x3f187fc0,0x3c490e90,0x3f7c3b28,0x3f7f84ab,0xbf13682a,0xbf721352,
0,0x3e8e9a22,0,0x3f1ff6cb,0x3f08f59b,0x3f3fc767,0x3f79c79d,0x3f660f88,0x3f676bd8,0x3f7cbfc9,0x3edae880,0xbe6c9a7f,0x3f7e1324,0x3f6b4b0c,0xbf49d112,0xbf7ffb11,
0,0x3ea68f12,0,0x3f299415,0x3f1d7fd1,0x3f5695e5,0x3f7e1324,0x3f531849,0x3f7853f8,0x3f7f0e58,0x3e78cfcc,0xbeebcbbb,0x3f6a09a7,0x3f3b8f3b,0xbf6ed89e,0xbf6ff573,
0,0x3ebe1d4a,0,0x3f32c8c9,0x3f3085bb,0x3f68bf3c,0x3f7fec43,0x3f3b8f3b,0x3f7fb10f,0x3f721352,0x3d48fb30,0xbf299415,0x3f41d870,0x3eebcbbb,0xbf7f4e6d,0xbf43e200,
0x354ccccd,0x354ccccd,0x354ccccd,0x354ccccd,0x354ccccd,0x354ccccd,0x354ccccd,0x354ccccd,0x354ccccd,0x354ccccd,0x354ccccd,0x354ccccd,0x354ccccd,0x354ccccd,0x354ccccd,0x354ccccd,
0x354a9556,0x3540d407,0xb3f06739,0xb489fd76,0x352fa9af,0x3517bf2e,0xb4d29394,0xb5098908,0x34f3ff99,0x34af2067,0xb5247f35,0xb5392313,0x34470ca3,0x3320c8f3,0xb546a993,0xb54c8da6,
0x354ca946,0x354c0b7a,0x353a3296,0x3535c9e1,0x354aefd6,0x3549570a,0x3530f10f,0x352bab1e,0x35474213,0x3544b238,0x3525fb4c,0x351fe51e,0x3541a90f,0x353e2876,0x35196c52,0x351294e9,
0x3549570a,0x353a3296,0xb4df5d78,0xb5160c2f,0x351fe51e,0x34f8046f,0xb5336b4e,0xb546096a,0x34a1610f,0x340222f8,0xb54cc8da,0xb5474213,0xb38c9200,0xb4853f42,0xb535c9e1,0xb5196c52,
0x354c3ebe,0x3549c8ed,0x3505c511,0x34ebd9dd,0x3545619f,0x353f13b1,0x34c9e41f,0x34a5fca2,0x3536eeae,0x352d06a9,0x34807bea,0x34337cdc,0x3521740f,0x35145368,0x33c88ec2,0x32a0d559,
0x3547d2e4,0x3532319e,0xb52d06a9,0xb545619f,0x350d37c9,0x34b8292a,0xb54cbd02,0xb54276a0,0x340c0d4f,0xb3c88ec2,0xb52770fe,0xb4fbffb5,0xb4a5fca2,0xb505c511,0xb49369bb,0xb3710e6e,
0x354b8d5a,0x3546096a,0x346429d0,0x33dc7f3e,0x353c3c09,0x352e5b88,0xb220d873,0xb40222f8,0x351cb4cd,0x3507a9aa,0xb477673d,0xb4b3a83f,0x34df5d78,0x34aa91ce,0xb4e7b948,0xb50b6318,
0x3546096a,0x3528e03a,0xb54aefd6,0xb5485c01,0x34eff15b,0x346429d0,0xb52e5b88,0xb4fff144,0xb348ef90,0xb4a1610f,0xb4853f42,0x3220d873,0xb50b6318,0xb535c9e1,0x348eb659,0x3503db51,
0,0,0,0,0,0,0,0,0,0,0,0,0,0,0,0,
0x33f06739,0x3489fd76,0x354a9556,0x3540d407,0x34d29394,0x35098908,0x352fa9af,0x3517bf2e,0x35247f35,0x35392313,0x34f3ff99,0x34af2067,0x3546a993,0x354c8da6,0x34470ca3,0x3320c8f3,
0x32f13846,0x338c9200,0x34aa91ce,0x34bca2fc,0x33dc7f3e,0x3415f23f,0x34ce3fd4,0x34df5d78,0x343d4866,0x346429d0,0x34eff15b,0x34fff144,0x34853f42,0x3498176e,0x3507a9aa,0x350f0707,
0x3415f23f,0x34aa91ce,0x352bab1e,0x350b6318,0x34fff144,0x3522fcc6,0x34c580a2,0x3450c934,0x353c3c09,0x354a3307,0x3220d873,0xb43d4866,0x354c0b7a,0x3541a90f,0xb4bca2fc,0xb507a9aa,
0x33710e6e,0x340c0d4f,0x351b138d,0x352770fe,0x345a7db8,0x349369bb,0x3532319e,0x353b3aec,0x34b8292a,0x34db2291,0x354276a0,0x3547d2e4,0x34fbffb5,0x350d37c9,0x354b4283,0x354cbd02,
0x34337cdc,0x34c9e41f,0x34db2291,0x345a7db8,0x35145368,0x3536eeae,0xb2a0d559,0xb4807bea,0x3549c8ed,0x354b4283,0xb4ebd9dd,0xb521740f,0x353b3aec,0x351b138d,0xb53f13b1,0xb54c3ebe,
0x33b4968b,0x3450c934,0x3544b238,0x354aefd6,0x34a1610f,0x34d6df37,0x354cc8da,0x354a3307,0x3503db51,0x35196c52,0x35433cb1,0x35380c6c,0x352bab1e,0x353a3296,0x3528e03a,0x35160c2f,
0x3450c934,0x34e7b948,0x33dc7f3e,0xb429aa67,0x3525fb4c,0x3544b238,0xb4d6df37,0xb51fe51e,0x354c6a23,0x353c3c09,0xb541a90f,0xb54cc8da,0x35160c2f,0x34bca2fc,0xb53ff78f,0xb51cb4cd,
0x3f80,0x3f80,0x3f753e95,0x3f753e95,0x3ea13f73,0xbea1bf73,0x3f80bcc9,0xbf803cc9,0x3f183f4e,0x3f183f4e,0x3f71beac,0x3f71beac,0x3f513f13,0xbf51bf13,0x3f4abf1d,0xbf4a3f1d,
0x3f80,0x3f80,0x3e95bf75,0x3e95bf75,0x3f273f42,0xbf27bf42,0xbecfbf6a,0x3ecf3f6a,0x3f7d3e16,0x3f7d3e16,0xbf67bedb,0xbf67bedb,0x3f58bf09,0xbf583f09,0xbf773e89,0x3f77be89,
0x3f80,0x3f80,0xbf75be95,0xbf75be95,0x3f653ee6,0xbf65bee6,0xbf313f39,0x3f31bf39,0x3f4ebf18,0x3f4ebf18,0x3eac3f71,0x3eac3f71,0xbe2fbf7c,0x3e2f3f7c,0x3f7e3dfb,0xbf7ebdfb,
0x3f80,0x3f80,0xbe953f75,0xbe953f75,0x3f7f3d97,0xbf7fbd97,0x3f6f3eb8,0xbf6fbeb8,0x3e16bf7d,0x3e16bf7d,0x3edbbf67,0x3edbbf67,0xbf7abe60,0x3f7a3e60,0xbf5fbefc,0x3f5f3efc,
0x3f80,0x3f80,0x3f753e95,0x3f753e95,0x3f73bea1,0xbf733ea1,0xbcc9bf80,0x3cc93f80,0xbf18bf4e,0xbf18bf4e,0xbf713eac,0xbf713eac,0xbf133f51,0x3f13bf51,0x3f1d3f4a,0xbf1dbf4a,
0x3f80,0x3f80,0x3e95bf75,0x3e95bf75,0x3f42bf27,0xbf423f27,0xbf6a3ecf,0x3f6abecf,0xbf7dbe16,0xbf7dbe16,0x3f673edb,0x3f673edb,0x3f093f58,0xbf09bf58,0xbe89bf77,0x3e893f77,
0x3f80,0x3f80,0xbf75be95,0xbf75be95,0x3ee6bf65,0xbee63f65,0x3f393f31,0xbf39bf31,0xbf4e3f18,0xbf4e3f18,0xbeacbf71,0xbeacbf71,0x3f7cbe2f,0xbf7c3e2f,0xbdfb3f7e,0x3dfbbf7e,
0x3f80,0x3f80,0xbe953f75,0xbe953f75,0x3d97bf7f,0xbd973f7f,0x3eb8bf6f,0xbeb83f6f,0xbe163f7d,0xbe163f7d,0xbedb3f67,0xbedb3f67,0x3e60bf7a,0xbe603f7a,0x3efcbf5f,0xbefc3f5f,
0x3f0ebf55,0x3f0ebf55,0xbf22bf46,0xbf22bf46,0x3e89bf77,0xbe893f77,0xbf58bf09,0x3f583f09,0xbd49bf80,0xbd49bf80,0xbf78be79,0xbf78be79,0xbeb8bf6f,0x3eb83f6f,0xbf7f3d97,0x3f7fbd97,
0xbf0e3f55,0xbf0e3f55,0x3f46bf22,0x3f46bf22,0x3dfb3f7e,0xbdfbbf7e,0x3e2fbf7c,0xbe2f3f7c,0x3f3e3f2c,0x3f3e3f2c,0xbf04bf5c,0xbf04bf5c,0x3f803cc9,0xbf80bcc9,0xbf73bea1,0x3f733ea1,
0x3f0ebf55,0x3f0ebf55,0x3f223f46,0x3f223f46,0xbefcbf5f,0x3efc3f5f,0x3f7abe60,0xbf7a3e60,0xbf803d49,0xbf803d49,0x3e79bf78,0x3e79bf78,0xbecf3f6a,0x3ecfbf6a,0xbf42bf27,0x3f423f27,
0xbf0e3f55,0xbf0e3f55,0xbf463f22,0xbf463f22,0x3f4a3f1d,0xbf4abf1d,0x3f133f51,0xbf13bf51,0x3f2cbf3e,0x3f2cbf3e,0x3f5cbf04,0x3f5cbf04,0xbf31bf39,0x3f313f39,0xbee6bf65,0x3ee63f65,
0x3f0ebf55,0x3f0ebf55,0xbf22bf46,0xbf22bf46,0xbf77be89,0x3f773e89,0xbf093f58,0x3f09bf58,0x3d493f80,0x3d493f80,0x3f783e79,0x3f783e79,0x3f6fbeb8,0xbf6f3eb8,0xbd97bf7f,0x3d973f7f,
0xbf0e3f55,0xbf0e3f55,0x3f46bf22,0x3f46bf22,0x3f7ebdfb,0xbf7e3dfb,0xbf7cbe2f,0x3f7c3e2f,0xbf3ebf2c,0xbf3ebf2c,0x3f043f5c,0x3f043f5c,0xbcc93f80,0x3cc9bf80,0x3ea1bf73,0xbea13f73,
0x3f0ebf55,0x3f0ebf55,0x3f223f46,0x3f223f46,0xbf5f3efc,0x3f5fbefc,0xbe60bf7a,0x3e603f7a,0x3f80bd49,0x3f80bd49,0xbe793f78,0xbe793f78,0xbf6abecf,0x3f6a3ecf,0x3f27bf42,0xbf273f42,
0xbf0e3f55,0xbf0e3f55,0xbf463f22,0xbf463f22,0x3f1dbf4a,0xbf1d3f4a,0x3f51bf13,0xbf513f13,0xbf2c3f3e,0xbf2c3f3e,0xbf5c3f04,0xbf5c3f04,0x3f39bf31,0xbf393f31,0x3f65bee6,0xbf653ee6,
0x3f800000,0x3f800000,0x3e95bf75,0x3e95bf75,0x3f73bea1,0xbf733ea1,0xbcc9bf80,0x3cc93f80,0x3f4ebf18,0x3f4ebf18,0xbeacbf71,0xbeacbf71,0x3f13bf51,0xbf133f51,0xbf1dbf4a,0x3f1d3f4a,
0x3f800000,0x3f800000,0xbf75be95,0xbf75be95,0x3f42bf27,0xbf423f27,0xbf6a3ecf,0x3f6abecf,0x3e16bf7d,0x3e16bf7d,0xbedb3f67,0xbedb3f67,0xbf09bf58,0x3f093f58,0x3e893f77,0xbe89bf77,
0x3f800000,0x3f800000,0xbe953f75,0xbe953f75,0x3ee6bf65,0xbee63f65,0x3f393f31,0xbf39bf31,0xbf18bf4e,0xbf18bf4e,0x3f71beac,0x3f71beac,0xbf7c3e2f,0x3f7cbe2f,0x3dfbbf7e,0xbdfb3f7e,
0x3f800000,0x3f800000,0x3f753e95,0x3f753e95,0x3d97bf7f,0xbd973f7f,0x3eb8bf6f,0xbeb83f6f,0xbf7dbe16,0xbf7dbe16,0xbf67bedb,0xbf67bedb,0xbe603f7a,0x3e60bf7a,0xbefc3f5f,0x3efcbf5f,
0x3f800000,0x3f800000,0x3e95bf75,0x3e95bf75,0xbea1bf73,0x3ea13f73,0xbf803cc9,0x3f80bcc9,0xbf4e3f18,0xbf4e3f18,0x3eac3f71,0x3eac3f71,0x3f513f13,0xbf51bf13,0x3f4abf1d,0xbf4a3f1d,
0x3f800000,0x3f800000,0xbf75be95,0xbf75be95,0xbf27bf42,0x3f273f42,0x3ecf3f6a,0xbecfbf6a,0xbe163f7d,0xbe163f7d,0x3edbbf67,0x3edbbf67,0x3f58bf09,0xbf583f09,0xbf773e89,0x3f77be89,
0x3f800000,0x3f800000,0xbe953f75,0xbe953f75,0xbf65bee6,0x3f653ee6,0x3f31bf39,0xbf313f39,0x3f183f4e,0x3f183f4e,0xbf713eac,0xbf713eac,0xbe2fbf7c,0x3e2f3f7c,0x3f7e3dfb,0xbf7ebdfb,
0x3f800000,0x3f800000,0x3f753e95,0x3f753e95,0xbf7fbd97,0x3f7f3d97,0xbf6fbeb8,0x3f6f3eb8,0x3f7d3e16,0x3f7d3e16,0x3f673edb,0x3f673edb,0xbf7abe60,0x3f7a3e60,0xbf5fbefc,0x3f5f3efc,
0xbf55bf0e,0xbf55bf0e,0xbf463f22,0xbf463f22,0xbf77be89,0x3f773e89,0xbf093f58,0x3f09bf58,0xbf803d49,0xbf803d49,0xbe793f78,0xbe793f78,0xbf6f3eb8,0x3f6fbeb8,0x3d973f7f,0xbd97bf7f,
0x3f553f0e,0x3f553f0e,0xbf22bf46,0xbf22bf46,0x3f7ebdfb,0xbf7e3dfb,0xbf7cbe2f,0x3f7c3e2f,0x3f2cbf3e,0x3f2cbf3e,0xbf5c3f04,0xbf5c3f04,0x3cc9bf80,0xbcc93f80,0xbea13f73,0x3ea1bf73,
0xbf55bf0e,0xbf55bf0e,0x3f46bf22,0x3f46bf22,0xbf5f3efc,0x3f5fbefc,0xbe60bf7a,0x3e603f7a,0x3d493f80,0x3d493f80,0xbf78be79,0xbf78be79,0x3f6a3ecf,0xbf6abecf,0xbf273f42,0x3f27bf42,
0x3f553f0e,0x3f553f0e,0x3f223f46,0x3f223f46,0x3f1dbf4a,0xbf1d3f4a,0x3f51bf13,0xbf513f13,0xbf3ebf2c,0xbf3ebf2c,0xbf04bf5c,0xbf04bf5c,0xbf393f31,0x3f39bf31,0xbf653ee6,0x3f65bee6,
0xbf55bf0e,0xbf55bf0e,0xbf463f22,0xbf463f22,0xbe893f77,0x3e89bf77,0x3f583f09,0xbf58bf09,0x3f80bd49,0x3f80bd49,0x3e79bf78,0x3e79bf78,0xbeb8bf6f,0x3eb83f6f,0xbf7f3d97,0x3f7fbd97,
0x3f553f0e,0x3f553f0e,0xbf22bf46,0xbf22bf46,0xbdfbbf7e,0x3dfb3f7e,0xbe2f3f7c,0x3e2fbf7c,0xbf2c3f3e,0xbf2c3f3e,0x3f5cbf04,0x3f5cbf04,0x3f803cc9,0xbf80bcc9,0xbf73bea1,0x3f733ea1,
0xbf55bf0e,0xbf55bf0e,0x3f46bf22,0x3f46bf22,0x3efc3f5f,0xbefcbf5f,0xbf7a3e60,0x3f7abe60,0xbd49bf80,0xbd49bf80,0x3f783e79,0x3f783e79,0xbecf3f6a,0x3ecfbf6a,0xbf42bf27,0x3f423f27,
0x3f553f0e,0x3f553f0e,0x3f223f46,0x3f223f46,0xbf4abf1d,0x3f4a3f1d,0xbf13bf51,0x3f133f51,0x3f3e3f2c,0x3f3e3f2c,0x3f043f5c,0x3f043f5c,0xbf31bf39,0x3f313f39,0xbee6bf65,0x3ee63f65,
0x3f803f80,0x3f55bf55,0x3f803f80,0x3f55bf55,0x3f803f80,0x3f55bf55,0x3f803f80,0x3f55bf55,0x3f803f80,0x3f55bf55,0x3f803f80,0x3f55bf55,0x3f803f80,0x3f55bf55,0x3f803f80,0x3f55bf55,
0x3f423f73,0x3f7ebf77,0xbf42bf73,0xbf7e3f77,0x3d973ee6,0x3f1dbf5f,0xbd97bee6,0xbf1d3f5f,0xbf27bea1,0xbdfbbe89,0x3f273ea1,0x3dfb3e89,0xbf7fbf65,0xbf4a3efc,0x3f7f3f65,0x3f4abefc,
0x3e163f4e,0x3f2cbf80,0x3e163f4e,0x3f2cbf80,0xbf7dbf18,0xbf3e3d49,0xbf7dbf18,0xbf3e3d49,0xbe16bf4e,0xbf2c3f80,0xbe16bf4e,0xbf2c3f80,0x3f7d3f18,0x3f3ebd49,0x3f7d3f18,0x3f3ebd49,
0xbf093f13,0x3cc9bf6f,0x3f09bf13,0xbcc93f6f,0xbe60bf7c,0xbf393f6a,0x3e603f7c,0x3f39bf6a,0x3f583f51,0x3f80beb8,0xbf58bf51,0xbf803eb8,0xbf7abe2f,0xbf31becf,0x3f7a3e2f,0x3f313ecf,
0xbf753e95,0xbf22bf46,0xbf753e95,0xbf22bf46,0x3f75be95,0x3f223f46,0x3f75be95,0x3f223f46,0xbf753e95,0xbf22bf46,0xbf753e95,0xbf22bf46,0x3f75be95,0x3f223f46,0x3f75be95,0x3f223f46,
0xbf6abcc9,0xbf7cbf09,0x3f6a3cc9,0x3f7c3f09,0x3eb83f39,0x3f51be60,0xbeb8bf39,0xbf513e60,0x3ecfbf80,0xbe2f3f58,0xbecf3f80,0x3e2fbf58,0xbf6f3f31,0xbf13bf7a,0x3f6fbf31,0x3f133f7a,
0xbedbbeac,0xbf5cbe79,0xbedbbeac,0xbf5cbe79,0xbf673f71,0xbf04bf78,0xbf673f71,0xbf04bf78,0x3edb3eac,0x3f5c3e79,0x3edb3eac,0x3f5c3e79,0x3f67bf71,0x3f043f78,0x3f67bf71,0x3f043f78,
0x3e89bf1d,0xbea13d97,0xbe893f1d,0x3ea1bd97,0xbefc3dfb,0xbf65bf27,0x3efcbdfb,0x3f653f27,0xbf773f4a,0xbf73bf7f,0x3f77bf4a,0x3f733f7f,0xbf5f3f7e,0xbee6bf42,0x3f5fbf7e,0x3ee63f42,
0,0xbf0e3f0e,0,0xbf0e3f0e,0,0xbf0e3f0e,0,0xbf0e3f0e,0,0xbf0e3f0e,0,0xbf0e3f0e,0,0xbf0e3f0e,0,0xbf0e3f0e,
0x3f273ea1,0x3dfb3e89,0xbf27bea1,0xbdfbbe89,0x3f7f3f65,0x3f4abefc,0xbf7fbf65,0xbf4a3efc,0x3f423f73,0x3f7ebf77,0xbf42bf73,0xbf7e3f77,0x3d973ee6,0x3f1dbf5f,0xbd97bee6,0xbf1d3f5f,
0x3f7d3f18,0x3f3ebd49,0x3f7d3f18,0x3f3ebd49,0x3e163f4e,0x3f2cbf80,0x3e163f4e,0x3f2cbf80,0xbf7dbf18,0xbf3e3d49,0xbf7dbf18,0xbf3e3d49,0xbe16bf4e,0xbf2c3f80,0xbe16bf4e,0xbf2c3f80,
0x3f583f51,0x3f80beb8,0xbf58bf51,0xbf803eb8,0xbf7abe2f,0xbf31becf,0x3f7a3e2f,0x3f313ecf,0x3f09bf13,0xbcc93f6f,0xbf093f13,0x3cc9bf6f,0x3e603f7c,0x3f39bf6a,0xbe60bf7c,0xbf393f6a,
0x3e953f75,0x3f46bf22,0x3e953f75,0x3f46bf22,0xbe95bf75,0xbf463f22,0xbe95bf75,0xbf463f22,0x3e953f75,0x3f46bf22,0x3e953f75,0x3f46bf22,0xbe95bf75,0xbf463f22,0xbe95bf75,0xbf463f22,
0xbecf3f80,0x3e2fbf58,0x3ecfbf80,0xbe2f3f58,0x3f6fbf31,0x3f133f7a,0xbf6f3f31,0xbf13bf7a,0xbf6abcc9,0xbf7cbf09,0x3f6a3cc9,0x3f7c3f09,0x3eb83f39,0x3f51be60,0xbeb8bf39,0xbf513e60,
0xbf673f71,0xbf04bf78,0xbf673f71,0xbf04bf78,0x3edb3eac,0x3f5c3e79,0x3edb3eac,0x3f5c3e79,0x3f67bf71,0x3f043f78,0x3f67bf71,0x3f043f78,0xbedbbeac,0xbf5cbe79,0xbedbbeac,0xbf5cbe79,
0xbf773f4a,0xbf73bf7f,0x3f77bf4a,0x3f733f7f,0xbf5f3f7e,0xbee6bf42,0x3f5fbf7e,0x3ee63f42,0xbe893f1d,0x3ea1bd97,0x3e89bf1d,0xbea13d97,0x3efcbdfb,0x3f653f27,0xbefc3dfb,0xbf65bf27,
0,0x3f0ebf0e,0,0x3f0ebf0e,0,0x3f0ebf0e,0,0x3f0ebf0e,0,0x3f0ebf0e,0,0x3f0ebf0e,0,0x3f0ebf0e,0,0x3f0ebf0e,
0xbf27bea1,0xbdfbbe89,0x3f273ea1,0x3dfb3e89,0xbf7fbf65,0xbf4a3efc,0x3f7f3f65,0x3f4abefc,0xbf42bf73,0xbf7e3f77,0x3f423f73,0x3f7ebf77,0xbd97bee6,0xbf1d3f5f,0x3d973ee6,0x3f1dbf5f,
0xbf7dbf18,0xbf3e3d49,0xbf7dbf18,0xbf3e3d49,0xbe16bf4e,0xbf2c3f80,0xbe16bf4e,0xbf2c3f80,0x3f7d3f18,0x3f3ebd49,0x3f7d3f18,0x3f3ebd49,0x3e163f4e,0x3f2cbf80,0x3e163f4e,0x3f2cbf80,
0xbf58bf51,0xbf803eb8,0x3f583f51,0x3f80beb8,0x3f7a3e2f,0x3f313ecf,0xbf7abe2f,0xbf31becf,0xbf093f13,0x3cc9bf6f,0x3f09bf13,0xbcc93f6f,0xbe60bf7c,0xbf393f6a,0x3e603f7c,0x3f39bf6a,
0xbe95bf75,0xbf463f22,0xbe95bf75,0xbf463f22,0x3e953f75,0x3f46bf22,0x3e953f75,0x3f46bf22,0xbe95bf75,0xbf463f22,0xbe95bf75,0xbf463f22,0x3e953f75,0x3f46bf22,0x3e953f75,0x3f46bf22,
0x3ecfbf80,0xbe2f3f58,0xbecf3f80,0x3e2fbf58,0xbf6f3f31,0xbf13bf7a,0x3f6fbf31,0x3f133f7a,0x3f6a3cc9,0x3f7c3f09,0xbf6abcc9,0xbf7cbf09,0xbeb8bf39,0xbf513e60,0x3eb83f39,0x3f51be60,
0x3f67bf71,0x3f043f78,0x3f67bf71,0x3f043f78,0xbedbbeac,0xbf5cbe79,0xbedbbeac,0xbf5cbe79,0xbf673f71,0xbf04bf78,0xbf673f71,0xbf04bf78,0x3edb3eac,0x3f5c3e79,0x3edb3eac,0x3f5c3e79,
0x3f77bf4a,0x3f733f7f,0xbf773f4a,0xbf73bf7f,0x3f5fbf7e,0x3ee63f42,0xbf5f3f7e,0xbee6bf42,0x3e89bf1d,0xbea13d97,0xbe893f1d,0x3ea1bd97,0xbefc3dfb,0xbf65bf27,0x3efcbdfb,0x3f653f27,
0x3f800000,0x3f7fcbe2,0x3f800000,0x3f686b39,0x3f7f2f9d,0x3f7e2b72,0x3f26050a,0x3e8a11f7,0x3f7cbfc9,0x3f7aed37,0xbe22abb6,0xbf0ee0db,0x3f78b47b,0x3f76167a,0xbf5ac450,0xbf7e5a38,
0x3f800000,0x3f7efcc9,0x3f800000,0x3f62df7b,0x3f7bf531,0x3f76ef5b,0x3f121eb0,0x3e007745,0x3f6ff573,0x3f671599,0xbeb263ef,0xbf3e35c5,0x3f5c61c7,0x3f4fefa8,0xbf77f110,0xbf7940c0,
0x3f800000,0x3f7d906e,0x3f800000,0x3f5cc7d1,0x3f764d97,0x3f6a5ad9,0x3ef9a02d,0xbcafea69,0x3f59f26a,0x3f456439,0xbf064b82,0xbf62241a,0x3f2d1469,0x3f11796b,0xbf7fc38f,0xbf570348,
0x3f800000,0x3f7b87b2,0x3f800000,0x3f5627fe,0x3f6e46be,0x3f58b3a1,0x3ecc9b8b,0xbe2bf804,0x3f3b8f3b,0x3f17de12,0xbf2e3bde,0xbf788486,0x3eddbe79,0x3e840270,0xbf718f57,0xbf1ba299,
0x3f800000,0x3f78e3d6,0x3f800000,0x3f4f0417,0x3f63f473,0x3f425b89,0x3e9d9e78,0xbe9f1cdf,0x3f15f6d9,0x3ec27b55,0xbf4f7a1f,0xbf7fffb1,0x3e1c76de,0xbda973ba,0xbf4e8d90,0xbe9c1faf,
0x3f800000,0x3f75a67b,0x3f800000,0x3f476085,0x3f577026,0x3f27ce61,0x3e5a3997,0xbee4cbfe,0x3ed53641,0x3e1324ca,0xbf68bf3c,0xbf7822d1,0xbe1008b7,0xbed3c867,0xbf19c200,0x3d0a342f,
0x3f800000,0x3f71d19f,0x3f800000,0x3f3f41fc,0x3f48d8b3,0x3f099f4e,0x3dee3876,0xbf12c39a,0x3e6c9a7f,0xbdcefdb7,0xbf791298,0xbf61668a,0xbed8106b,0xbf3238aa,0xbeaf713a,0x3ebca7af,
0x3f800000,0x3f6d67a1,0x3f800000,0x3f36ad7f,0x3f385216,0x3ed0eb2a,0x3c96c9b6,0xbf2ff3e6,0x3d16c32c,0xbeadf73c,0xbf7fd397,0xbf3d27b8,0xbf2ac082,0xbf65b710,0xbd621469,0x3f28fd41,
0,0x3d2351cb,0,0x3ed6a399,0x3da3308c,0x3df475c0,0x3f42de29,0x3f76841b,0x3e22abb6,0x3e4ada4f,0x3f7cbfc9,0x3f546b3b,0x3e72b651,0x3e8d17c0,0x3f04f484,0x3de7fa9a,
0,0x3db5f8da,0,0x3eed3063,0x3e354098,0x3e870ada,0x3f5233c6,0x3f7dfa38,0x3eb263ef,0x3edc53c1,0x3f6ff573,0x3f2b561b,0x3f0242b1,0x3f1553b7,0x3e7ee6e1,0xbe698bba,
0,0x3e0cec4a,0,0x3f019573,0x3e8b9507,0x3ece0bea,0x3f5f8327,0x3f7ff0e3,0x3f064b82,0x3f2302d3,0x3f59f26a,0x3eeff7fb,0x3f3ca003,0x3f52a649,0xbd2fe007,0xbf0af1b7,
0,0x3e3e853e,0,0x3f0c42c9,0x3ebb31a0,0x3f084b92,0x3f6aab7b,0x3f7c5d3a,0x3f2e3bde,0x3f4e1689,0x3f3b8f3b,0x3e75c35a,0x3f66becc,0x3f77583a,0xbea986c4,0xbf4b41fa,
0,0x3e6fa8b2,0,0x3f16999f,0x3ee900b7,0x3f269de3,0x3f73913f,0x3f73530e,0x3f4f7a1f,0x3f6cd007,0x3f15f6d9,0xbb490fc6,0x3f7cfe73,0x3f7f1f49,0xbf173c07,0xbf73ced9,
0,0x3e901c2c,0,0x3f209393,0x3f0a48ad,0x3f4154e1,0x3f7a1e84,0x3f650479,0x3f68bf3c,0x3f7d57de,0x3ed53641,0xbe7bdba4,0x3f7d7474,0x3f6912ae,0xbf4cae79,0xbf7fdaaf,
0,0x3ea80b1f,0,0x3f2a2a80,0x3f1ebc12,0x3f57dc7f,0x3f7e4323,0x3f51c0c2,0x3f791298,0x3f7eb069,0x3e6c9a7f,0xbef2bd43,0x3f6816a8,0x3f37c655,0xbf708066,0xbf6dfcf2,
0,0x3ebf926f,0,0x3f33587a,0x3f31a81d,0x3f69b7e4,0x3f7ff4e6,0x3f39f2ac,0x3f7fd397,0x3f70c501,0x3d16c32c,0xbf2c800f,0x3f3ebc1b,0x3ee1fb6a,0xbf7f9c18,0xbf404c5c,
0x354ccccd,0x354ccccd,0x354ccccd,0x354ccccd,0x354ccccd,0x354ccccd,0x354ccccd,0x354ccccd,0x354ccccd,0x354ccccd,0x354ccccd,0x354ccccd,0x354ccccd,0x354ccccd,0x354ccccd,0x354ccccd,
0x354a3307,0x353ff78f,0xb40222f8,0xb48eb659,0x352e5b88,0x35160c2f,0xb4d6df37,0xb50b6318,0x34eff15b,0x34aa91ce,0xb525fb4c,0xb53a3296,0x343d4866,0x32f13846,0xb5474213,0xb54ca946,
0x354ca31b,0x354bfd6e,0x3539ef61,0x35357f95,0x354ad9f2,0x3549395b,0x35309fda,0x352b5332,0x35471cab,0x3544852f,0x35259ce0,0x351f806a,0x35417480,0x353dec81,0x35190197,0x35122466,
0x3548bdc6,0x3538de14,0xb4e49af8,0xb5182b04,0x351de9c7,0x34f2fcea,0xb534e9ae,0xb546d06b,0x349b95de,0x33eb6e11,0xb54ccc8e,0xb5468241,0xb3a597c6,0xb48b2c30,0xb5345208,0xb51752fa,
0x354c2618,0x354990f4,0x3504d0d5,0x34e9cab3,0x35450adf,0x353e9eff,0x34c7b357,0x34a3afa2,0x35365d28,0x352c59b8,0x347c30c0,0x342e9479,0x3520ad5c,0x351374de,0x33be9392,0x327142bd,
0x3546f6c8,0x35304e38,0xb52f0373,0xb5465a74,0x350a76bb,0x34b1652e,0xb54c9c72,0xb5413f79,0x33fa57c9,0xb3e67457,0xb5253e0d,0xb4f60334,0xb4acd9f0,0xb5089a01,0xb48c5a95,0xb334dd20,
0x354b55f5,0x35458c49,0x345ce98c,0x33cd8ba2,0x353b7be1,0x352d5c81,0xb28cbb87,0xb4099337,0x351b7c6d,0x35063eb4,0xb47e9498,0xb4b70998,0x34dc3217,0x34a72288,0xb4ead291,0xb50cc31e,
0x3544dec8,0x35265953,0xb54b7b60,0xb5476700,0x34e8c245,0x3453371a,0xb52c02a0,0xb4f90428,0xb3878fc8,0xb4a96d1f,0xb479cc4b,0x32dd204b,0xb50e93bb,0xb537c5a7,0x3496ec8c,0x35073101,
0,0,0,0,0,0,0,0,0,0,0,0,0,0,0,0,
0x340222f8,0x348eb659,0x354a3307,0x353ff78f,0x34d6df37,0x350b6318,0x352e5b88,0x35160c2f,0x3525fb4c,0x353a3296,0x34eff15b,0x34aa91ce,0x35474213,0x354ca946,0x343d4866,0x32f13846,
0x3302a7d6,0x339193e2,0x34abb614,0x34bdc04f,0x33e17a10,0x34186a98,0x34cf5584,0x34e06adb,0x343fba28,0x3466937a,0x34f0f5cb,0x3500760f,0x34866f4c,0x349941f2,0x35082200,0x350f79fb,
0x3422483f,0x34b04301,0x3529ef63,0x350911af,0x350268a9,0x3524ded4,0x34bff996,0x34449c48,0x353d7339,0x354aacb2,0xb120d96b,0xb4497c83,0x354bc054,0x35409d9b,0xb4c23103,0xb50a000c,
0x33828d3d,0x3411007a,0x351be4ed,0x3528296b,0x345f54d8,0x3495c14d,0x3532cf52,0x353bbc62,0x34ba66f9,0x34dd4116,0x3542da99,0x3548186a,0x34fdf9b6,0x350e2017,0x354b68e9,0x354cc3eb,
0x34422b74,0x34d06ab5,0x34d4ba6c,0x344bebe7,0x3516e669,0x353898a3,0xb30cb338,0xb4879f03,0x354a6529,0x354ac390,0xb4f1f9a5,0xb523bec8,0x3539abba,0x3518967c,0xb54066b8,0xb54c7ce0,
0x33c39166,0x3458115e,0x3545367c,0x354b2e94,0x34a4d655,0x34da1284,0x354cc0b6,0x3549e42e,0x35054b1c,0x351aaa4d,0x3542a8d8,0x353736c7,0x352cb065,0x353af983,0x3527cd68,0x3514c224,
0x3461bf99,0x34eeec58,0x33b99548,0xb43ad62f,0x35288507,0x3545e02f,0xb4de4f8b,0xb5229b2e,0x354c1907,0x353a7558,0xb5430be1,0xb54caef3,0x35130511,0x34b4c922,0xb53e63f5,0xb519d6b0,
0x3f80,0x3f80,0x3f7b3e48,0x3f7b3e48,0x3eac3f71,0xbeacbf71,0x3f7dbe16,0xbf7d3e16,0x3f223f46,0x3f223f46,0x3f62bef1,0x3f62bef1,0x3f5c3f04,0xbf5cbf04,0x3f2cbf3e,0xbf2c3f3e,
0x3f80,0x3f80,0x3e48bf7b,0x3e48bf7b,0x3f2c3f3e,0xbf2cbf3e,0xbf04bf5c,0x3f043f5c,0x3f7f3dc9,0x3f7f3dc9,0xbf75be95,0xbf75be95,0x3f4ebf18,0xbf4e3f18,0xbf673edb,0x3f67bedb,
0x3f80,0x3f80,0xbf7bbe48,0xbf7bbe48,0x3f673edb,0xbf67bedb,0xbf183f4e,0x3f18bf4e,0x3f46bf22,0x3f46bf22,0x3ef13f62,0x3ef13f62,0xbe79bf78,0x3e793f78,0x3f80bd49,0xbf803d49,
0x3f80,0x3f80,0xbe483f7b,0xbe483f7b,0x3f803d49,0xbf80bd49,0x3f783e79,0xbf78be79,0x3dc9bf7f,0x3dc9bf7f,0x3e95bf75,0x3e95bf75,0xbf7dbe16,0x3f7d3e16,0xbf71beac,0x3f713eac,
0x3f80,0x3f80,0x3f7b3e48,0x3f7b3e48,0x3f71beac,0xbf713eac,0xbe16bf7d,0x3e163f7d,0xbf22bf46,0xbf22bf46,0xbf623ef1,0xbf623ef1,0xbf043f5c,0x3f04bf5c,0x3f3e3f2c,0xbf3ebf2c,
0x3f80,0x3f80,0x3e48bf7b,0x3e48bf7b,0x3f3ebf2c,0xbf3e3f2c,0xbf5c3f04,0x3f5cbf04,0xbf7fbdc9,0xbf7fbdc9,0x3f753e95,0x3f753e95,0x3f183f4e,0xbf18bf4e,0xbedbbf67,0x3edb3f67,
0x3f80,0x3f80,0xbf7bbe48,0xbf7bbe48,0x3edbbf67,0xbedb3f67,0x3f4e3f18,0xbf4ebf18,0xbf463f22,0xbf463f22,0xbef1bf62,0xbef1bf62,0x3f78be79,0xbf783e79,0x3d493f80,0xbd49bf80,
0x3f80,0x3f80,0xbe483f7b,0xbe483f7b,0x3d49bf80,0xbd493f80,0x3e79bf78,0xbe793f78,0xbdc93f7f,0xbdc93f7f,0xbe953f75,0xbe953f75,0x3e16bf7d,0xbe163f7d,0x3eacbf71,0xbeac3f71,
0x3ec4bf6d,0x3ec4bf6d,0xbf55bf0e,0xbf55bf0e,0x3d49bf80,0xbd493f80,0xbf78be79,0x3f783e79,0xbe95bf75,0xbe95bf75,0xbf7f3dc9,0xbf7f3dc9,0xbf18bf4e,0x3f183f4e,0xbf673edb,0x3f67bedb,
0xbec43f6d,0xbec43f6d,0x3f0ebf55,0x3f0ebf55,0x3eac3f71,0xbeacbf71,0xbe16bf7d,0x3e163f7d,0x3f623ef1,0x3f623ef1,0xbf46bf22,0xbf46bf22,0x3f78be79,0xbf783e79,0xbf803d49,0x3f80bd49,
0x3ec4bf6d,0x3ec4bf6d,0x3f553f0e,0x3f553f0e,0xbf2cbf3e,0x3f2c3f3e,0x3f5cbf04,0xbf5c3f04,0xbf753e95,0xbf753e95,0xbdc9bf7f,0xbdc9bf7f,0xbe163f7d,0x3e16bf7d,0xbf71beac,0x3f713eac,
0xbec43f6d,0xbec43f6d,0xbf0e3f55,0xbf0e3f55,0x3f673edb,0xbf67bedb,0x3f4e3f18,0xbf4ebf18,0x3ef1bf62,0x3ef1bf62,0x3f22bf46,0x3f22bf46,0xbf5cbf04,0x3f5c3f04,0xbf3ebf2c,0x3f3e3f2c,
0x3ec4bf6d,0x3ec4bf6d,0xbf55bf0e,0xbf55bf0e,0xbf80bd49,0x3f803d49,0xbe793f78,0x3e79bf78,0x3e953f75,0x3e953f75,0x3f7fbdc9,0x3f7fbdc9,0x3f4ebf18,0xbf4e3f18,0xbedbbf67,0x3edb3f67,
0xbec43f6d,0xbec43f6d,0x3f0ebf55,0x3f0ebf55,0x3f71beac,0xbf713eac,0xbf7d3e16,0x3f7dbe16,0xbf62bef1,0xbf62bef1,0x3f463f22,0x3f463f22,0x3e793f78,0xbe79bf78,0xbd49bf80,0x3d493f80,
0x3ec4bf6d,0x3ec4bf6d,0x3f553f0e,0x3f553f0e,0xbf3e3f2c,0x3f3ebf2c,0xbf04bf5c,0x3f043f5c,0x3f75be95,0x3f75be95,0x3dc93f7f,0x3dc93f7f,0xbf7dbe16,0x3f7d3e16,0x3eacbf71,0xbeac3f71,
0xbec43f6d,0xbec43f6d,0xbf0e3f55,0xbf0e3f55,0x3edbbf67,0xbedb3f67,0x3f18bf4e,0xbf183f4e,0xbef13f62,0xbef13f62,0xbf223f46,0xbf223f46,0x3f04bf5c,0xbf043f5c,0x3f2cbf3e,0xbf2c3f3e,
0x3f800000,0x3f800000,0x3e48bf7b,0x3e48bf7b,0x3f71beac,0xbf713eac,0xbe16bf7d,0x3e163f7d,0x3f46bf22,0x3f46bf22,0xbef1bf62,0xbef1bf62,0x3f04bf5c,0xbf043f5c,0xbf3ebf2c,0x3f3e3f2c,
0x3f800000,0x3f800000,0xbf7bbe48,0xbf7bbe48,0x3f3ebf2c,0xbf3e3f2c,0xbf5c3f04,0x3f5cbf04,0x3dc9bf7f,0x3dc9bf7f,0xbe953f75,0xbe953f75,0xbf18bf4e,0x3f183f4e,0x3edb3f67,0xbedbbf67,
0x3f800000,0x3f800000,0xbe483f7b,0xbe483f7b,0x3edbbf67,0xbedb3f67,0x3f4e3f18,0xbf4ebf18,0xbf22bf46,0xbf22bf46,0x3f62bef1,0x3f62bef1,0xbf783e79,0x3f78be79,0xbd49bf80,0x3d493f80,
0x3f800000,0x3f800000,0x3f7b3e48,0x3f7b3e48,0x3d49bf80,0xbd493f80,0x3e79bf78,0xbe793f78,0xbf7fbdc9,0xbf7fbdc9,0xbf75be95,0xbf75be95,0xbe163f7d,0x3e16bf7d,0xbeac3f71,0x3eacbf71,
0x3f800000,0x3f800000,0x3e48bf7b,0x3e48bf7b,0xbeacbf71,0x3eac3f71,0xbf7d3e16,0x3f7dbe16,0xbf463f22,0xbf463f22,0x3ef13f62,0x3ef13f62,0x3f5c3f04,0xbf5cbf04,0x3f2cbf3e,0xbf2c3f3e,
0x3f800000,0x3f800000,0xbf7bbe48,0xbf7bbe48,0xbf2cbf3e,0x3f2c3f3e,0x3f043f5c,0xbf04bf5c,0xbdc93f7f,0xbdc93f7f,0x3e95bf75,0x3e95bf75,0x3f4ebf18,0xbf4e3f18,0xbf673edb,0x3f67bedb,
0x3f800000,0x3f800000,0xbe483f7b,0xbe483f7b,0xbf67bedb,0x3f673edb,0x3f18bf4e,0xbf183f4e,0x3f223f46,0x3f223f46,0xbf623ef1,0xbf623ef1,0xbe79bf78,0x3e793f78,0x3f80bd49,0xbf803d49,
0x3f800000,0x3f800000,0x3f7b3e48,0x3f7b3e48,0xbf80bd49,0x3f803d49,0xbf78be79,0x3f783e79,0x3f7f3dc9,0x3f7f3dc9,0x3f753e95,0x3f753e95,0xbf7dbe16,0x3f7d3e16,0xbf71beac,0x3f713eac,
0xbf6dbec4,0xbf6dbec4,0xbf0e3f55,0xbf0e3f55,0xbf80bd49,0x3f803d49,0xbe793f78,0x3e79bf78,0xbf753e95,0xbf753e95,0x3dc93f7f,0x3dc93f7f,0xbf4e3f18,0x3f4ebf18,0x3edb3f67,0xbedbbf67,
0x3f6d3ec4,0x3f6d3ec4,0xbf55bf0e,0xbf55bf0e,0x3f71beac,0xbf713eac,0xbf7d3e16,0x3f7dbe16,0x3ef1bf62,0x3ef1bf62,0xbf223f46,0xbf223f46,0xbe79bf78,0x3e793f78,0x3d493f80,0xbd49bf80,
0xbf6dbec4,0xbf6dbec4,0x3f0ebf55,0x3f0ebf55,0xbf3e3f2c,0x3f3ebf2c,0xbf04bf5c,0x3f043f5c,0x3e953f75,0x3e953f75,0xbf7f3dc9,0xbf7f3dc9,0x3f7d3e16,0xbf7dbe16,0xbeac3f71,0x3eacbf71,
0x3f6d3ec4,0x3f6d3ec4,0x3f553f0e,0x3f553f0e,0x3edbbf67,0xbedb3f67,0x3f18bf4e,0xbf183f4e,0xbf62bef1,0xbf62bef1,0xbf46bf22,0xbf46bf22,0xbf043f5c,0x3f04bf5c,0xbf2c3f3e,0x3f2cbf3e,
0xbf6dbec4,0xbf6dbec4,0xbf0e3f55,0xbf0e3f55,0xbd493f80,0x3d49bf80,0x3f783e79,0xbf78be79,0x3f75be95,0x3f75be95,0xbdc9bf7f,0xbdc9bf7f,0xbf18bf4e,0x3f183f4e,0xbf673edb,0x3f67bedb,
0x3f6d3ec4,0x3f6d3ec4,0xbf55bf0e,0xbf55bf0e,0xbeacbf71,0x3eac3f71,0x3e163f7d,0xbe16bf7d,0xbef13f62,0xbef13f62,0x3f22bf46,0x3f22bf46,0x3f78be79,0xbf783e79,0xbf803d49,0x3f80bd49,
0xbf6dbec4,0xbf6dbec4,0x3f0ebf55,0x3f0ebf55,0x3f2c3f3e,0xbf2cbf3e,0xbf5c3f04,0x3f5cbf04,0xbe95bf75,0xbe95bf75,0x3f7fbdc9,0x3f7fbdc9,0xbe163f7d,0x3e16bf7d,0xbf71beac,0x3f713eac,
0x3f6d3ec4,0x3f6d3ec4,0x3f553f0e,0x3f553f0e,0xbf67bedb,0x3f673edb,0xbf4ebf18,0x3f4e3f18,0x3f623ef1,0x3f623ef1,0x3f463f22,0x3f463f22,0xbf5cbf04,0x3f5c3f04,0xbf3ebf2c,0x3f3e3f2c,
0x3f803f80,0x3f6dbf6d,0x3f803f80,0x3f6dbf6d,0x3f803f80,0x3f6dbf6d,0x3f803f80,0x3f6dbf6d,0x3f803f80,0x3f6dbf6d,0x3f803f80,0x3f6dbf6d,0x3f803f80,0x3f6dbf6d,0x3f803f80,0x3f6dbf6d,
0x3f3e3f71,0x3f71bf80,0xbf3ebf71,0xbf713f80,0x3d493edb,0x3edbbf3e,0xbd49bedb,0xbedb3f3e,0xbf2cbeac,0xbeacbd49,0x3f2c3eac,0x3eac3d49,0xbf80bf67,0xbf673f2c,0x3f803f67,0x3f67bf2c,
0x3dc93f46,0x3ef1bf75,0x3dc93f46,0x3ef1bf75,0xbf7fbf22,0xbf623e95,0xbf7fbf22,0xbf623e95,0xbdc9bf46,0xbef13f75,0xbdc9bf46,0xbef13f75,0x3f7f3f22,0x3f62be95,0x3f7f3f22,0x3f62be95,
0xbf183f04,0xbe79bf4e,0x3f18bf04,0x3e793f4e,0xbe16bf78,0xbf043f7d,0x3e163f78,0x3f04bf7d,0x3f4e3f5c,0x3f78bf18,0xbf4ebf5c,0xbf783f18,0xbf7dbe79,0xbf5cbe16,0x3f7d3e79,0x3f5c3e16,
0xbf7b3e48,0xbf55bf0e,0xbf7b3e48,0xbf55bf0e,0x3f7bbe48,0x3f553f0e,0x3f7bbe48,0x3f553f0e,0xbf7b3e48,0xbf55bf0e,0xbf7b3e48,0xbf55bf0e,0x3f7bbe48,0x3f553f0e,0x3f7bbe48,0x3f553f0e,
0xbf5cbe16,0xbf7dbe79,0x3f5c3e16,0x3f7d3e79,0x3e793f4e,0x3f18bf04,0xbe79bf4e,0xbf183f04,0x3f04bf7d,0x3e163f78,0xbf043f7d,0xbe16bf78,0xbf783f18,0xbf4ebf5c,0x3f78bf18,0x3f4e3f5c,
0xbe95bef1,0xbf223dc9,0xbe95bef1,0xbf223dc9,0xbf753f62,0xbf46bf7f,0xbf753f62,0xbf46bf7f,0x3e953ef1,0x3f22bdc9,0x3e953ef1,0x3f22bdc9,0x3f75bf62,0x3f463f7f,0x3f75bf62,0x3f463f7f,
0x3edbbf3e,0x3d493edb,0xbedb3f3e,0xbd49bedb,0xbeacbd49,0xbf2cbeac,0x3eac3d49,0x3f2c3eac,0xbf673f2c,0xbf80bf67,0x3f67bf2c,0x3f803f67,0xbf713f80,0xbf3ebf71,0x3f71bf80,0x3f3e3f71,
0,0xbec43ec4,0,0xbec43ec4,0,0xbec43ec4,0,0xbec43ec4,0,0xbec43ec4,0,0xbec43ec4,0,0xbec43ec4,0,0xbec43ec4,
0x3f2c3eac,0x3eac3d49,0xbf2cbeac,0xbeacbd49,0x3f803f67,0x3f67bf2c,0xbf80bf67,0xbf673f2c,0x3f3e3f71,0x3f71bf80,0xbf3ebf71,0xbf713f80,0x3d493edb,0x3edbbf3e,0xbd49bedb,0xbedb3f3e,
0x3f7f3f22,0x3f62be95,0x3f7f3f22,0x3f62be95,0x3dc93f46,0x3ef1bf75,0x3dc93f46,0x3ef1bf75,0xbf7fbf22,0xbf623e95,0xbf7fbf22,0xbf623e95,0xbdc9bf46,0xbef13f75,0xbdc9bf46,0xbef13f75,
0x3f4e3f5c,0x3f78bf18,0xbf4ebf5c,0xbf783f18,0xbf7dbe79,0xbf5cbe16,0x3f7d3e79,0x3f5c3e16,0x3f18bf04,0x3e793f4e,0xbf183f04,0xbe79bf4e,0x3e163f78,0x3f04bf7d,0xbe16bf78,0xbf043f7d,
0x3e483f7b,0x3f0ebf55,0x3e483f7b,0x3f0ebf55,0xbe48bf7b,0xbf0e3f55,0xbe48bf7b,0xbf0e3f55,0x3e483f7b,0x3f0ebf55,0x3e483f7b,0x3f0ebf55,0xbe48bf7b,0xbf0e3f55,0xbe48bf7b,0xbf0e3f55,
0xbf043f7d,0xbe16bf78,0x3f04bf7d,0x3e163f78,0x3f78bf18,0x3f4e3f5c,0xbf783f18,0xbf4ebf5c,0xbf5cbe16,0xbf7dbe79,0x3f5c3e16,0x3f7d3e79,0x3e793f4e,0x3f18bf04,0xbe79bf4e,0xbf183f04,
0xbf753f62,0xbf46bf7f,0xbf753f62,0xbf46bf7f,0x3e953ef1,0x3f22bdc9,0x3e953ef1,0x3f22bdc9,0x3f75bf62,0x3f463f7f,0x3f75bf62,0x3f463f7f,0xbe95bef1,0xbf223dc9,0xbe95bef1,0xbf223dc9,
0xbf673f2c,0xbf80bf67,0x3f67bf2c,0x3f803f67,0xbf713f80,0xbf3ebf71,0x3f71bf80,0x3f3e3f71,0xbedb3f3e,0xbd49bedb,0x3edbbf3e,0x3d493edb,0x3eac3d49,0x3f2c3eac,0xbeacbd49,0xbf2cbeac,
0,0x3ec4bec4,0,0x3ec4bec4,0,0x3ec4bec4,0,0x3ec4bec4,0,0x3ec4bec4,0,0x3ec4bec4,0,0x3ec4bec4,0,0x3ec4bec4,
0xbf2cbeac,0xbeacbd49,0x3f2c3eac,0x3eac3d49,0xbf80bf67,0xbf673f2c,0x3f803f67,0x3f67bf2c,0xbf3ebf71,0xbf713f80,0x3f3e3f71,0x3f71bf80,0xbd49bedb,0xbedb3f3e,0x3d493edb,0x3edbbf3e,
0xbf7fbf22,0xbf623e95,0xbf7fbf22,0xbf623e95,0xbdc9bf46,0xbef13f75,0xbdc9bf46,0xbef13f75,0x3f7f3f22,0x3f62be95,0x3f7f3f22,0x3f62be95,0x3dc93f46,0x3ef1bf75,0x3dc93f46,0x3ef1bf75,
0xbf4ebf5c,0xbf783f18,0x3f4e3f5c,0x3f78bf18,0x3f7d3e79,0x3f5c3e16,0xbf7dbe79,0xbf5cbe16,0xbf183f04,0xbe79bf4e,0x3f18bf04,0x3e793f4e,0xbe16bf78,0xbf043f7d,0x3e163f78,0x3f04bf7d,
0xbe48bf7b,0xbf0e3f55,0xbe48bf7b,0xbf0e3f55,0x3e483f7b,0x3f0ebf55,0x3e483f7b,0x3f0ebf55,0xbe48bf7b,0xbf0e3f55,0xbe48bf7b,0xbf0e3f55,0x3e483f7b,0x3f0ebf55,0x3e483f7b,0x3f0ebf55,
0x3f04bf7d,0x3e163f78,0xbf043f7d,0xbe16bf78,0xbf783f18,0xbf4ebf5c,0x3f78bf18,0x3f4e3f5c,0x3f5c3e16,0x3f7d3e79,0xbf5cbe16,0xbf7dbe79,0xbe79bf4e,0xbf183f04,0x3e793f4e,0x3f18bf04,
0x3f75bf62,0x3f463f7f,0x3f75bf62,0x3f463f7f,0xbe95bef1,0xbf223dc9,0xbe95bef1,0xbf223dc9,0xbf753f62,0xbf46bf7f,0xbf753f62,0xbf46bf7f,0x3e953ef1,0x3f22bdc9,0x3e953ef1,0x3f22bdc9,
0x3f67bf2c,0x3f803f67,0xbf673f2c,0xbf80bf67,0x3f71bf80,0x3f3e3f71,0xbf713f80,0xbf3ebf71,0x3edbbf3e,0x3d493edb,0xbedb3f3e,0xbd49bedb,0xbeacbd49,0xbf2cbeac,0x3eac3d49,0x3f2c3eac,
0x3f800000,0x3f7fc38f,0x3f800000,0x3f6816a8,0x3f7f0e58,0x3f7de0b1,0x3f24d225,0x3e8586ce,0x3f7c3b28,0x3f7a1e84,0xbe2f10a2,0xbf121eb0,0x3f778bc5,0x3f748422,0xbf5d2d53,0xbf7eea9d,
0x3f800000,0x3f7eea9d,0x3f800000,0x3f628210,0x3f7baccd,0x3f764d97,0x3f10d3cd,0x3dee3876,0x3f6ed89e,0x3f655e0b,0xbeb8442a,0xbf40d0da,0x3f59f26a,0x3f4cae79,0xbf791298,0xbf77f110,
0x3f800000,0x3f7d7474,0x3f800000,0x3f5c61c7,0x3f75dec6,0x3f696591,0x3ef6e0cb,0xbcfb49ba,0x3f584853,0x3f42de29,0xbf08f59b,0xbf63f473,0x3f299415,0x3f0cead0,0xbf7f84ab,0xbf53fac3,
0x3f800000,0x3f7b61fc,0x3f800000,0x3f55b993,0x3f6db293,0x3f577026,0x3ec9b953,0xbe354098,0x3f396842,0x3f14b039,0xbf3085bb,0xbf796e4e,0x3ed53641,0x3e72b651,0xbf6ff573,0xbf173c07,
0x3f800000,0x3f78b47b,0x3f800000,0x3f4e8d90,0x3f633c5a,0x3f40d0da,0x3e9aa086,0xbea395c5,0x3f13682a,0x3ebb31a0,0xbf514d3d,0xbf7ff4e6,0x3e09cf86,0xbdd53db9,0xbf4bbbf8,0xbe919ddd,
0x3f800000,0x3f756d97,0x3f800000,0x3f46e22a,0x3f5695e5,0x3f26050a,0x3e541501,0xbee900b7,0x3ecf7bca,0x3e039502,0xbf6a09a7,0xbf772417,0xbe22abb6,0xbeddbe79,0xbf15f6d9,0x3d621469,
0x3f800000,0x3f718f57,0x3f800000,0x3f3ebc1b,0x3f47de65,0x3f07a136,0x3de1bc2e,0xbf14b039,0x3e605c13,0xbdee3876,0xbf79c79d,0xbf5f8327,0xbee0924f,0xbf36206c,0xbea68f12,0x3ec6d529,
0x3f800000,0x3f6d1c1d,0x3f800000,0x3f36206c,0x3f373a23,0x3ecc9b8b,0x3c490e90,0xbf31a81d,0x3cc90ab0,0xbeb554ec,0xbf7fec43,0xbf3a7ca4,0xbf2e3bde,0xbf6816a8,0xbd16c32c,0x3f2d1469,
0,0x3d2fe007,0,0x3ed8106b,0x3dafb680,0x3e039502,0x3f43e200,0x3f772417,0x3e2f10a2,0x3e5a3997,0x3f7c3b28,0x3f5233c6,0x3e827dc0,0x3e97a117,0x3f00e7e4,0x3dbc3ac3,
0,0x3dbc3ac3,0,0x3eee9479,0x3e3b6ecf,0x3e8b9507,0x3f531849,0x3f7e4323,0x3eb8442a,0x3ee363fa,0x3f6ed89e,0x3f286605,0x3f064b82,0x3f19c200,0x3e6c9a7f,0xbe7ee6e1,
0,0x3e1008b7,0,0x3f0242b1,0x3e8e9a22,0x3ed25a09,0x3f604621,0x3f7fe129,0x3f08f59b,0x3f26050a,0x3f584853,0x3ee900b7,0x3f3fc767,0x3f55b993,0xbd7b2b74,0xbf0f8784,
0,0x3e419b37,0,0x3f0cead0,0x3ebe1d4a,0x3f0a48ad,0x3f6b4b0c,0x3f7bf531,0x3f3085bb,0x3f5064af,0x3f396842,0x3e667c66,0x3f68bf3c,0x3f78b47b,0xbeb263ef,0xbf4e8d90,
0,0x3e72b651,0,0x3f173c07,0x3eebcbbb,0x3f286605,0x3f740bdd,0x3f7294f8,0x3f514d3d,0x3f6e46be,0x3f13682a,0xbc96c9b6,0x3f7dabcc,0x3f7e9bc9,0xbf1b02c6,0xbf756d97,
0,0x3e919ddd,0,0x3f212ff9,0x3f0b9a6b,0x3f42de29,0x3f7a7302,0x3f63f473,0x3f6a09a7,0x3f7de0b1,0x3ecf7bca,0xbe8586ce,0x3f7cbfc9,0x3f66becc,0xbf4f7a1f,0xbf7f9c18,
0,0x3ea986c4,0,0x3f2ac082,0x3f1ff6cb,0x3f591e6a,0x3f7e70b0,0x3f5064af,0x3f79c79d,0x3f7e4323,0x3e605c13,0xbef9a02d,0x3f660f88,0x3f33e7bc,0xbf721352,0xbf6be858,
0,0x3ec1071e,0,0x3f33e7bc,0x3f32c8c9,0x3f6aab7b,0x3f7ffb11,0x3f385216,0x3f7fec43,0x3f6f6830,0x3cc90ab0,0xbf2f61a5,0x3f3b8f3b,0x3ed8106b,0xbf7fd397,0xbf3ca003,
0x354ccccd,0x354ccccd,0x354ccccd,0x354ccccd,0x354ccccd,0x354ccccd,0x354ccccd,0x354ccccd,0x354ccccd,0x354ccccd,0x354ccccd,0x354ccccd,0x354ccccd,0x354ccccd,0x354ccccd,0x354ccccd,
0x3549c8ed,0x353f13b1,0xb40c0d4f,0xb49369bb,0x352d06a9,0x35145368,0xb4db2291,0xb50d37c9,0x34ebd9dd,0x34a5fca2,0xb52770fe,0xb53b3aec,0x34337cdc,0x32a0d559,0xb547d2e4,0xb54cbd02,
0x354c9c72,0x354beee4,0x3539abba,0x353534da,0x354ac390,0x35491b30,0x35304e38,0x352afadc,0x3546f6c8,0x354457ac,0x35253e0d,0x351f1b54,0x35413f79,0x353db017,0x3518967c,0x3511b389,
0x3548186a,0x35377e6f,0xb4e9cab3,0xb51a40ae,0x351be4ed,0x34ede6c2,0xb5365d28,0xb5478b72,0x3495c14d,0x33d28804,0xb54cc3eb,0xb545b679,0xb3be9392,0xb49110bd,0xb532cf52,0xb5153084,
0x354c0b7a,0x3549570a,0x3503db51,0x34e7b948,0x3544b238,0x353e2876,0x34c580a2,0x34a1610f,0x3535c9e1,0x352bab1e,0x3477673d,0x3429aa67,0x351fe51e,0x351294e9,0x33b4968b,0x3220d873,
0x3546096a,0x352e5b88,0xb530f10f,0xb5474213,0x3507a9aa,0x34aa91ce,0xb54c6a23,0xb53ff78f,0x33dc7f3e,0xb40222f8,0xb522fcc6,0xb4eff15b,0xb4b3a83f,0xb50b6318,0xb4853f42,0xb2f13846,
0x354b1a27,0x35450adf,0x3455a47e,0x33be9392,0x353ab7a7,0x352c59b8,0xb2c907c8,0xb411007a,0x351a40ae,0x3504d0d5,0xb482de37,0xb4ba66f9,0x34d901f0,0x34a3afa2,0xb4ede6c2,0xb50e2017,
0x35439ce8,0x3523bec8,0xb54beee4,0xb5465a74,0x34e177b4,0x34422b74,0xb5299568,0xb4f1f9a5,0xb3aa97c7,0xb4b1652e,0xb468fc95,0x3334dd20,0xb511b389,0xb539abba,0x349f10ee,0x350a76bb,
0,0,0,0,0,0,0,0,0,0,0,0,0,0,0,0,
0x340c0d4f,0x349369bb,0x3549c8ed,0x353f13b1,0x34db2291,0x350d37c9,0x352d06a9,0x35145368,0x352770fe,0x353b3aec,0x34ebd9dd,0x34a5fca2,0x3547d2e4,0x354cbd02,0x34337cdc,0x32a0d559,
0x330cb338,0x33969569,0x34acd9f0,0x34bedd2d,0x33e67457,0x341ae293,0x34d06ab5,0x34e177b4,0x34422b74,0x3468fc95,0x34f1f9a5,0x3500f32d,0x34879f03,0x349a6c18,0x35089a01,0x350fec97,
0x342e9479,0x34b5e995,0x3528296b,0x3506b804,0x3504d0d5,0x3526b6f3,0x34ba66f9,0x34386384,0x353e9eff,0x354b1a27,0xb27142bd,0xb455a47e,0x354b68e9,0x353f868d,0xb4c7b357,0xb50c4e1d,
0x338c9200,0x3415f23f,0x351cb4cd,0x3528e03a,0x346429d0,0x3498176e,0x35336b4e,0x353c3c09,0x34bca2fc,0x34df5d78,0x35433cb1,0x35485c01,0x34fff144,0x350f0707,0x354b8d5a,0x354cc8da,
0x3450c934,0x34d6df37,0x34ce3fd4,0x343d4866,0x35196c52,0x353a3296,0xb348ef90,0xb48eb659,0x354aefd6,0x354a3307,0xb4f8046f,0xb525fb4c,0x35380c6c,0x35160c2f,0xb541a90f,0xb54ca946,
0x33d28804,0x345f54d8,0x3545b679,0x354b68e9,0x34a84807,0x34dd4116,0x354cb421,0x354990f4,0x3506b804,0x351be4ed,0x354210c7,0x35365d28,0x352db1ef,0x353bbc62,0x3526b6f3,0x351374de,
0x34729b58,0x34f60334,0x33969569,0xb44bebe7,0x352afadc,0x3546f6c8,0xb4e5a5a1,0xb5253e0d,0x354bafd4,0x353898a3,0xb54457ac,0xb54c7ce0,0x350fec97,0x34acd9f0,0xb53cb9e0,0xb516e669,
0x3f80,0x3f80,0x3f7f3dc9,0x3f7f3dc9,0x3eb83f6f,0xbeb8bf6f,0x3f77be89,0xbf773e89,0x3f2c3f3e,0x3f2c3f3e,0x3f4ebf18,0x3f4ebf18,0x3f653ee6,0xbf65bee6,0x3f09bf58,0xbf093f58,
0x3f80,0x3f80,0x3dc9bf7f,0x3dc9bf7f,0x3f313f39,0xbf31bf39,0xbf1dbf4a,0x3f1d3f4a,0x3f803d49,0x3f803d49,0xbf7dbe16,0xbf7dbe16,0x3f42bf27,0xbf423f27,0xbf513f13,0x3f51bf13,
0x3f80,0x3f80,0xbf7fbdc9,0xbf7fbdc9,0x3f6a3ecf,0xbf6abecf,0xbefc3f5f,0x3efcbf5f,0x3f3ebf2c,0x3f3ebf2c,0x3f183f4e,0x3f183f4e,0xbea1bf73,0x3ea13f73,0x3f7abe60,0xbf7a3e60,
0x3f80,0x3f80,0xbdc93f7f,0xbdc93f7f,0x3f803cc9,0xbf80bcc9,0x3f7e3dfb,0xbf7ebdfb,0x3d49bf80,0x3d49bf80,0x3e16bf7d,0x3e16bf7d,0xbf7fbd97,0x3f7f3d97,0xbf7cbe2f,0x3f7c3e2f,
0x3f80,0x3f80,0x3f7f3dc9,0x3f7f3dc9,0x3f6fbeb8,0xbf6f3eb8,0xbe89bf77,0x3e893f77,0xbf2cbf3e,0xbf2cbf3e,0xbf4e3f18,0xbf4e3f18,0xbee63f65,0x3ee6bf65,0x3f583f09,0xbf58bf09,
0x3f80,0x3f80,0x3dc9bf7f,0x3dc9bf7f,0x3f39bf31,0xbf393f31,0xbf4a3f1d,0x3f4abf1d,0xbf80bd49,0xbf80bd49,0x3f7d3e16,0x3f7d3e16,0x3f273f42,0xbf27bf42,0xbf13bf51,0x3f133f51,
0x3f80,0x3f80,0xbf7fbdc9,0xbf7fbdc9,0x3ecfbf6a,0xbecf3f6a,0x3f5f3efc,0xbf5fbefc,0xbf3e3f2c,0xbf3e3f2c,0xbf18bf4e,0xbf18bf4e,0x3f73bea1,0xbf733ea1,0x3e603f7a,0xbe60bf7a,
0x3f80,0x3f80,0xbdc93f7f,0xbdc93f7f,0x3cc9bf80,0xbcc93f80,0x3dfbbf7e,0xbdfb3f7e,0xbd493f80,0xbd493f80,0xbe163f7d,0xbe163f7d,0x3d97bf7f,0xbd973f7f,0x3e2fbf7c,0xbe2f3f7c,
0x3e48bf7b,0x3e48bf7b,0xbf75be95,0xbf75be95,0xbe2fbf7c,0x3e2f3f7c,0xbf7f3d97,0x3f7fbd97,0xbf04bf5c,0xbf04bf5c,0xbf673edb,0xbf673edb,0xbf4abf1d,0x3f4a3f1d,0xbf313f39,0x3f31bf39,
0xbe483f7b,0xbe483f7b,0x3e95bf75,0x3e95bf75,0x3f093f58,0xbf09bf58,0xbee6bf65,0x3ee63f65,0x3f783e79,0x3f783e79,0xbf71beac,0xbf71beac,0x3f5fbefc,0xbf5f3efc,0xbf6a3ecf,0x3f6abecf,
0x3e48bf7b,0x3e48bf7b,0x3f753e95,0x3f753e95,0xbf51bf13,0x3f513f13,0x3f27bf42,0xbf273f42,0xbf5c3f04,0xbf5c3f04,0xbedbbf67,0xbedbbf67,0x3dfb3f7e,0xbdfbbf7e,0xbf803cc9,0x3f80bcc9,
0xbe483f7b,0xbe483f7b,0xbe953f75,0xbe953f75,0x3f7a3e60,0xbf7abe60,0x3f733ea1,0xbf73bea1,0x3e79bf78,0x3e79bf78,0x3eacbf71,0x3eacbf71,0xbf77be89,0x3f773e89,0xbf6fbeb8,0x3f6f3eb8,
0x3e48bf7b,0x3e48bf7b,0xbf75be95,0xbf75be95,0xbf7c3e2f,0x3f7cbe2f,0x3d973f7f,0xbd97bf7f,0x3f043f5c,0x3f043f5c,0x3f67bedb,0x3f67bedb,0x3f1dbf4a,0xbf1d3f4a,0xbf39bf31,0x3f393f31,
0xbe483f7b,0xbe483f7b,0x3e95bf75,0x3e95bf75,0x3f58bf09,0xbf583f09,0xbf653ee6,0x3f65bee6,0xbf78be79,0xbf78be79,0x3f713eac,0x3f713eac,0x3efc3f5f,0xbefcbf5f,0xbecfbf6a,0x3ecf3f6a,
0x3e48bf7b,0x3e48bf7b,0x3f753e95,0x3f753e95,0xbf133f51,0x3f13bf51,0xbf42bf27,0x3f423f27,0x3f5cbf04,0x3f5cbf04,0x3edb3f67,0x3edb3f67,0xbf7e3dfb,0x3f7ebdfb,0xbcc9bf80,0x3cc93f80,
0xbe483f7b,0xbe483f7b,0xbe953f75,0xbe953f75,0x3e60bf7a,0xbe603f7a,0x3ea1bf73,0xbea13f73,0xbe793f78,0xbe793f78,0xbeac3f71,0xbeac3f71,0x3e89bf77,0xbe893f77,0x3eb8bf6f,0xbeb83f6f,
0x3f800000,0x3f800000,0x3dc9bf7f,0x3dc9bf7f,0x3f6fbeb8,0xbf6f3eb8,0xbe89bf77,0x3e893f77,0x3f3ebf2c,0x3f3ebf2c,0xbf18bf4e,0xbf18bf4e,0x3ee6bf65,0xbee63f65,0xbf58bf09,0x3f583f09,
0x3f800000,0x3f800000,0xbf7fbdc9,0xbf7fbdc9,0x3f39bf31,0xbf393f31,0xbf4a3f1d,0x3f4abf1d,0x3d49bf80,0x3d49bf80,0xbe163f7d,0xbe163f7d,0xbf27bf42,0x3f273f42,0x3f133f51,0xbf13bf51,
0x3f800000,0x3f800000,0xbdc93f7f,0xbdc93f7f,0x3ecfbf6a,0xbecf3f6a,0x3f5f3efc,0xbf5fbefc,0xbf2cbf3e,0xbf2cbf3e,0x3f4ebf18,0x3f4ebf18,0xbf733ea1,0x3f73bea1,0xbe60bf7a,0x3e603f7a,
0x3f800000,0x3f800000,0x3f7f3dc9,0x3f7f3dc9,0x3cc9bf80,0xbcc93f80,0x3dfbbf7e,0xbdfb3f7e,0xbf80bd49,0xbf80bd49,0xbf7dbe16,0xbf7dbe16,0xbd973f7f,0x3d97bf7f,0xbe2f3f7c,0x3e2fbf7c,
0x3f800000,0x3f800000,0x3dc9bf7f,0x3dc9bf7f,0xbeb8bf6f,0x3eb83f6f,0xbf773e89,0x3f77be89,0xbf3e3f2c,0xbf3e3f2c,0x3f183f4e,0x3f183f4e,0x3f653ee6,0xbf65bee6,0x3f09bf58,0xbf093f58,
0x3f800000,0x3f800000,0xbf7fbdc9,0xbf7fbdc9,0xbf31bf39,0x3f313f39,0x3f1d3f4a,0xbf1dbf4a,0xbd493f80,0xbd493f80,0x3e16bf7d,0x3e16bf7d,0x3f42bf27,0xbf423f27,0xbf513f13,0x3f51bf13,
0x3f800000,0x3f800000,0xbdc93f7f,0xbdc93f7f,0xbf6abecf,0x3f6a3ecf,0x3efcbf5f,0xbefc3f5f,0x3f2c3f3e,0x3f2c3f3e,0xbf4e3f18,0xbf4e3f18,0xbea1bf73,0x3ea13f73,0x3f7abe60,0xbf7a3e60,
0x3f800000,0x3f800000,0x3f7f3dc9,0x3f7f3dc9,0xbf80bcc9,0x3f803cc9,0xbf7ebdfb,0x3f7e3dfb,0x3f803d49,0x3f803d49,0x3f7d3e16,0x3f7d3e16,0xbf7fbd97,0x3f7f3d97,0xbf7cbe2f,0x3f7c3e2f,
0xbf7bbe48,0xbf7bbe48,0xbe953f75,0xbe953f75,0xbf7c3e2f,0x3f7cbe2f,0x3d973f7f,0xbd97bf7f,0xbf5c3f04,0xbf5c3f04,0x3edb3f67,0x3edb3f67,0xbf1d3f4a,0x3f1dbf4a,0x3f393f31,0xbf39bf31,
0x3f7b3e48,0x3f7b3e48,0xbf75be95,0xbf75be95,0x3f58bf09,0xbf583f09,0xbf653ee6,0x3f65bee6,0x3e79bf78,0x3e79bf78,0xbeac3f71,0xbeac3f71,0xbefcbf5f,0x3efc3f5f,0x3ecf3f6a,0xbecfbf6a,
0xbf7bbe48,0xbf7bbe48,0x3e95bf75,0x3e95bf75,0xbf133f51,0x3f13bf51,0xbf42bf27,0x3f423f27,0x3f043f5c,0x3f043f5c,0xbf673edb,0xbf673edb,0x3f7ebdfb,0xbf7e3dfb,0x3cc93f80,0xbcc9bf80,
0x3f7b3e48,0x3f7b3e48,0x3f753e95,0x3f753e95,0x3e60bf7a,0xbe603f7a,0x3ea1bf73,0xbea13f73,0xbf78be79,0xbf78be79,0xbf71beac,0xbf71beac,0xbe893f77,0x3e89bf77,0xbeb83f6f,0x3eb8bf6f,
0xbf7bbe48,0xbf7bbe48,0xbe953f75,0xbe953f75,0x3e2f3f7c,0xbe2fbf7c,0x3f7fbd97,0xbf7f3d97,0x3f5cbf04,0x3f5cbf04,0xbedbbf67,0xbedbbf67,0xbf4abf1d,0x3f4a3f1d,0xbf313f39,0x3f31bf39,
0x3f7b3e48,0x3f7b3e48,0xbf75be95,0xbf75be95,0xbf09bf58,0x3f093f58,0x3ee63f65,0xbee6bf65,0xbe793f78,0xbe793f78,0x3eacbf71,0x3eacbf71,0x3f5fbefc,0xbf5f3efc,0xbf6a3ecf,0x3f6abecf,
0xbf7bbe48,0xbf7bbe48,0x3e95bf75,0x3e95bf75,0x3f513f13,0xbf51bf13,0xbf273f42,0x3f27bf42,0xbf04bf5c,0xbf04bf5c,0x3f67bedb,0x3f67bedb,0x3dfb3f7e,0xbdfbbf7e,0xbf803cc9,0x3f80bcc9,
0x3f7b3e48,0x3f7b3e48,0x3f753e95,0x3f753e95,0xbf7abe60,0x3f7a3e60,0xbf73bea1,0x3f733ea1,0x3f783e79,0x3f783e79,0x3f713eac,0x3f713eac,0xbf77be89,0x3f773e89,0xbf6fbeb8,0x3f6f3eb8,
0x3f803f80,0x3f7bbf7b,0x3f803f80,0x3f7bbf7b,0x3f803f80,0x3f7bbf7b,0x3f803f80,0x3f7bbf7b,0x3f803f80,0x3f7bbf7b,0x3f803f80,0x3f7bbf7b,0x3f803f80,0x3f7bbf7b,0x3f803f80,0x3f7bbf7b,
0x3f393f6f,0x3f58bf7c,0xbf39bf6f,0xbf583f7c,0x3cc93ecf,0x3e60bf13,0xbcc9becf,0xbe603f13,0xbf31beb8,0xbf093e2f,0x3f313eb8,0x3f09be2f,0xbf80bf6a,0xbf7a3f51,0x3f803f6a,0x3f7abf51,
0x3d493f3e,0x3e79bf5c,0x3d493f3e,0x3e79bf5c,0xbf80bf2c,0xbf783f04,0xbf80bf2c,0xbf783f04,0xbd49bf3e,0xbe793f5c,0xbd49bf3e,0xbe793f5c,0x3f803f2c,0x3f78bf04,0x3f803f2c,0x3f78bf04,
0xbf273ee6,0xbefcbf1d,0x3f27bee6,0x3efc3f1d,0xbd97bf73,0xbe893f7e,0x3d973f73,0x3e89bf7e,0x3f423f65,0x3f5fbf4a,0xbf42bf65,0xbf5f3f4a,0xbf7fbea1,0xbf773dfb,0x3f7f3ea1,0x3f77bdfb,
0xbf7f3dc9,0xbf75be95,0xbf7f3dc9,0xbf75be95,0x3f7fbdc9,0x3f753e95,0x3f7fbdc9,0x3f753e95,0xbf7f3dc9,0xbf75be95,0xbf7f3dc9,0xbf75be95,0x3f7fbdc9,0x3f753e95,0x3f7fbdc9,0x3f753e95,
0xbf4abe89,0xbf653d97,0x3f4a3e89,0x3f65bd97,0x3dfb3f5f,0x3ea1bf42,0xbdfbbf5f,0xbea13f42,0x3f1dbf77,0x3ee63f7f,0xbf1d3f77,0xbee6bf7f,0xbf7e3efc,0xbf73bf27,0x3f7ebefc,0x3f733f27,
0xbe16bf18,0xbeac3edb,0xbe16bf18,0xbeac3edb,0xbf7d3f4e,0xbf71bf67,0xbf7d3f4e,0xbf71bf67,0x3e163f18,0x3eacbedb,0x3e163f18,0x3eacbedb,0x3f7dbf4e,0x3f713f67,0x3f7dbf4e,0x3f713f67,
0x3f13bf58,0x3ecf3f39,0xbf133f58,0xbecfbf39,0xbe2fbe60,0xbeb83cc9,0x3e2f3e60,0x3eb8bcc9,0xbf513f09,0xbf6abf31,0x3f51bf09,0x3f6a3f31,0xbf7c3f7a,0xbf6fbf80,0x3f7cbf7a,0x3f6f3f80,
0,0xbe483e48,0,0xbe483e48,0,0xbe483e48,0,0xbe483e48,0,0xbe483e48,0,0xbe483e48,0,0xbe483e48,0,0xbe483e48,
0x3f313eb8,0x3f09be2f,0xbf31beb8,0xbf093e2f,0x3f803f6a,0x3f7abf51,0xbf80bf6a,0xbf7a3f51,0x3f393f6f,0x3f58bf7c,0xbf39bf6f,0xbf583f7c,0x3cc93ecf,0x3e60bf13,0xbcc9becf,0xbe603f13,
0x3f803f2c,0x3f78bf04,0x3f803f2c,0x3f78bf04,0x3d493f3e,0x3e79bf5c,0x3d493f3e,0x3e79bf5c,0xbf80bf2c,0xbf783f04,0xbf80bf2c,0xbf783f04,0xbd49bf3e,0xbe793f5c,0xbd49bf3e,0xbe793f5c,
0x3f423f65,0x3f5fbf4a,0xbf42bf65,0xbf5f3f4a,0xbf7fbea1,0xbf773dfb,0x3f7f3ea1,0x3f77bdfb,0x3f27bee6,0x3efc3f1d,0xbf273ee6,0xbefcbf1d,0x3d973f73,0x3e89bf7e,0xbd97bf73,0xbe893f7e,
0x3dc93f7f,0x3e95bf75,0x3dc93f7f,0x3e95bf75,0xbdc9bf7f,0xbe953f75,0xbdc9bf7f,0xbe953f75,0x3dc93f7f,0x3e95bf75,0x3dc93f7f,0x3e95bf75,0xbdc9bf7f,0xbe953f75,0xbdc9bf7f,0xbe953f75,
0xbf1d3f77,0xbee6bf7f,0x3f1dbf77,0x3ee63f7f,0x3f7ebefc,0x3f733f27,0xbf7e3efc,0xbf73bf27,0xbf4abe89,0xbf653d97,0x3f4a3e89,0x3f65bd97,0x3dfb3f5f,0x3ea1bf42,0xbdfbbf5f,0xbea13f42,
0xbf7d3f4e,0xbf71bf67,0xbf7d3f4e,0xbf71bf67,0x3e163f18,0x3eacbedb,0x3e163f18,0x3eacbedb,0x3f7dbf4e,0x3f713f67,0x3f7dbf4e,0x3f713f67,0xbe16bf18,0xbeac3edb,0xbe16bf18,0xbeac3edb,
0xbf513f09,0xbf6abf31,0x3f51bf09,0x3f6a3f31,0xbf7c3f7a,0xbf6fbf80,0x3f7cbf7a,0x3f6f3f80,0xbf133f58,0xbecfbf39,0x3f13bf58,0x3ecf3f39,0x3e2f3e60,0x3eb8bcc9,0xbe2fbe60,0xbeb83cc9,
0,0x3e48be48,0,0x3e48be48,0,0x3e48be48,0,0x3e48be48,0,0x3e48be48,0,0x3e48be48,0,0x3e48be48,0,0x3e48be48,
0xbf31beb8,0xbf093e2f,0x3f313eb8,0x3f09be2f,0xbf80bf6a,0xbf7a3f51,0x3f803f6a,0x3f7abf51,0xbf39bf6f,0xbf583f7c,0x3f393f6f,0x3f58bf7c,0xbcc9becf,0xbe603f13,0x3cc93ecf,0x3e60bf13,
0xbf80bf2c,0xbf783f04,0xbf80bf2c,0xbf783f04,0xbd49bf3e,0xbe793f5c,0xbd49bf3e,0xbe793f5c,0x3f803f2c,0x3f78bf04,0x3f803f2c,0x3f78bf04,0x3d493f3e,0x3e79bf5c,0x3d493f3e,0x3e79bf5c,
0xbf42bf65,0xbf5f3f4a,0x3f423f65,0x3f5fbf4a,0x3f7f3ea1,0x3f77bdfb,0xbf7fbea1,0xbf773dfb,0xbf273ee6,0xbefcbf1d,0x3f27bee6,0x3efc3f1d,0xbd97bf73,0xbe893f7e,0x3d973f73,0x3e89bf7e,
0xbdc9bf7f,0xbe953f75,0xbdc9bf7f,0xbe953f75,0x3dc93f7f,0x3e95bf75,0x3dc93f7f,0x3e95bf75,0xbdc9bf7f,0xbe953f75,0xbdc9bf7f,0xbe953f75,0x3dc93f7f,0x3e95bf75,0x3dc93f7f,0x3e95bf75,
0x3f1dbf77,0x3ee63f7f,0xbf1d3f77,0xbee6bf7f,0xbf7e3efc,0xbf73bf27,0x3f7ebefc,0x3f733f27,0x3f4a3e89,0x3f65bd97,0xbf4abe89,0xbf653d97,0xbdfbbf5f,0xbea13f42,0x3dfb3f5f,0x3ea1bf42,
0x3f7dbf4e,0x3f713f67,0x3f7dbf4e,0x3f713f67,0xbe16bf18,0xbeac3edb,0xbe16bf18,0xbeac3edb,0xbf7d3f4e,0xbf71bf67,0xbf7d3f4e,0xbf71bf67,0x3e163f18,0x3eacbedb,0x3e163f18,0x3eacbedb,
0x3f51bf09,0x3f6a3f31,0xbf513f09,0xbf6abf31,0x3f7cbf7a,0x3f6f3f80,0xbf7c3f7a,0xbf6fbf80,0x3f13bf58,0x3ecf3f39,0xbf133f58,0xbecfbf39,0xbe2fbe60,0xbeb83cc9,0x3e2f3e60,0x3eb8bcc9,
0x3f800000,0x3f7fba9e,0x3f800000,0x3f67c187,0x3f7eea9d,0x3f7d906e,0x3f239da9,0x3e80f8c0,0x3f7baccd,0x3f7940c0,0xbe3b6ecf,0xbf1553b7,0x3f764d97,0x3f72d4eb,0xbf5f8327,0xbf7f5ce9,
0x3f800000,0x3f7ed7d4,0x3f800000,0x3f62241a,0x3f7b61fc,0x3f75a67b,0x3f0f8784,0x3ddb7d37,0x3f6db293,0x3f6398ac,0xbebe1d4a,0xbf436051,0x3f577026,0x3f495521,0xbf7a1e84,0xbf76841b,
0x3f800000,0x3f7d57de,0x3f800000,0x3f5bfb34,0x3f756d97,0x3f686b39,0x3ef41f07,0xbd2351cb,0x3f5695e5,0x3f404c5c,0xbf0b9a6b,0xbf65b710,0x3f26050a,0x3f084b92,0xbf7f2f9d,0xbf50d937,
0x3f800000,0x3f7b3bab,0x3f800000,0x3f554aa4,0x3f6d1c1d,0x3f5627fe,0x3ec6d529,0xbe3e853e,0x3f373a23,0x3f11796b,0xbf32c8c9,0xbf7a4910,0x3ecc9b8b,0x3e5d4b1a,0xbf6e46be,0xbf12c39a,
0x3f800000,0x3f788486,0x3f800000,0x3f4e1689,0x3f628210,0x3f3f41fc,0x3e97a117,0xbea80b1f,0x3f10d3cd,0x3eb3dca5,0xbf531849,0xbf7fdaaf,0x3dee3876,0xbe007745,0xbf48d8b3,0xbe870ada,
0x3f800000,0x3f75341d,0x3f800000,0x3f466354,0x3f55b993,0x3f24381a,0x3e4dee60,0xbeed3063,0x3ec9b953,0x3de7fa9a,0xbf6b4b0c,0xbf76167a,0xbe354098,0xbee79a5d,0xbf121eb0,0x3d9cecf9,
0x3f800000,0x3f714c7a,0x3f800000,0x3f3e35c5,0x3f46e22a,0x3f05a02c,0x3dd53db9,0xbf16999f,0x3e541501,0xbe06b26e,0xbf7a7302,0xbf5d924d,0xbee900b7,0xbf39f2ac,0xbe9d9e78,0x3ed0eb2a,
0x3f800000,0x3f6cd007,0x3f800000,0x3f3592e7,0x3f36206c,0x3ec8477c,0x3bc90f88,0xbf33587a,0x3c490e90,0xbebca7af,0xbf7ffb11,0xbf37c655,0xbf31a81d,0xbf6a5ad9,0xbc96c9b6,0x3f311722,
0,0x3d3c6dd5,0,0x3ed97cb9,0x3dbc3ac3,0x3e0cec4a,0x3f44e3f5,0x3f77beb7,0x3e3b6ecf,0x3e698bba,0x3f7baccd,0x3f4fefa8,0x3e8b9507,0x3ea21887,0x3ef9a02d,0x3d9064b4,
0,0x3dc27c39,0,0x3eeff7fb,0x3e419b37,0x3e901c2c,0x3f53fac3,0x3f7e868b,0x3ebe1d4a,0x3eea6681,0x3f6db293,0x3f256bcb,0x3f0a48ad,0x3f1e1e22,0x3e5a3997,0xbe8a11f7,
0,0x3e1324ca,0,0x3f02ef9f,0x3e919ddd,0x3ed6a399,0x3f6106f2,0x3f7fcbe2,0x3f0b9a6b,0x3f28fd41,0x3f5695e5,0x3ee1fb6a,0x3f42de29,0x3f58b3a1,0xbda3308c,0xbf140c5f,
0,0x3e44b0b9,0,0x3f0d9281,0x3ec1071e,0x3f0c42c9,0x3f6be858,0x3f7b87b2,0x3f32c8c9,0x3f52a649,0x3f373a23,0x3e57278f,0x3f6aab7b,0x3f79f35e,0xbebb31a0,0xbf51c0c2,
0,0x3e75c35a,0,0x3f17de12,0x3eee9479,0x3f2a2a80,0x3f748422,0x3f71d19f,0x3f531849,0x3f6faf1b,0x3f10d3cd,0xbd0a342f,0x3f7e4323,0x3f7dfa38,0xbf1ebc12,0xbf76ef5b,
0,0x3e931f35,0,0x3f21cbfb,0x3f0cead0,0x3f446337,0x3f7ac516,0x3f62df7b,0x3f6b4b0c,0x3f7e5a38,0x3ec9b953,0xbe8d17c0,0x3f7bf531,0x3f644fac,0xbf5233c6,0xbf7f3f54,
0,0x3eab0201,0,0x3f2b561b,0x3f212ff9,0x3f5a5ba0,0x3f7e9bc9,0x3f4f0417,0x3f7a7302,0x3f7dc68c,0x3e541501,0xbf003a06,0x3f63f473,0x3f2ff3e6,0xbf73913f,0xbf69b7e4,
0,0x3ec27b55,0,0x3f34768f,0x3f33e7bc,0x3f6b99fb,0x3f7ffec4,0x3f36ad7f,0x3f7ffb11,0x3f6dfcf2,0x3c490e90,0xbf3238aa,0x3f385216,0x3ece0bea,0xbf7ff4e6,0xbf38dd65,
0x354ccccd,0x354ccccd,0x354ccccd,0x354ccccd,0x354ccccd,0x354ccccd,0x354ccccd,0x354ccccd,0x354ccccd,0x354ccccd,0x354ccccd,0x354ccccd,0x354ccccd,0x354ccccd,0x354ccccd,0x354ccccd,
0x3549570a,0x353e2876,0xb415f23f,0xb498176e,0x352bab1e,0x351294e9,0xb4df5d78,0xb50f0707,0x34e7b948,0x34a1610f,0xb528e03a,0xb53c3c09,0x3429aa67,0x3220d873,0xb5485c01,0xb54cc8da,
0x354c954b,0x354bdfdd,0x3539679f,0x3534e9ae,0x354aacb2,0x3548fc89,0x352ffc2a,0x352aa21d,0x3546d06b,0x354429b0,0x3524ded4,0x351eb5dd,0x354109fb,0x353d7339,0x35182b04,0x35114253,
0x35476700,0x353613bd,0xb4eeec58,0xb51c4d0e,0x3519d6b0,0x34e8c245,0xb537c5a7,0xb5483a73,0x348fe3b7,0x33b99548,0xb54caef3,0xb544dec8,0xb3d783e3,0xb496ec8c,0xb53141d7,0xb5130511,
0x354beee4,0x35491b30,0x3502e487,0x34e5a5a1,0x354457ac,0x353db017,0x34c34c06,0x349f10ee,0x353534da,0x352afadc,0x34729b58,0x3424beb3,0x351f1b54,0x3511b389,0x33aa97c7,0x31a0d93a,
0x35450adf,0x352c59b8,0xb532cf52,0xb548186a,0x3504d0d5,0x34a3afa2,0xb54c2618,0xb53e9eff,0x33be9392,0xb411007a,0xb520ad5c,0xb4e9cab3,0xb4ba66f9,0xb50e2017,0xb47c30c0,0xb27142bd,
0x354ad9f2,0x3544852f,0x344e5acd,0x33af9760,0x3539ef61,0x352b5332,0xb302a7d6,0xb4186a98,0x35190197,0x35036014,0xb4866f4c,0xb4bdc04f,0x34d5cd14,0x34a03930,0xb4f0f5cb,0xb50f79fb,
0x354243ef,0x352110e7,0xb54c4a54,0xb545367c,0x34da1284,0x343108e1,0xb527142c,0xb4ead291,0xb3cd8ba2,0xb4b9484b,0xb458115e,0x337b14c1,0xb514c224,0xb53b7be1,0x34a72288,0x350dac1c,
0,0,0,0,0,0,0,0,0,0,0,0,0,0,0,0,
0x3415f23f,0x3498176e,0x3549570a,0x353e2876,0x34df5d78,0x350f0707,0x352bab1e,0x351294e9,0x3528e03a,0x353c3c09,0x34e7b948,0x34a1610f,0x35485c01,0x354cc8da,0x3429aa67,0x3220d873,
0x3316be44,0x339b9694,0x34adfd61,0x34bff996,0x33eb6e11,0x341d5a2e,0x34d17f65,0x34e28401,0x34449c48,0x346b6521,0x34f2fcea,0x35016ffc,0x3488ce67,0x349b95de,0x350911af,0x35105ed9,
0x343ad62f,0x34bb8534,0x35265953,0x3504563c,0x35073101,0x35288507,0x34b4c922,0x342c1fa5,0x353fbf49,0x354b7b60,0xb2dd204b,0xb461bf99,0x354b053d,0x353e63f5,0xb4cd29a4,0xb50e93bb,
0x33969569,0x341ae293,0x351d832a,0x35299568,0x3468fc95,0x349a6c18,0x3534058e,0x353cb9e0,0x34bedd2d,0x34e177b4,0x35439ce8,0x35489dab,0x3500f32d,0x350fec97,0x354bafd4,0x354ccbd0,
0x345f54d8,0x34dd4116,0x34c7b357,0x342e9479,0x351be4ed,0x353bbc62,0xb3828d3d,0xb495c14d,0x354b68e9,0x354990f4,0xb4fdf9b6,0xb528296b,0x35365d28,0x351374de,0xb542da99,0xb54cc3eb,
0x33e17a10,0x3466937a,0x3546322c,0x354b9ed5,0x34abb614,0x34e06adb,0x354ca31b,0x3549395b,0x35082200,0x351d1c2c,0x35417480,0x35357f95,0x352eafb3,0x353c7b2f,0x35259ce0,0x35122466,
0x3481ad39,0x34fcfd04,0x33670786,0xb45ce98c,0x352d5c81,0x3547f5e5,0xb4ece099,0xb527cd68,0x354b2e94,0x3536a623,0xb5458c49,0xb54c32aa,0x350cc31e,0x34a4d655,0xb53af983,0xb513e451,
};
__device__ __forceinline__ void wgmma_n128(float (&d)[64], uint64_t da, uint64_t db, int sc) {
  asm volatile("{\n.reg .pred p;\nsetp.ne.b32 p, %66, 0;\n"
    "wgmma.mma_async.sync.aligned.m64n128k16.f32.bf16.bf16 "
    "{%0, %1, %2, %3, %4, %5, %6, %7, %8, %9, %10, %11, %12, %13, %14, %15, "
    "%16, %17, %18, %19, %20, %21, %22, %23, %24, %25, %26, %27, %28, %29, %30, %31, "
    "%32, %33, %34, %35, %36, %37, %38, %39, %40, %41, %42, %43, %44, %45, %46, %47, "
    "%48, %49, %50, %51, %52, %53, %54, %55, %56, %57, %58, %59, %60, %61, %62, %63}, %64, %65, p, 1, 1, 0, 1;\n}\n"
    : "+f"(d[0]), "+f"(d[1]), "+f"(d[2]), "+f"(d[3]), "+f"(d[4]), "+f"(d[5]), "+f"(d[6]), "+f"(d[7]),
      "+f"(d[8]), "+f"(d[9]), "+f"(d[10]), "+f"(d[11]), "+f"(d[12]), "+f"(d[13]), "+f"(d[14]), "+f"(d[15]),
      "+f"(d[16]), "+f"(d[17]), "+f"(d[18]), "+f"(d[19]), "+f"(d[20]), "+f"(d[21]), "+f"(d[22]), "+f"(d[23]),
      "+f"(d[24]), "+f"(d[25]), "+f"(d[26]), "+f"(d[27]), "+f"(d[28]), "+f"(d[29]), "+f"(d[30]), "+f"(d[31]),
      "+f"(d[32]), "+f"(d[33]), "+f"(d[34]), "+f"(d[35]), "+f"(d[36]), "+f"(d[37]), "+f"(d[38]), "+f"(d[39]),
      "+f"(d[40]), "+f"(d[41]), "+f"(d[42]), "+f"(d[43]), "+f"(d[44]), "+f"(d[45]), "+f"(d[46]), "+f"(d[47]),
      "+f"(d[48]), "+f"(d[49]), "+f"(d[50]), "+f"(d[51]), "+f"(d[52]), "+f"(d[53]), "+f"(d[54]), "+f"(d[55]),
      "+f"(d[56]), "+f"(d[57]), "+f"(d[58]), "+f"(d[59]), "+f"(d[60]), "+f"(d[61]), "+f"(d[62]), "+f"(d[63])
    : "l"(da), "l"(db), "r"(sc));
}

__device__ __forceinline__ void wgmma_n160(float (&d)[80], uint64_t da, uint64_t db, int sc) {
  asm volatile("{\n.reg .pred p;\nsetp.ne.b32 p, %82, 0;\n"
    "wgmma.mma_async.sync.aligned.m64n160k16.f32.bf16.bf16 "
    "{%0, %1, %2, %3, %4, %5, %6, %7, %8, %9, %10, %11, %12, %13, %14, %15, "
    "%16, %17, %18, %19, %20, %21, %22, %23, %24, %25, %26, %27, %28, %29, %30, %31, "
    "%32, %33, %34, %35, %36, %37, %38, %39, %40, %41, %42, %43, %44, %45, %46, %47, "
    "%48, %49, %50, %51, %52, %53, %54, %55, %56, %57, %58, %59, %60, %61, %62, %63, "
    "%64, %65, %66, %67, %68, %69, %70, %71, %72, %73, %74, %75, %76, %77, %78, %79}, %80, %81, p, 1, 1, 0, 1;\n}\n"
    : "+f"(d[0]), "+f"(d[1]), "+f"(d[2]), "+f"(d[3]), "+f"(d[4]), "+f"(d[5]), "+f"(d[6]), "+f"(d[7]),
      "+f"(d[8]), "+f"(d[9]), "+f"(d[10]), "+f"(d[11]), "+f"(d[12]), "+f"(d[13]), "+f"(d[14]), "+f"(d[15]),
      "+f"(d[16]), "+f"(d[17]), "+f"(d[18]), "+f"(d[19]), "+f"(d[20]), "+f"(d[21]), "+f"(d[22]), "+f"(d[23]),
      "+f"(d[24]), "+f"(d[25]), "+f"(d[26]), "+f"(d[27]), "+f"(d[28]), "+f"(d[29]), "+f"(d[30]), "+f"(d[31]),
      "+f"(d[32]), "+f"(d[33]), "+f"(d[34]), "+f"(d[35]), "+f"(d[36]), "+f"(d[37]), "+f"(d[38]), "+f"(d[39]),
      "+f"(d[40]), "+f"(d[41]), "+f"(d[42]), "+f"(d[43]), "+f"(d[44]), "+f"(d[45]), "+f"(d[46]), "+f"(d[47]),
      "+f"(d[48]), "+f"(d[49]), "+f"(d[50]), "+f"(d[51]), "+f"(d[52]), "+f"(d[53]), "+f"(d[54]), "+f"(d[55]),
      "+f"(d[56]), "+f"(d[57]), "+f"(d[58]), "+f"(d[59]), "+f"(d[60]), "+f"(d[61]), "+f"(d[62]), "+f"(d[63]),
      "+f"(d[64]), "+f"(d[65]), "+f"(d[66]), "+f"(d[67]), "+f"(d[68]), "+f"(d[69]), "+f"(d[70]), "+f"(d[71]),
      "+f"(d[72]), "+f"(d[73]), "+f"(d[74]), "+f"(d[75]), "+f"(d[76]), "+f"(d[77]), "+f"(d[78]), "+f"(d[79])
    : "l"(da), "l"(db), "r"(sc));
}

constexpr float C5_1 = 0.30901699437494745f, C5_2 = -0.8090169943749475f;
constexpr float S5_1 = 0.9510565162951535f, R5 = 0.6180339887498949f;
template <bool FWD>
__device__ __forceinline__ void dft5(float& r0, float& i0, float& r1, float& i1, float& r2, float& i2, float& r3, float& i3, float& r4, float& i4,
                                     bool two) {
  float t1r = r1 + r4, t2r = r2 + r3, t3r = r1 - r4, t4r = r2 - r3;
  float t1i = FWD ? i1 + i4 : i1 - i4, t2i = FWD ? i2 + i3 : i2 - i3;
  float t3i = FWD ? i1 - i4 : i1 + i4, t4i = FWD ? i2 - i3 : i2 + i3;
  if (!FWD && two) {
    t1r = r1 + r1; t1i = r4 + r4; t3r = i4 + i4; t3i = i1 + i1;
    t2r = r2 + r2; t2i = r3 + r3; t4r = i3 + i3; t4i = i2 + i2;
  }
  const float m1r = fmaf(C5_2, t2r, fmaf(C5_1, t1r, r0)), m1i = fmaf(C5_2, t2i, fmaf(C5_1, t1i, i0));
  const float m2r = fmaf(C5_1, t2r, fmaf(C5_2, t1r, r0)), m2i = fmaf(C5_1, t2i, fmaf(C5_2, t1i, i0));
  const float n1r = fmaf(R5, t4r, t3r), n1i = fmaf(R5, t4i, t3i);
  const float n2r = fmaf(R5, t3r, -t4r), n2i = fmaf(R5, t3i, -t4i);
  r0 = r0 + t1r + t2r; i0 = i0 + t1i + t2i;
  if (FWD) {
    r1 = fmaf(S5_1, n1i, m1r); i1 = fmaf(-S5_1, n1r, m1i); r4 = fmaf(-S5_1, n1i, m1r); i4 = fmaf(-S5_1, n1r, -m1i);
    r2 = fmaf(S5_1, n2i, m2r); i2 = fmaf(-S5_1, n2r, m2i); r3 = fmaf(-S5_1, n2i, m2r); i3 = fmaf(-S5_1, n2r, -m2i);
    if (two) {
      r1 = m1r; i1 = -S5_1 * n1r; r4 = m1i; i4 = S5_1 * n1i;
      r2 = m2r; i2 = -S5_1 * n2r; r3 = m2i; i3 = S5_1 * n2i;
    }
  } else {
    r1 = fmaf(-S5_1, n1i, m1r); i1 = fmaf(S5_1, n1r, m1i); r4 = fmaf(S5_1, n1i, m1r); i4 = fmaf(-S5_1, n1r, m1i);
    r2 = fmaf(-S5_1, n2i, m2r); i2 = fmaf(S5_1, n2r, m2i); r3 = fmaf(S5_1, n2i, m2r); i3 = fmaf(-S5_1, n2r, m2i);
  }
}

__device__ __forceinline__ void mma_newA(float (&c)[4], const uint4& a, uint32_t b0, uint32_t b1) { mma_new(c, a.x, a.y, a.z, a.w, b0, b1); }
__device__ __forceinline__ void mma_accA(float (&c)[4], const uint4& a, uint32_t b0, uint32_t b1) { mma_acc(c, a.x, a.y, a.z, a.w, b0, b1); }
__device__ __forceinline__ float comp(const uint4& v, int i) { return __uint_as_float(i == 0 ? v.x : i == 1 ? v.y : i == 2 ? v.z : v.w); }

struct P2Const { uint4 MAre[2], MAim[2], IC, IS, ISn, t1c, t1s, t2c, t2s, F8, I8; };
__device__ __forceinline__ void p2_fwd(const P2Const& K, const uint32_t (&u)[4], float (&vr)[4], float (&vi)[4]) {
  float tr[4], ti[4], xr[4], xi[4];
  mma_newA(tr, K.MAre[0], u[0], u[1]);
  mma_newA(ti, K.MAim[0], u[0], u[1]);
  mma_accA(tr, K.MAre[1], u[2], u[3]);
  mma_accA(ti, K.MAim[1], u[2], u[3]);
#pragma unroll
  for (int r = 0; r < 4; r++) {
    xr[r] = fmaf(ti[r], comp(K.t1s, r), tr[r] * comp(K.t1c, r));
    xi[r] = fmaf(-tr[r], comp(K.t1s, r), ti[r] * comp(K.t1c, r));
  }
  const uint32_t a0 = pack2(xr[0], xr[1]), a1 = pack2(xr[2], xr[3]), a2 = pack2(xi[0], xi[1]), a3 = pack2(xi[2], xi[3]);
  mma_new(vr, a0, a1, a2, a3, K.F8.x, K.F8.y);
  mma_new(vi, a0, a1, a2, a3, K.F8.z, K.F8.w);
}
__device__ __forceinline__ void p2_inv(const P2Const& K, const float (&yr)[4], const float (&yi)[4], float (&ore)[4], float (&oim)[4]) {
  float z0[4], z1[4], xr[4], xi[4];
  mma_newA(z0, K.I8, pack2(yr[0], yr[1]), pack2(yi[0], yi[1]));
  mma_newA(z1, K.I8, pack2(yr[2], yr[3]), pack2(yi[2], yi[3]));
#pragma unroll
  for (int e = 0; e < 2; e++) {
    xr[e] = fmaf(-z0[2 + e], comp(K.t2s, e), z0[e] * comp(K.t2c, e));
    xi[e] = fmaf(z0[e], comp(K.t2s, e), z0[2 + e] * comp(K.t2c, e));
    xr[2 + e] = fmaf(-z1[2 + e], comp(K.t2s, 2 + e), z1[e] * comp(K.t2c, 2 + e));
    xi[2 + e] = fmaf(z1[e], comp(K.t2s, 2 + e), z1[2 + e] * comp(K.t2c, 2 + e));
  }
  const uint32_t br0 = pack2(xr[0], xr[1]), br1 = pack2(xr[2], xr[3]), bi0 = pack2(xi[0], xi[1]), bi1 = pack2(xi[2], xi[3]);
  mma_newA(ore, K.IC, br0, br1);
  mma_newA(oim, K.IS, br0, br1);
  mma_accA(ore, K.ISn, bi0, bi1);
  mma_accA(oim, K.IC, bi0, bi1);
}

__device__ __forceinline__ void gemv_slice(uint32_t tile, const uint32_t (&a)[5][2], int slice, int w, int lane, uint32_t red, uint32_t epa) {
  uint32_t bw[5][4];
#pragma unroll
  for (int i = 0; i < 5; i++) ldsm4t(bw[i][0], bw[i][1], bw[i][2], bw[i][3], tile + (80 * w + 16 * i + (lane & 15)) * 32 + (lane >> 4) * 16);
  float d0[4], d1[4], e0[4], e1[4];
  mma_new(d0, a[0][0], 0u, a[0][1], 0u, bw[0][0], bw[0][1]); mma_new(d1, a[0][0], 0u, a[0][1], 0u, bw[0][2], bw[0][3]);
  mma_new(e0, a[1][0], 0u, a[1][1], 0u, bw[1][0], bw[1][1]); mma_new(e1, a[1][0], 0u, a[1][1], 0u, bw[1][2], bw[1][3]);
  mma_acc(d0, a[2][0], 0u, a[2][1], 0u, bw[2][0], bw[2][1]); mma_acc(d1, a[2][0], 0u, a[2][1], 0u, bw[2][2], bw[2][3]);
  mma_acc(e0, a[3][0], 0u, a[3][1], 0u, bw[3][0], bw[3][1]); mma_acc(e1, a[3][0], 0u, a[3][1], 0u, bw[3][2], bw[3][3]);
  mma_acc(d0, a[4][0], 0u, a[4][1], 0u, bw[4][0], bw[4][1]); mma_acc(d1, a[4][0], 0u, a[4][1], 0u, bw[4][2], bw[4][3]);
  if (lane < 4) {
    const uint32_t ra = red + lane * 64 + w * 4;
    sts32(ra, __float_as_uint(d0[0] + e0[0])); sts32(ra + 32, __float_as_uint(d0[1] + e0[1]));
    sts32(ra + 256, __float_as_uint(d1[0] + e1[0])); sts32(ra + 288, __float_as_uint(d1[1] + e1[1]));
  }
  bar_sync(1, 256);
  if (w < 4) {
    const uint4 p = lds128(red + (lane & 15) * 32), q = lds128(red + (lane & 15) * 32 + 16);
    const uint32_t ep = lds32(epa);
    float v = ((__uint_as_float(p.x) + __uint_as_float(p.y)) + (__uint_as_float(p.z) + __uint_as_float(p.w))) +
              ((__uint_as_float(q.x) + __uint_as_float(q.y)) + (__uint_as_float(q.z) + __uint_as_float(q.w)));
    v = bf_round(v);
    if ((slice >= 40 && slice < 80) || (slice >= 160 && slice < 200)) v = bf_round(1.f + v);
    st_relaxed(&g_mod[(2 * w + (lane >> 4)) * 3840 + slice * 16 + (lane & 15)], __float_as_uint(v) | (ep & 0xffffu));
  }
}
__device__ __forceinline__ uint32_t silu2(uint32_t c) {
  const float c0 = bf_lo(c), c1 = bf_hi(c);
  return pack2(__fdividef(c0, 1.f + __expf(-c0)), __fdividef(c1, 1.f + __expf(-c1)));
}

template <int NI, int NT>
__device__ __forceinline__ void poll_mods(const uint32_t* src, uint32_t dst, bool last, uint32_t tag) {
  int it = 0;
  uint32_t acc;
  const int lo = last ? (NI - 1) * NT : 0;
  do {
    uint4 v[NI];
#pragma unroll
    for (int i = 0; i < NI; i++) v[i] = ld_relaxed4(src + (i < NI - 1 ? i * NT : lo) * 4);
    acc = 0;
#pragma unroll
    for (int i = 0; i < NI; i++) {
      sts64(dst + (i < NI - 1 ? i * NT : lo) * 8, __byte_perm(v[i].x, v[i].y, 0x7632), __byte_perm(v[i].z, v[i].w, 0x7632));
      acc |= ((v[i].x ^ tag) | (v[i].y ^ tag)) | ((v[i].z ^ tag) | (v[i].w ^ tag));
    }
  } while (__any_sync(0xffffffffu, (acc & 0xffffu) != 0) && ++it < SPIN_LIMIT);
}

__device__ __forceinline__ void ln_stats(const uint32_t (&xw)[2][10], int g, int t, uint32_t (&nm)[2], float (&rs)[2]) {
  float q[2], s[2];
#pragma unroll
  for (int r = 0; r < 2; r++) {
    float d[4];
    mma_new(d, xw[r][0], 0x3f803f80u, xw[r][1], 0x3f803f80u, xw[r][0], xw[r][1]);
#pragma unroll
    for (int i = 2; i < 10; i += 2) mma_acc(d, xw[r][i], 0x3f803f80u, xw[r][i + 1], 0x3f803f80u, xw[r][i], xw[r][i + 1]);
    q[r] = (g & 1) ? d[1] : d[0];
    s[r] = d[2] + d[3];
  }
  float z = __shfl_sync(0xffffffffu, q[0], 4 * g + (g >> 1)), z1 = __shfl_sync(0xffffffffu, q[1], 4 * g + (g >> 1));
  z = (t & 1) ? z1 : z;
  float y = (t & 1) ? s[1] : s[0];
  y += __shfl_xor_sync(0xffffffffu, (t & 1) ? s[0] : s[1], 1);
  z += __shfl_xor_sync(0xffffffffu, z, 4);
  y += __shfl_xor_sync(0xffffffffu, y, 2);
  z += __shfl_xor_sync(0xffffffffu, z, 8);
  z += __shfl_xor_sync(0xffffffffu, z, 16);
  const float m = y * (1.f / 640.f);
  float r0;
  asm("rsqrt.approx.ftz.f32 %0, %1;" : "=f"(r0) : "f"(fmaxf(fmaf(z, 1.f / 640.f, -m * m), 0.f) + 1e-5f));
  const uint32_t n0 = pack2(-m, -m);
  const float r1 = __shfl_xor_sync(0xffffffffu, r0, 1);
  const uint32_t n1 = __shfl_xor_sync(0xffffffffu, n0, 1);
  rs[0] = (t & 1) ? r1 : r0; rs[1] = (t & 1) ? r0 : r1;
  nm[0] = (t & 1) ? n1 : n0; nm[1] = (t & 1) ? n0 : n1;
}
__device__ __forceinline__ float gelu_mul(float g, float u) {
  const float z = g * fmaf(g * g, 0.035677408136300125f, 0.7978845608028654f);
  float th; asm("tanh.approx.f32 %0, %1;" : "=f"(th) : "f"(z));
  const float gu = g * u;
  return fmaf(gu, th, gu);
}

template <int NW, int S0, int S1>
__device__ __forceinline__ bool validate(uint32_t dst, uint32_t ta, const void* src, uint32_t par, uint32_t rbar, uint32_t& rph, int which) {
  int it = 0;
  while (true) {
    uint32_t acc = 0;
#pragma unroll
    for (int i = 0; i < NW; i++) acc |= lds32(ta + (i & 1) * S0 + (i >> 1) * S1) ^ par;
    if (!__any_sync(0xffffffffu, (acc & 1) != 0) || ++it >= SPIN_LIMIT) break;
    fence_async_smem();
    __syncwarp();
    if (elect()) { mbar_expect(rbar, NW * 1024); bulk_g2s(dst, src, NW * 1024, rbar); }
    __syncwarp();
    mbar_wait(rbar, rph); rph ^= 1;
  }
  return it != 0;
}

__global__ void __launch_bounds__(NTHR, 1)
fused_kernel(const __grid_constant__ CUtensorMap tmMod, const __grid_constant__ CUtensorMap tmW,
             const __grid_constant__ CUtensorMap tmE, const __grid_constant__ CUtensorMap tmH2,
             const __grid_constant__ CUtensorMap tmGU,
             const __grid_constant__ CUtensorMap tmOut, const __grid_constant__ CUtensorMap tmW2,
             const __grid_constant__ CUtensorMap tmGU2, const __grid_constant__ CUtensorMap tmCr,
             const __grid_constant__ CUtensorMap tmCi, const __grid_constant__ CUtensorMap tmWd,
             const __grid_constant__ CUtensorMap tmS, int split,
             const __nv_bfloat16* __restrict__ x,
             const __nv_bfloat16* __restrict__ wd,
             const __nv_bfloat16* __restrict__ cvec, const __nv_bfloat16* __restrict__ wmod, __nv_bfloat16* __restrict__ out) {
  extern __shared__ __align__(1024) uint8_t smem_raw[];
  const uint32_t t_start = clock32();
  constexpr uint32_t sb = 1024, bars = sb + OFF_BAR;
  if ((uint32_t)__cvta_generic_to_shared(smem_raw) != sb) __trap();
  const int tid = threadIdx.x, w = __shfl_sync(0xffffffffu, tid >> 5, 0), lane = tid & 31, g = lane >> 2, t = lane & 3;
  const int b = blockIdx.x, grp = b >> 3, nsl = b & 7;
  const int k1 = b & 15, Bk = b >> 4;
  const int mb2 = nsl & 1, nq = nsl >> 1;
  uint32_t* const gcnt = g_cnt + 32 + 32 * grp;

  if (w < 8) {
    if (tid == 0) { STAMP(0); GSTAMP(60); }
#pragma unroll 1
    for (int i = BAR_EARLY + w; i < BAR_G1; i += 8) mbar_init(bars + 8 * i, i == BAR_MODA ? 4 : 1);
    if (tid < 3) sts32(sb + OFF_EP + 4 + 4 * tid, 0);
    bar_arrive(4, 384);
    if (tid == 0) STAMP(45);
    spin_until(t_start + X_DELAY);
#pragma unroll
    for (int i = 0; i < 5; i++) {
      const int idx = lane + 32 * i, row = idx >= 80, ch = idx - 80 * row;
      asm volatile("cp.async.cg.shared.global [%0], [%1], 16;" :: "r"(sb + OFF_XS + (2 * w + row) * 1280 + ch * 16),
                   "l"(x + (size_t)(128 * (2 * w + row) + b) * 640 + ch * 8) : "memory");
    }
    if (tid == 0) STAMP(30);
    bar_sync(3, 320);
    mbar_wait(bars + 8 * BAR_C, 0);
    {
      const uint32_t ca = sb + OFF_SC + (40 * w + lane) * 4;
      const uint32_t c0 = lds32(ca), c1 = lds32(ca + 32);
      const uint32_t s0 = silu2(c0), s1 = silu2(c1);
      __syncwarp();
      sts32(ca + 32, s1);
      if (lane < 8) sts32(ca, s0);
      __syncwarp();
    }
    uint32_t sc[5][2];
#pragma unroll
    for (int i = 0; i < 10; i++) sc[i >> 1][i & 1] = lds32(sb + OFF_SC + (40 * w + 4 * i + t) * 4);
    if (tid == 0) STAMP(32);
    if (b < 80) {
      mbar_wait(bars + 8 * BAR_G1, 0);
      if (tid == 0) STAMP(33);
      gemv_slice(sb + OFF_BUFB, sc, b, w, lane, sb + OFF_RED, sb + OFF_EP);
    } else if (tid == 0) STAMP(33);
    if (tid == 0) STAMP(18);
    const uint32_t tl = sb + lane * 16;
    uint32_t eoff[5], tagm, tagv, par;
    {
      asm volatile("cp.async.wait_all;" ::: "memory");
      __syncwarp();
      if (tid == 0) STAMP(1);
      const int mi = lane >> 3;
      const uint32_t lrow = (mi >> 1) * 1280 + (8 * (mi & 1) + (lane & 7)) * 80;
      uint32_t nw[2][10];
      {
        uint32_t xw[2][10];
#pragma unroll
        for (int n = 0; n < 5; n++)
          ldsm4t(xw[0][2 * n], xw[0][2 * n + 1], xw[1][2 * n], xw[1][2 * n + 1], sb + OFF_XS + 2 * w * 1280 + lrow + n * 16);
        uint32_t nm[2]; float rs[2];
        ln_stats(xw, g, t, nm, rs);
#pragma unroll
        for (int r = 0; r < 2; r++) {
          const uint32_t rh = pack2(rs[r], rs[r]);
          const float lo = rs[r] - bf_lo(rh);
          const uint32_t rl = pack2(lo, lo);
#pragma unroll
          for (int i = 0; i < 10; i++) {
            const uint32_t d = hadd2(xw[r][i], nm[r]);
            nw[r][i] = hfma2(d, rh, hmul2(d, rl));
          }
        }
      }
#pragma unroll
      for (int i = 0; i < 10; i++) asm volatile("" : "+r"(nw[0][i]), "+r"(nw[1][i]) :: "memory");
      mbar_wait(bars + 8 * BAR_TB, 0);
      const uint4 eo = lds128(tl + OFF_T1 + (6 * w + 5) * 512);
      eoff[0] = eo.x; eoff[1] = eo.y; eoff[2] = eo.z; eoff[3] = eo.w & 0xffffu; eoff[4] = eo.w >> 16;
      const uint4 A1 = lds128(tl + OFF_TC), Cb = lds128(tl + OFF_TC + 512), Sb = lds128(tl + OFF_TC + 1024);
      uint4 A2[5];
#pragma unroll
      for (int f = 0; f < 5; f++) A2[f] = lds128(tl + OFF_T1 + (6 * w + f) * 512);
      if (tid == 0) STAMP(2);
      mbar_wait(bars + 8 * BAR_MODA, 0);
      if (tid == 0) STAMP(3);
      par = lds32(sb + OFF_EP);
      uint32_t mv[5][4];
#pragma unroll
      for (int n = 0; n < 5; n++) ldsm4t(mv[n][0], mv[n][1], mv[n][2], mv[n][3], sb + OFF_MODS + lrow + n * 16);
#pragma unroll
      for (int n = 0; n < 5; n++) {
        const uint32_t a0 = mv[n][0], a1 = mv[n][1], c0 = mv[n][2], c1 = mv[n][3];
#pragma unroll
        for (int r = 0; r < 2; r++) {
          const uint32_t b0 = hfma2(nw[r][2 * n], c0, a0), b1 = hfma2(nw[r][2 * n + 1], c1, a1);
          float d[4];
          mma_newA(d, A1, b0, b1);
          sts64(sb + OFF_TS + (g * TS_P + (2 * w + r) * TS_J + 8 * n + 2 * t) * 4, pack2(d[0], d[2]), pack2(d[1], d[3]));
        }
      }
      if (tid == 0) STAMP(34);
      bar_sync(6, 288);
      const bool spec = tid < 4;
      float G[5][2][4];
#pragma unroll
      for (int f = 0; f < 5; f++)
#pragma unroll
        for (int h = 0; h < 2; h++) {
          const uint32_t ad = sb + OFF_TS + (w * TS_P + (g + 8 * h) * TS_J + 5 * t + f) * 4;
          mma_newA(G[f][h], A2[f], lds32(ad), lds32(ad + 80));
        }
#pragma unroll
      for (int h = 0; h < 2; h++)
#pragma unroll
        for (int e = 0; e < 2; e++)
          dft5<true>(G[0][h][e], G[0][h][2 + e], G[1][h][e], G[1][h][2 + e], G[2][h][e], G[2][h][2 + e],
                     G[3][h][e], G[3][h][2 + e], G[4][h][e], G[4][h][2 + e], spec);
      const uint32_t sg2 = (w > 0 && g >= 4) ? 0x80008000u : 0u;
      const uint32_t sw1 = b & 28;
      tagm = w == 0 ? 1u : 0u; tagv = par & tagm;
#pragma unroll
      for (int v = 0; v < 5; v++) {
        const uint32_t re0 = pack2(G[v][0][0], G[v][0][1]), re1 = pack2(G[v][1][0], G[v][1][1]);
        uint32_t im0 = pack2(G[v][0][2], G[v][0][3]), im1 = pack2(G[v][1][2], G[v][1][3]);
        if (v == 2) { im0 ^= sg2; im1 ^= sg2; }
        const uint32_t ad = sb + OFF_BUFA + (eoff[v] ^ sw1);
#pragma unroll
        for (int h = 0; h < 2; h++) {
          uint32_t a0 = re0, a1 = im0, a2 = re1, a3 = im1;
          if (v == 0 && spec) { a0 = h ? im0 : re0; a2 = h ? im1 : re1; a1 = 0; a3 = 0; }
          float d[4];
          mma_new(d, a0, a1, a2, a3, h ? Cb.z : Cb.x, h ? Cb.w : Cb.y);
          mma_acc(d, a1, a0 ^ 0x80008000u, a3, a2 ^ 0x80008000u, h ? Sb.z : Sb.x, h ? Sb.w : Sb.y);
          if (v == 0) {
            float e[4];
            mma_new(e, re0, im0, re1, im1, h ? Cb.z : Cb.x, h ? Cb.w : Cb.y);
            if (tid == 0) { d[0] = e[0]; d[2] = e[2]; }
          }
          sts32(ad + (2 * h) * 640, (pack2(d[0], d[2]) & ~tagm) | tagv);
          sts32(ad + (2 * h + 1) * 640, (pack2(d[1], d[3]) & ~tagm) | tagv);
        }
      }
    }
    bar_arrive(5, 320);
    if (tid == 0) STAMP(4);

    {
      mbar_wait(bars + 8 * PREP_BAR, 0);
      P2Const K;
      {
        const uint32_t tb = tl + OFF_T2;
        K.MAre[0] = lds128(tb); K.MAre[1] = lds128(tb + 512); K.MAim[0] = lds128(tb + 1024); K.MAim[1] = lds128(tb + 1536);
        K.IC = lds128(tb + 2048); K.IS = lds128(tb + 2560); K.ISn = lds128(tb + 3072);
        K.t1c = lds128(tb + 3584); K.t1s = lds128(tb + 4096); K.t2c = lds128(tb + 4608); K.t2s = lds128(tb + 5120);
        K.F8 = lds128(tl + OFF_TC + 1536); K.I8 = lds128(tl + OFF_TC + 2048);
      }
      float wr[5][4], wi[5][4];
      mbar_wait(bars + 8 * BAR_W, 0);
      if (tid == 0) STAMP(49);
      {
        uint4 m[6];
        const uint32_t wa = sb + OFF_WR + (lane >> 4) * (OFF_WI - OFF_WR) + ((lane & 8) * 8 + 8 * w + (lane & 7)) * 112;
#pragma unroll
        for (int c = 0; c < 6; c++) ldsm4t(m[c].x, m[c].y, m[c].z, m[c].w, wa + c * 16);
#pragma unroll
        for (int c = 0; c < 6; c++) sts128(sb + OFF_WT + (8 * c + g) * 576 + (4 * w + t) * 16, m[c]);
        bar_sync(1, 256);
#pragma unroll
        for (int v = 0; v < 5; v++) {
          const uint4 q = lds128(tl + OFF_WT + (8 * v + w + (k1 & 7)) * 576);
          wr[v][0] = bf_lo(q.x); wr[v][1] = bf_hi(q.x); wr[v][2] = bf_lo(q.y); wr[v][3] = bf_hi(q.y);
          wi[v][0] = bf_lo(q.z); wi[v][1] = bf_hi(q.z); wi[v][2] = bf_lo(q.w); wi[v][3] = bf_hi(q.w);
        }
      }
      const bool col0 = (Bk == 0 && w == 0);
      const uint32_t aba = sb + OFF_AB + (g + 32 * t) * 16;
      if (col0) {
        mbar_wait(bars + 8 * BAR_AB, 0);
#pragma unroll
        for (int r = 0; r < 4; r++) {
          const uint4 ab = lds128(aba + (8 * (r >> 1) + 16 * (r & 1)) * 16);
          wr[0][r] = __uint_as_float(ab.x); wi[0][r] = __uint_as_float(ab.y);
        }
      }
#pragma unroll
      for (int v = 0; v < 5; v++) { reg_fence(wr[v]); reg_fence(wi[v]); }
      uint32_t ia[5], oa[5];
#pragma unroll
      for (int v = 0; v < 5; v++) {
        const int m4 = (5 * Bk + v) >> 1;
        ia[v] = sb + OFF_BUFB + ((8 * t + g) * 40 + 8 * v + ((w ^ m4 ^ (2 * t + (g >> 2))) & 7)) * 4;
        oa[v] = sb + OFF_P2A + (v >= 3) * 12288 + ((8 * g + t) * 24 + 8 * (v % 3) + ((w ^ m4 ^ g) & 7)) * 4;
        asm volatile("" : "+r"(ia[v]), "+r"(oa[v]));
      }
      if (tid == 0) STAMP(5);
      mbar_wait(bars + 8 * BAR_IN2, 0);
      if (tid == 0) STAMP(6);
#pragma unroll 1
      for (int pass = 0; pass < 2; pass++) {
      uint32_t u[5][4];
#pragma unroll
      for (int v = 0; v < 5; v++) {
#pragma unroll
        for (int i = 0; i < 4; i++) u[v][i] = lds32(ia[v] + i * 5120);
      }
      float er[4] = {0.f, 0.f, 0.f, 0.f}, ei[4] = {0.f, 0.f, 0.f, 0.f};
      if (col0 && (k1 & 7) == 0) {
        const uint32_t uc[4] = {u[0][0] ^ 0x80000000u, u[0][1] ^ 0x80000000u, u[0][2] ^ 0x80000000u, u[0][3] ^ 0x80000000u};
        float vr[4], vi[4];
        p2_fwd(K, uc, vr, vi);
#pragma unroll
        for (int r = 0; r < 4; r++) {
          const uint4 ab = lds128(aba + (8 * (r >> 1) + 16 * (r & 1)) * 16);
          er[r] = fmaf(-vi[r], __uint_as_float(ab.w), vr[r] * __uint_as_float(ab.z));
          ei[r] = fmaf(vr[r], __uint_as_float(ab.w), vi[r] * __uint_as_float(ab.z));
        }
      }
      uint32_t verd;
#pragma unroll
      for (int v = 0; v < 5; v++) {
        float vr[4], vi[4], yr[4], yi[4], ore[4], oim[4];
        p2_fwd(K, u[v], vr, vi);
#pragma unroll
        for (int r = 0; r < 4; r++) {
          yr[r] = fmaf(-vi[r], wi[v][r], v == 0 ? fmaf(vr[r], wr[v][r], er[r]) : vr[r] * wr[v][r]);
          yi[r] = fmaf(vr[r], wi[v][r], v == 0 ? fmaf(vi[r], wr[v][r], ei[r]) : vi[r] * wr[v][r]);
        }
        p2_inv(K, yr, yi, ore, oim);
#pragma unroll
        for (int r = 0; r < 4; r++) sts32(oa[v] + ((r & 1) * 4 + (r >> 1) * 64) * 96, (pack2(ore[r], oim[r]) & ~tagm) | tagv);
        if (v == 2) {
          bar_arrive(9, 288);
          mbar_wait(bars + 8 * BAR_IN2, 0);
#pragma unroll
          for (int i = 0; i < 4; i++) asm volatile("" : "+r"(u[3][i]), "+r"(u[4][i]) :: "memory");
        }
        if (v == 3) verd = lds32v(sb + OFF_EP + 4);
      }
      for (int it = 0; verd == 0 && it < SPIN_LIMIT; it++) verd = lds32v(sb + OFF_EP + 4);
      if (verd != 2) break;
      __threadfence_block();
      }
    }
    bar_arrive(5, 320);
    if (tid == 0) STAMP(7);

    {
      uint32_t sc2[5][2];
#pragma unroll
      for (int i = 0; i < 10; i++) sc2[i >> 1][i & 1] = lds32(sb + OFF_SC + (40 * w + 4 * i + t) * 4);
#pragma unroll 1
      for (int i = 0; i < 1 + (b < 32); i++) {
        mbar_wait(bars + 8 * (BAR_G2 + i), 0);
        if (tid == 0 && i == 0) STAMP(40);
        gemv_slice(sb + (i ? OFF_X1 : OFF_B), sc2, b + 80 + 128 * i, w, lane, sb + OFF_RED + 512 * i, sb + OFF_EP);
      }
      if (tid == 0) STAMP(29);
    }
    {
      const uint4 JR0 = lds128(tl + OFF_TC + 2560), JR1 = lds128(tl + OFF_TC + 3072), JI0 = lds128(tl + OFF_TC + 3584),
                  JI1 = lds128(tl + OFF_TC + 4096), A1i = lds128(tl + OFF_TC + 4608);
      uint4 B2[5];
      mbar_wait(bars + 8 * BAR_TB3, 0);
#pragma unroll
      for (int f = 0; f < 5; f++) B2[f] = lds128(tl + OFF_T3 + (5 * w + f) * 512);
      bar_arrive(11, 320);
      const uint32_t dof = (40 * g + 2 * t) * 2;
      uint32_t xv[2][10], gav[10], sbv[10], cbv[10];
#pragma unroll
      for (int i = 0; i < 10; i++) {
        const uint32_t o = dof + (i >> 1) * 16 + (i & 1) * 640;
        xv[0][i] = lds32(sb + OFF_XS + 2 * w * 1280 + o); xv[1][i] = lds32(sb + OFF_XS + (2 * w + 1) * 1280 + o);
      }
      const uint32_t sw3 = (b >> 1) & 28;
#pragma unroll 1
      for (int pass = w != 6; pass < 3; pass++) {
      if (pass == 1) {
        mbar_wait(bars + 8 * BAR_IN3, 0);
        if (tid == 0) STAMP(9);
      }
      float Zr[5][4], Zi[5][4];
#pragma unroll
      for (int v = 0; v < 5; v++) {
        const uint32_t ad = sb + OFF_BUFB + (eoff[v] ^ sw3);
        const uint32_t q0 = lds32(ad), q1 = lds32(ad + 640), q2 = lds32(ad + 1280), q3 = lds32(ad + 1920);
        uint32_t r2 = q2, r3 = q3, i0 = q0, i1 = q1;
        if (v == 0 && tid < 4) { r3 = 0; i1 = 0; if (tid != 0) { r2 = 0; i0 = 0; } }
        mma_newA(Zr[v], JR0, q0, q1);
        mma_newA(Zi[v], JI0, i0, i1);
        mma_accA(Zr[v], JR1, r2, r3);
        mma_accA(Zi[v], JI1, q2, q3);
      }
      const float sg2 = (w > 0 && t >= 2) ? -1.f : 1.f;
      uint32_t verd;
#pragma unroll
      for (int r = 0; r < 4; r++) {
        Zi[2][r] *= sg2;
        dft5<false>(Zr[0][r], Zi[0][r], Zr[1][r], Zi[1][r], Zr[2][r], Zi[2][r], Zr[3][r], Zi[3][r], Zr[4][r], Zi[4][r], (r & 1) == 0 && w == 0 && t == 0);
      }
#pragma unroll
      for (int f = 0; f < 5; f++) {
        const uint32_t a0 = pack2(Zr[f][0], Zr[f][1]), a1 = pack2(Zr[f][2], Zr[f][3]);
        const uint32_t a2 = pack2(Zi[f][0], Zi[f][1]), a3 = pack2(Zi[f][2], Zi[f][3]);
#pragma unroll
        for (int h = 0; h < 2; h++) {
          float d[4];
          mma_new(d, a0, a1, a2, a3, h ? B2[f].z : B2[f].x, h ? B2[f].w : B2[f].y);
          const uint32_t ad = sb + OFF_TS + (w * TS_P + g * TS_J + 5 * (4 * h + t) + f) * 4;
          sts32(ad, pack2(d[0], d[1]));
          sts32(ad + 8 * TS_J * 4, pack2(d[2], d[3]));
        }
        if (f == 0) verd = lds32v(sb + OFF_EP + 8);
      }
      if (pass == 0) continue;
      if (tid == 0) STAMP(41);
      for (int it = 0; verd == 0 && it < SPIN_LIMIT; it++) verd = lds32v(sb + OFF_EP + 8);
      if (verd != 2) break;
      __threadfence_block();
      }
      if (tid == 0) STAMP(8);
      bar_sync(7, 352);
      float y[2][5][4];
#pragma unroll
      for (int r = 0; r < 2; r++)
#pragma unroll
        for (int n = 0; n < 5; n++) {
          const uint32_t ad = sb + OFF_TS + (t * TS_P + (2 * w + r) * TS_J + 8 * n + g) * 4;
          mma_newA(y[r][n], A1i, lds32(ad), lds32(ad + 4 * TS_P * 4));
        }
#pragma unroll
      for (int i = 0; i < 10; i++) gav[i] = lds32(sb + OFF_MODS + 2 * 1280 + dof + (i >> 1) * 16 + (i & 1) * 640);
#pragma unroll
      for (int i = 0; i < 10; i++) {
        const uint32_t o = dof + (i >> 1) * 16 + (i & 1) * 640;
        sbv[i] = lds32(sb + OFF_MODS + 3 * 1280 + o); cbv[i] = lds32(sb + OFF_MODS + 4 * 1280 + o);
      }
#pragma unroll
      for (int r = 0; r < 2; r++)
#pragma unroll
        for (int i = 0; i < 10; i++)
          xv[r][i] = hfma2(gav[i], pack2(y[r][i >> 1][2 * (i & 1)], y[r][i >> 1][2 * (i & 1) + 1]), xv[r][i]);
      uint32_t nm[2]; float rs[2];
      ln_stats(xv, g, t, nm, rs);
      const uint32_t rh[2] = {pack2(rs[0], rs[0]), pack2(rs[1], rs[1])};
#pragma unroll
      for (int n = 0; n < 5; n++) {
        const int c8 = 5 * g + n;
        const uint32_t ha = sb + OFF_H2S + (c8 >> 3) * 2048 + 2 * w * 128 + ((c8 ^ (2 * w)) & 7) * 16 + t * 4;
#pragma unroll
        for (int hh = 0; hh < 2; hh++) {
          const uint32_t sv = sbv[2 * n + hh], cv = cbv[2 * n + hh];
#pragma unroll
          for (int r = 0; r < 2; r++) {
            const uint32_t tm = (t == ((2 * w + r) & 3) && ((g + n + r + (w >> 1)) & 1) == 0) ? 1u : 0u;
            sts32((r ? (ha ^ 16) + 128 : ha) + hh * 5 * 2048, (hfma2(hadd2(xv[r][2 * n + hh], nm[r]), hmul2(cv, rh[r]), sv) & ~tm) | (par & tm));
          }
        }
      }
      bar_arrive(2, 288);
      if (tid == 0) STAMP(10);
#pragma unroll
      for (int r = 0; r < 2; r++)
#pragma unroll
        for (int i = 0; i < 10; i++) sts32(sb + OFF_X1 + (2 * w + r) * 1280 + dof + (i >> 1) * 16 + (i & 1) * 640, xv[r][i]);
    }

    const int wq = w & 3, wgi = w >> 2, tau = tid & 127;
    bar_arrive(8, 288);
    uint32_t rph = 0;
    if (wgi == 1) {
      uint32_t dst = sb + wq * 8192;
      const uint4* src = g_H2 + (size_t)grp * 10240 + wq * 512;
#pragma unroll 1
      for (int kb = wq >> 1; kb < 10; kb += 2, dst += 32768, src += 2048) {
        mbar_wait(bars + 8 * (BAR_ALAND + kb), 0);
        if (kb == 1 && tau == 64) STAMP(53);
        bool again = validate<8, 1024, 2048>(dst, dst + lane * 32 + (lane >> 2) * 4, src, par, bars + 8 * (BAR_WRETRY + w), rph, 2);
        if (again && kb < 2) sts32(sb + OFF_EP + 12, 1);
        mbar_arrive_if(bars + 8 * (BAR_BFULL + max(kb, 2)), lane == 0);
        if (kb == 1 && tau == 64) STAMP(54);
        if (kb == 0 && tau == 0) STAMP(55);
      }
    }
#pragma unroll 1
    for (int ch = wgi; ch < 3; ch += 2) {
      float acc0[64], acc1[64];
      mbar_wait(bars + 8 * (BAR_BFULL + 10 * ch), 0);
      int kb = 0;
      if (ch == 0) {
        mbar_wait(bars + 8 * (BAR_BFULL + 1), 0);
#pragma unroll
        for (int s = 0; s < 2; s++) {
          mbar_wait(bars + 8 * (BAR_ALAND + s), 0);
          if (tid == 0 && s == 0) { STAMP(25); GSTAMP(61); }
          wg_fence();
#pragma unroll
          for (int kk = 0; kk < 4; kk++) {
            wgmma_n128(acc0, mkdesc(sb + s * 16384, 16, 1024, 1) + 2 * kk, mkdesc(sb + OFF_B + s * 16384, 8192, 1024, 1) + 128 * kk, (s | kk) != 0);
            wgmma_n128(acc1, mkdesc(sb + s * 16384, 16, 1024, 1) + 512 + 2 * kk, mkdesc(sb + OFF_B + s * 16384, 8192, 1024, 1) + 128 * kk, (s | kk) != 0);
          }
          wg_commit();
          if (tau == 0) STAMP(64 + s);
        }
        wg_wait<1>();
        mbar_wait(bars + 8 * (BAR_BFULL + 2), 0);
        kb = __shfl_sync(0xffffffffu, lds32(sb + OFF_EP + 12), 0) == 0 ? 2 : 0;
        mbar_arrive_if(bars + 8 * BAR_BEMPTY, lane == 0 && kb == 2);
      }
      wg_fence();
      uint32_t dal = (uint32_t)mkdesc(sb, 16, 1024, 1) + 1024 * kb;
      uint32_t dbl = (uint32_t)mkdesc(sb + OFF_B, 8192, 1024, 1) + 1024 * ((10 * ch + kb) & 3);
#pragma unroll 1
      for (; kb < 10; kb++) {
        const int job = 10 * ch + kb;
        const uint64_t da = (mkdesc(sb, 16, 1024, 1) & ~0xffffffffull) | dal, db = (mkdesc(sb, 8192, 1024, 1) & ~0xffffffffull) | dbl;
        wgmma_n128(acc0, da, db, kb != 0);
        wgmma_n128(acc1, da + 512, db, kb != 0);
        const uint32_t nxt = bars + 8 * (BAR_BFULL + job + (kb < 9));
        const uint32_t rdy = mbar_test(nxt, 0);
#pragma unroll
        for (int kk = 1; kk < 4; kk++) {
          wgmma_n128(acc0, da + 2 * kk, db + 128 * kk, 1);
          wgmma_n128(acc1, da + 512 + 2 * kk, db + 128 * kk, 1);
        }
        wg_commit();
        dal += 1024;
        dbl = (uint32_t)mkdesc(sb + OFF_B, 8192, 1024, 1) + 1024 * ((job + 1) & 3);
        uint32_t rel0 = bars + 8 * (BAR_BEMPTY + ((job - 1) & 3));
        uint32_t rel1 = bars + 8 * (BAR_G2EMPTY + __popc(0x2d4 & ((1 << kb) - 1)));
        asm volatile("" : "+r"(dal), "+r"(dbl), "+r"(rel0), "+r"(rel1));
        wg_wait<1>();
        if (tau == 0) STAMP(64 + job);
        mbar_arrive_if(rel0, lane == 0 && kb > 0);
        mbar_arrive_if(rel1, lane == 0 && ch == 2 && ((0x2d4 >> kb) & 1));
        if (!rdy) mbar_wait(nxt, 0);
      }
      wg_wait<0>();
      mbar_arrive_if(ch == 2 ? bars + 8 * (BAR_G2EMPTY + 5) : bars + 8 * (BAR_BEMPTY + ((10 * ch + 9) & 3)), lane == 0);
      mbar_arrive_if(bars + 8 * (BAR_G2EMPTY + 6), lane == 0 && ch == 2);
      mbar_wait(bars + 8 * BAR_BFULL, 0);
      reg_fence(acc0); reg_fence(acc1);
      if (tau == 0) STAMP(26 + ch);
      uint4* dst = g_H + (size_t)(grp * 24 + ch * 8 + nsl) * 1024 + (2 * wq) * 64;
      const uint32_t hm = ~(g ^ t) & 1;
      dst += t * 8 + g;
#pragma unroll
      for (int mb = 0; mb < 2; mb++) {
        float(&d)[64] = mb ? acc1 : acc0;
#pragma unroll
        for (int q = 0; q < 4; q++) {
          uint32_t o[4];
#pragma unroll
          for (int i = 0; i < 4; i++) {
            const int k = 4 * (4 * (q & 1) + i) + 2 * (q >> 1);
            if ((i & 1) == 0) mbar_wait(bars + 8 * BAR_BFULL, 0);
            asm volatile("" : "+f"(d[k]), "+f"(d[k + 1]), "+f"(d[k + 32]), "+f"(d[k + 33]) :: "memory");
            o[i] = pack2(gelu_mul(d[k], d[k + 32]), gelu_mul(d[k + 1], d[k + 33]));
            if (i == q) o[i] = (o[i] & ~hm) | (par & hm);
          }
          asm volatile("st.global.v4.u32 [%0], {%1,%2,%3,%4};" :: "l"(dst + mb * 512 + q * 32), "r"(o[0]), "r"(o[1]), "r"(o[2]), "r"(o[3]) : "memory");
        }
      }
      if (tau == 0) STAMP(35 + ch);
      if (ch == 0) bar_arrive(12, 160);
      if (tau == 0) STAMP(12 + ch);
    }
    if (wgi == 0) {
      mbar_arrive_if(bars + 8 * BAR_EPI, lane == 0);
      spin_until(clock32() + H_LAG);
      mbar_arrive_if(bars + 8 * BAR_H2, lane == 0);
      if (tau == 0) STAMP(38);
      if (wq == 0) {
        mbar_wait(bars + 8 * (BAR_G2FULL + X1_AT), 0);
        if (elect()) {
          mbar_expect(bars + 8 * BAR_X1, 20480);
          tma3d(sb + OFF_B, &tmOut, 160 * nq, 0, 8 * grp + 4 * mb2, bars + 8 * BAR_X1);
          tma3d(sb + OFF_B + 10240, &tmOut, 160 * nq + 80, 0, 8 * grp + 4 * mb2, bars + 8 * BAR_X1);
        }
      }
    } else {
      float acc[80];
      int slot = 0;
      uint32_t dal = (uint32_t)mkdesc(sb + g2_a(0), 128, 1024, 0), dbl = (uint32_t)mkdesc(sb + g2_b(0), 1024, 256, 3);
      mbar_wait(bars + 8 * (BAR_G2EMPTY + 4), 0);
      mbar_wait(bars + 8 * BAR_G2FULL, 0);
      if (tau == 0) STAMP(15);
      wg_fence();
#pragma unroll 1
      for (int i = 0; i < 24; i++) {
        const uint64_t da = (mkdesc(sb, 128, 1024, 0) & ~0xffffffffull) | dal, db = (mkdesc(sb, 1024, 256, 3) & ~0xffffffffull) | dbl;
        wgmma_n160(acc, da, db, i != 0);
        const uint32_t nxt = bars + 8 * (i < 23 ? BAR_G2FULL + i + 1 : BAR_X1);
        const uint32_t rdy = mbar_test(nxt, 0);
#pragma unroll
        for (int kk = 1; kk < 4; kk++) wgmma_n160(acc, da + 16 * kk, db + 32 * (kk & 1) + 640 * (kk >> 1), 1);
        wg_commit();
        if (++slot == 7) slot = 0;
        dal = (uint32_t)mkdesc(sb + g2_a(slot), 128, 1024, 0); dbl = (uint32_t)mkdesc(sb + g2_b(slot), 1024, 256, 3);
        asm volatile("" : "+r"(dal), "+r"(dbl));
        wg_wait<G2_DEEP>();
        if (tau == 0) STAMP(94 + i);
        mbar_arrive_if(bars + 8 * (BAR_G2EMPTY + i + 7 - G2_DEEP), lane == 0 && i >= G2_DEEP && i < 17 + G2_DEEP);
        if (!rdy) mbar_wait(nxt, 0);
      }
      uint32_t gbv[20], xr[2][20];
#pragma unroll
      for (int i = 0; i < 20; i++) gbv[i] = lds32(sb + OFF_GB + i * 16 + t * 4);
      const uint32_t xa = sb + OFF_B + (16 * wq + (lane & 15)) * 160 + (lane >> 4) * 16;
      uint4* op = reinterpret_cast<uint4*>(out) + (8 * grp + 4 * mb2 + wq) * 80 + 20 * nq + lane;
      uint32_t oo[5];
#pragma unroll
      for (int i = 0; i < 5; i++) oo[i] = 32 * i + (((lane + 32 * i) * 205) >> 11) * (128 * 80 - 10);
#pragma unroll
      for (int i = 0; i < 20; i += 2) ldsm4(xr[0][i], xr[1][i], xr[0][i + 1], xr[1][i + 1], xa + (i / 10) * 10240 + (i % 10) * 16);
      wg_wait<0>();
      reg_fence(acc);
      if (tau == 0) STAMP(16);
#pragma unroll
      for (int nh = 0; nh < 2; nh++) {
#pragma unroll
        for (int i = 10 * nh; i < 10 * nh + 10; i += 2)
          stsm4(xa + nh * 10240 + (i % 10) * 16,
                hfma2(gbv[i], pack2(acc[4 * i], acc[4 * i + 1]), xr[0][i]), hfma2(gbv[i], pack2(acc[4 * i + 2], acc[4 * i + 3]), xr[1][i]),
                hfma2(gbv[i + 1], pack2(acc[4 * i + 4], acc[4 * i + 5]), xr[0][i + 1]), hfma2(gbv[i + 1], pack2(acc[4 * i + 6], acc[4 * i + 7]), xr[1][i + 1]));
        __syncwarp();
        uint4 v[5];
#pragma unroll
        for (int i = 0; i < 5; i++) v[i] = lds128(sb + OFF_B + nh * 10240 + 16 * wq * 160 + (lane + 32 * i) * 16);
#pragma unroll
        for (int i = 0; i < 5; i++) op[10 * nh + oo[i]] = v[i];
      }
      if (tau == 0) { STAMP(17); GSTAMP(62); }
    }
  } else {
    const int tau = tid - 256, k1n = (16 - k1) & 15;
    if (w == 9 && elect()) {
#pragma unroll
      for (int i = 0; i < 5; i++) l2_prefetch(wmod + (size_t)(b + 128 * i) * 3840, 2560);
    }
    if (w == 8) {
      mbar_init(bars + 8 * BAR_G1, 2);
      mbar_init(bars + 8 * BAR_G1H, 1);
      mbar_init(bars + 8 * BAR_C, 1);
      fence_async_smem();
      if (elect()) {
        mbar_expect(bars + 8 * BAR_C, 1280);
        bulk_g2s(sb + OFF_SC, cvec, 1280, bars + 8 * BAR_C);
        if (b < 80) {
          mbar_expect(bars + 8 * BAR_G1H, 10240); tma3d(sb + OFF_BUFB, &tmMod, 16 * b, 0, 0, bars + 8 * BAR_G1H);
          mbar_expect(bars + 8 * BAR_G1, 10240); tma3d(sb + OFF_BUFB + 10240, &tmMod, 16 * b, 0, 2, bars + 8 * BAR_G1);
        }
      }
      bar_arrive(3, 320);
    }
    if (w == 10) {
      mbar_init(bars + 8 * BAR_COL, 1);
      mbar_init(bars + 8 * BAR_TB, 1);
      mbar_init(bars + 8 * BAR_W, 1);
      fence_async_smem();
      bar_arrive(3, 320);
      if (lane < 7) {
        const CUtensorMap* tm = lane == 0 ? &tmW : lane == 1 ? &tmE : lane == 2 ? &tmH2 : lane == 3 ? &tmGU : lane == 4 ? &tmOut : lane == 5 ? &tmWd : &tmS;
        asm volatile("prefetch.tensormap [%0];" :: "l"(tm) : "memory");
      }
      spin_until(t_start + TAB_AT);
      if (elect()) {
        mbar_expect(bars + 8 * BAR_TB, 5120 + 24576 + 5632);
        bulk_g2s(sb + OFF_TC, g_tab, 5120, bars + 8 * BAR_TB);
        bulk_g2s(sb + OFF_T1, g_tab + TAB_T1 * 128, 24576, bars + 8 * BAR_TB);
        bulk_g2s(sb + OFF_T2, g_tab + (TAB_T2 + 11 * k1) * 128, 5632, bars + 8 * BAR_TB);
      }
      if (Bk == 0) {
        spin_until(t_start + COL_AT);
        if (elect()) mbar_expect(bars + 8 * BAR_COL, 8 * 2048);
#pragma unroll 1
        for (int i = 0; i < 8; i++)
          if (elect()) tma2d(sb + OFF_COL + i * 2048, (i & 1) ? &tmCi : &tmCr, (((i & 2) ? k1n : k1) * 321 + 80 * (i & 4)) & ~7, 0, bars + 8 * BAR_COL);
      }
    }
    if (tau == 0) STAMP(31);
    const uint32_t ep128 = ld_relaxed(&g_cnt[C_T2]) + 128, ep8 = ld_relaxed(gcnt + C_T3) + GSZ;
    const uint32_t ep = ep128 >> 7;
    const uint32_t* msrc = g_mod + Bk * 3840 + tau * 4;
    uint32_t mdst = sb + OFF_MODS + tau * 8, tag = ep & 0xffffu;
    asm volatile("" : "+l"(msrc), "+r"(mdst), "+r"(tag));
    if (w == 8) {
      if (elect()) sts32(sb + OFF_EP, ep);
      if (b < 80) {
        mbar_wait(bars + 8 * BAR_G1H, 0);
        if (elect()) { mbar_arrive(bars + 8 * BAR_G1); red_relaxed(&g_cnt[C_MOD]); }
      }
      __syncwarp();
      poll_cnt(&g_cnt[C_MOD], 80u * ep);
      spin_until(clock32() + MOD_LAG);
    }
    int wc0 = k1 * 321 + 40 * Bk - (k1 & 7);
    asm volatile("" : "+r"(wc0));
    if (w == 10 && elect()) mbar_expect(bars + 8 * BAR_W, 2 * 14336);
    bar_sync(4, 384);
    poll_mods<3, 128>(msrc, mdst, tau < 64, tag);
    if (elect()) mbar_arrive(bars + 8 * BAR_MODA);
    if (w == 10 && elect()) {
      tma4d(sb + OFF_WR, &tmW, wc0, bars + 8 * BAR_W);
      if (split & 1) tma4d(sb + OFF_WI, &tmW2, wc0, bars + 8 * BAR_W);
    }
    if (tau == 0) STAMP(11);
    fence_async_smem();
    if (w == 9) {
#pragma unroll 1
      for (int e = 0; e < 2; e++) {
        if (elect()) mbar_expect(bars + 8 * (BAR_IN2 + e), 20480);
        bar_sync(5, 320);
        uint32_t tg = poll_hint(&g_cnt[C_T1 + 4 * e], ep128) + (e ? T2_LAG : T1_LAG);
        if (lane == 0) STAMP(51 + e);
        mbar_wait(bars + 8 * BAR_SENT, e);
        tg += min(lds32(sb + OFF_EP + 20) - lds32(sb + OFF_EP + 16), (uint32_t)(e ? T2_CAP : T1_CAP));
        for (int it = 0; (int)((uint32_t)gtime() - tg) < 0 && it < 10000; it++) {}
        if (elect()) {
          tma2d(sb + OFF_BUFB, &tmE, 40 * b, 128 * e, bars + 8 * (BAR_IN2 + e));
          if (e == 1) mbar_arrive(bars + 8 * BAR_T2P);
          else {
#pragma unroll
            for (int i = 0; i < 5; i++) l2_prefetch(wmod + (size_t)(b + 128 * i) * 3840 + 1280, 5120);
          }
          STAMP(20 + 2 * e);
        }
        __syncwarp();
      }
    }
    if (w == 8) {
      mbar_wait(bars + 8 * BAR_SENT, 0);
#pragma unroll
      for (int i = 0; i < BAR_EARLY; i++)
        mbar_init(bars + 8 * i, i < 2 ? 1 : i == 2 ? 7 : i < 10 ? 3 : (i >= BAR_BEMPTY && i <= BAR_H2) ? 4 : ((i >= BAR_G2FULL + 8 && i <= BAR_X1) || i == BAR_T3B) ? 2 : 1);
      fence_async_smem();
    }
    if (w < 10) {
      mbar_wait(bars + 8 * GEMV2_BAR, 0);
      if (w == 8 && elect()) {
        mbar_expect(bars + 8 * BAR_G2, 20480);
        mbar_expect(bars + 8 * (BAR_G2 + 1), 20480);
#pragma unroll 1
        for (int i = 0; i < (b < 32 ? 4 : 2); i++)
          tma3d(sb + (i & 2 ? OFF_X1 : OFF_B) + (i & 1) * 10240, &tmMod, 16 * (80 + b) + 1024 * (i & 2), 0, 2 * (i & 1), bars + 8 * (BAR_G2 + (i >> 1)));
      }
      __syncwarp();
      mbar_wait(bars + 8 * MODB_BAR, 0);
      spin_until(clock32() + MODB_LAG);
      poll_mods<8, 64>(msrc + 1280, mdst + 2560, tau < 32, tag);
      bar_arrive(7, 352);
      if (tau == 0) STAMP(42);
      bar_sync(11, 320);
      fence_async_smem();
    }

    if (w == 11) {
      mbar_wait(bars + 8 * BAR_TB, 0);
      const uint4 eo = lds128(sb + OFF_T1 + 5 * 512 + lane * 16);
      uint32_t lph = 0;
      bar_sync(6, 288);
      if (elect()) hint(&g_cnt[C_T1], sb + OFF_EP + 16);
#pragma unroll 1
      for (int e = 0; e < 2; e++) {
        uint32_t ca[5];
        const uint32_t eof[5] = {eo.x, eo.y, eo.z, eo.w & 0xffffu, eo.w >> 16};
#pragma unroll
        for (int v = 0; v < 5; v++)
          ca[v] = sb + OFF_BUFB + (e ? (eof[v] ^ ((b >> 1) & 28)) : ((8 * t + g) * 40 + 8 * v + ((((5 * Bk + v) >> 1) ^ (2 * t + (g >> 2))) & 7)) * 4);
        const uint32_t cs = e ? 640 : 5120;
        asm volatile("" : "+r"(ca[0]), "+r"(ca[1]), "+r"(ca[2]), "+r"(ca[3]), "+r"(ca[4]));
        bar_sync(5, 320);
        fence_async_smem();
        if (elect()) {
          if (e == 0) bulk_s2g(g_E + b * 5120, sb + OFF_BUFA, 20480);
          else tma2d_store(&tmS, 24, 128 * b, sb + OFF_P2A + 12288);
          bulk_commit();
        }
        bulk_wait0();
        if (elect()) { sts32(sb + OFF_EP + 20, (uint32_t)gtime()); mbar_arrive(bars + 8 * BAR_SENT); STAMP(47 + e); }
        __syncwarp();
        mbar_wait(bars + 8 * (BAR_IN2 + e), 0);
        if (e == 0 && elect()) hint(&g_cnt[C_T2], sb + OFF_EP + 16);
        int it = 0;
        while (true) {
          uint32_t acc = 0;
#pragma unroll
          for (int v = 0; v < 5; v++)
            acc |= ((lds32(ca[v]) ^ ep) | (lds32(ca[v] + cs) ^ ep)) | ((lds32(ca[v] + 2 * cs) ^ ep) | (lds32(ca[v] + 3 * cs) ^ ep));
          if (!__any_sync(0xffffffffu, (acc & 1) != 0) || it >= SPIN_LIMIT) break;
          it++;
          fence_async_smem();
          __syncwarp();
          if (elect()) { mbar_expect(bars + 8 * BAR_RETRY, 20480); tma2d(sb + OFF_BUFB, &tmE, 40 * b, 128 * e, bars + 8 * BAR_RETRY); }
          __syncwarp();
          mbar_wait(bars + 8 * BAR_RETRY, lph); lph ^= 1;
        }
        sts32(sb + OFF_EP + 4 + 4 * e, it ? 2 : 1);
        if (lane == 0) STAMP(19 + 2 * e);
      }
      bar_sync(7, 352);
      if (elect()) hint(gcnt + C_T3, sb + OFF_EP + 16);
      bar_sync(2, 288);
      fence_async_smem();
      if (elect()) {
        tma2d_store(&tmH2, 256 * nsl, 10 * grp, sb + OFF_H2S); bulk_commit();
        sts32(sb + OFF_EP + 20, (uint32_t)gtime());
        mbar_arrive(bars + 8 * BAR_SENT);
        STAMP(23);
      }
      mbar_wait(bars + 8 * BAR_ALD, 0);
      if (elect()) { tma2d_store(&tmH2, 256 * nsl, 10 * grp + 5, sb + OFF_H2S + 10240); bulk_commit(); }
      bulk_wait0();
      if (elect()) mbar_arrive(bars + 8 * BAR_T3B);
      mbar_wait(bars + 8 * BAR_T3B, 0);
      bar_sync(8, 288);
      fence_async_smem();
#pragma unroll 1
      for (int j = 0; j < 16; j++) {
        if (elect()) bulk_s2g(out + (size_t)(128 * j + b) * 640, sb + OFF_X1 + j * 1280, 1280);
        if (j == X1_SPLIT || j == 15) {
          bulk_commit();
          bulk_wait_read0();
          const int kb = 8 + (j == 15);
          if (elect()) { bulk_g2s(sb + kb * 16384, g_H2 + (size_t)(grp * 10 + kb) * 1024, 16384, bars + 8 * (BAR_ALAND + kb)); STAMP(50); }
        } else {
          spin_until(clock32() + X1_PACE);
        }
      }
      bulk_wait0();
      mbar_wait(bars + 8 * (BAR_BFULL + 10), 0);
      if (elect()) red_release(gcnt + C_X1);
      __syncwarp();
    } else if (w == 10) {
      if (Bk == 0) {
        mbar_wait(bars + 8 * BAR_COL, 0);
#pragma unroll 1
        for (int k2 = lane; k2 < 128; k2 += 32) {
          const uint32_t p = sb + OFF_COL + k2 * 16 + (k1 & 7) * 2;
          const uint32_t n = sb + OFF_COL + 4096 + ((127 + (k1 == 0) - k2) & 127) * 16 + (k1n & 7) * 2;
          const float s0r = bf_lo(lds16(p)) + bf_lo(lds16(n)), s0i = bf_lo(lds16(p + 2048)) - bf_lo(lds16(n + 2048));
          const float s1r = bf_lo(lds16(p + 8192)) + bf_lo(lds16(n + 8192)), s1i = bf_lo(lds16(p + 10240)) - bf_lo(lds16(n + 10240));
          float ar = k1 < 8 ? s0r : -s1i, ai = k1 < 8 ? s0i : s1r;
          if ((k1 & 7) == 0) { ar = 0.25f * (s0r + s1r); ai = 0.25f * (s0i + s1i); }
          sts128(sb + OFF_AB + k2 * 16, make_uint4(__float_as_uint(ar), __float_as_uint(ai),
                                                  __float_as_uint(0.25f * (s0r - s1r)), __float_as_uint(0.25f * (s0i - s1i))));
        }
        fence_async_smem();
      }
      __syncwarp();
      if (elect()) {
        mbar_arrive(bars + 8 * BAR_AB);
        mbar_expect(bars + 8 * BAR_TB3, 20480);
        bulk_g2s(sb + OFF_T3, g_tab + TAB_T3 * 128, 20480, bars + 8 * BAR_TB3);
      }
      __syncwarp();
      mbar_wait(bars + 8 * BAR_W, 0);
      if (lane==0) STAMP(39);
      if (elect()) l2_prefetch(wd + (size_t)b * 7680, 15360);
      {
        bar_sync(9, 288);
        uint32_t verd = 0;
        for (int it = 0; verd == 0 && it < SPIN_LIMIT; it++) verd = lds32v(sb + OFF_EP + 4);
        if (verd == 2) bar_sync(9, 288);
        fence_async_smem();
        if (elect()) { tma2d_store(&tmS, 0, 128 * b, sb + OFF_P2A); bulk_commit(); }
      }
      mbar_wait(bars + 8 * GU_BAR, 0);
      if (grp < 10 && elect()) {
        tma3d_prefetch(&tmGU, 192 * nsl, 64 * grp);
        if (split & 2) tma3d_prefetch(&tmGU2, 192 * nsl, 64 * grp);
      }
      mbar_wait(bars + 8 * WDG_BAR, 0);
      if (elect()) {
        mbar_expect(bars + 8 * BAR_WDL, 15360);
#pragma unroll
        for (int i = 0; i < 3; i++) {
          const int hb = 3 * k1 + i;
          tma5d(sb + OFF_WDS + i * 5120, &tmWd, 24 * ((hb >> 1) & 7) + 8 * (hb >> 4) + 4 * (hb & 1), 5 * Bk, bars + 8 * BAR_WDL);
        }
      }
      mbar_wait(bars + 8 * BAR_IN3, 0);
      mbar_wait(bars + 8 * BAR_WDL, 0);
      if (elect()) {
#pragma unroll
        for (int i = 0; i < 3; i++) bulk_s2g(g_WdP + ((Bk >> 1) * 48 + 3 * k1 + i) * 640 + (Bk & 1) * 320, sb + OFF_WDS + i * 5120, 5120);
        bulk_commit();
      }
      if (lane == 0) STAMP(43);
      uint32_t tg = poll_hint(gcnt + C_T3, ep8) + T3_LAG;
      mbar_wait(bars + 8 * BAR_SENT, 0);
      tg += min(lds32(sb + OFF_EP + 20) - lds32(sb + OFF_EP + 16), (uint32_t)T3_CAP);
      for (int it = 0; (int)((uint32_t)gtime() - tg) < 0 && it < 10000; it++) {}
      if (elect()) {
        STAMP(24);
#pragma unroll
        for (int kb = 0; kb < 5; kb++) {
          bulk_g2s(sb + kb * 16384, g_H2 + (size_t)(grp * 10 + kb) * 1024, 16384, bars + 8 * (BAR_ALAND + kb));
          if (kb == 1) mbar_arrive(bars + 8 * BAR_ALD);
        }
      }
      bulk_wait0();
      if (elect()) mbar_arrive(bars + 8 * BAR_T3B);
      __syncwarp();
    }

    if (w < 10) {
      if (lane < (w == 8 ? 30 : 10)) mbar_expect(bars + 8 * ((w == 8 ? BAR_BFULL : BAR_ALAND) + lane), 16384);
      mbar_wait(bars + 8 * BAR_IN3, 0);
#pragma unroll 1
      for (int job = w - 8; job < 30; job += 2) {
        const int ch = job / 10, kb = job - 10 * ch, slot = job & 3;
        if (job == 4 || job == 5) mbar_wait(bars + 8 * BAR_T3B, 0);
        if (job >= 4) mbar_wait(bars + 8 * (BAR_BEMPTY + slot), ((job >> 2) - 1) & 1);
        if (elect()) {
          tma3d(sb + OFF_B + slot * 16384, &tmGU, 192 * nsl + 64 * ch, 64 * kb, 0, bars + 8 * (BAR_BFULL + job));
          if (split & 2) tma3d(sb + OFF_B + slot * 16384 + 8192, &tmGU2, 192 * nsl + 64 * ch, 64 * kb, 0, bars + 8 * (BAR_BFULL + job));
          if (job >= 4 && job < 7) bulk_g2s(sb + (kb + 1) * 16384, g_H2 + (size_t)(grp * 10 + kb + 1) * 1024, 16384, bars + 8 * (BAR_ALAND + job + 1));
          const int pj = job + GU_D;
          if (job >= 4 && pj >= 10 && pj < 30 && (pj & 15) == grp) {
            tma3d_prefetch(&tmGU, 192 * nsl + 64 * (pj / 10), 64 * (pj % 10));
            if (split & 2) tma3d_prefetch(&tmGU2, 192 * nsl + 64 * (pj / 10), 64 * (pj % 10));
          }
          STAMP(128 + job);
        }
        __syncwarp();
      }
      const uint32_t to = (g & 3) * 516 + t * 32 + (g >> 2) * 144;
      uint32_t rph = 0;
#pragma unroll 1
      for (int i = w; i < 24; i += 2) {
        uint32_t dst = sb + g2_a(i % 7);
        asm volatile("" : "+r"(dst));
        mbar_wait(bars + 8 * (BAR_HLAND + i - 8), 0);
        validate<8, 256, 2048>(dst, dst + to, g_H + (size_t)(grp * 24 + i) * 1024 + mb2 * 512, ep, bars + 8 * (BAR_WRETRY + w - 8), rph, 3);
        if (i == GATE_T) { mbar_wait(bars + 8 * BAR_EPI, 0); spin_until(clock32() + GATE_LAG); }
        mbar_arrive_if(bars + 8 * (BAR_G2FULL + i), lane == 0);
      }
    } else {
      if (w == 10) {
        if (lane < 24) mbar_expect(bars + 8 * (BAR_G2FULL + lane), lane < 8 ? 28672 : 20480);
        if (lane < 16) mbar_expect(bars + 8 * (BAR_HLAND + lane), 8192);
        bar_sync(12, 160);
        if (elect()) { red_release(gcnt + C_H0); red_relaxed(&g_cnt[C_WD]); }
        __syncwarp();
      }
      if (w == 11) {
        uint4 v, u;
        int it = 0;
        do {
          const uint32_t* p = &g_mod[Bk * 3840 + 3200 + 160 * nq + 8 * min(lane, 19)];
          v = ld_relaxed4(p); u = ld_relaxed4(p + 4);
        } while (__any_sync(0xffffffffu, (((v.x ^ tag) | (v.y ^ tag) | (v.z ^ tag) | (v.w ^ tag) | (u.x ^ tag) | (u.y ^ tag) | (u.z ^ tag) | (u.w ^ tag)) & 0xffffu) != 0) &&
                 ++it < SPIN_LIMIT);
        if (lane < 20)
          sts128(sb + OFF_GB + lane * 16, make_uint4(hmul2(__byte_perm(v.x, v.y, 0x7632), 0x3f003f00u), hmul2(__byte_perm(v.z, v.w, 0x7632), 0x3f003f00u),
                                                     hmul2(__byte_perm(u.x, u.y, 0x7632), 0x3f003f00u), hmul2(__byte_perm(u.z, u.w, 0x7632), 0x3f003f00u)));
        mbar_wait(bars + 8 * (BAR_BFULL + 16), 0);
        poll_cnt(gcnt + C_X1, ep8);
        if (elect()) mbar_arrive(bars + 8 * BAR_X1);
      }
      mbar_wait(bars + 8 * (BAR_BFULL + 23), 0);
      poll_cnt(&g_cnt[C_WD], ep128);
      poll_cnt(gcnt + C_H0, ep8);
      mbar_wait(bars + 8 * (BAR_BFULL + G2_AT + G2_STEP * (w - 10)), 0);
      const uint4* srcb = g_WdP + (size_t)nq * 24 * 1280;
      const uint4* srca = g_H + (size_t)grp * 24 * 1024 + mb2 * 512;
#pragma unroll 1
      for (int i = w - 10; i < 24; i += 2) {
        const uint32_t da = sb + g2_a(i % 7), db = sb + g2_b(i % 7), full = bars + 8 * (BAR_G2FULL + i);
        const uint32_t land = i < 8 ? full : bars + 8 * (BAR_HLAND + i - 8);
        mbar_wait(bars + 8 * (BAR_G2EMPTY + i), 0);
        if ((i >> 1) == 8) {
          if (elect()) bulk_g2s(db, srcb + i * 1280, 20480, full);
          mbar_wait(bars + 8 * BAR_H2, 0);
          if (elect()) bulk_g2s(da, srca + i * 1024, 8192, land);
        } else if (elect()) {
          bulk_g2s(da, srca + i * 1024, 8192, land);
          bulk_g2s(db, srcb + i * 1280, 20480, full);
        }
      }
    }
  }
}

typedef CUresult (*EncodeFn)(CUtensorMap*, CUtensorMapDataType, cuuint32_t, void*, const cuuint64_t*, const cuuint64_t*,
                             const cuuint32_t*, const cuuint32_t*, CUtensorMapInterleave, CUtensorMapSwizzle,
                             CUtensorMapL2promotion, CUtensorMapFloatOOBfill);

void make_map(EncodeFn enc, CUtensorMap* tm, CUtensorMapDataType dt, int rank, const void* base, const cuuint64_t* dims,
              const cuuint64_t* strides, const cuuint32_t* box, CUtensorMapSwizzle sw,
              CUtensorMapL2promotion promo = CU_TENSOR_MAP_L2_PROMOTION_NONE) {
  cuuint32_t es[5] = {1, 1, 1, 1, 1};
  enc(tm, dt, rank, const_cast<void*>(base), dims, strides, box, es, CU_TENSOR_MAP_INTERLEAVE_NONE, sw,
      promo, CU_TENSOR_MAP_FLOAT_OOB_FILL_NONE);
}

}

extern "C" void kernel_launch(void* const* d_in, const int* in_sizes, int n_in, void* d_out, int out_size) {
  (void)in_sizes; (void)n_in; (void)out_size;
  const __nv_bfloat16* x = (const __nv_bfloat16*)d_in[0];
  const __nv_bfloat16* w_r = (const __nv_bfloat16*)d_in[1];
  const __nv_bfloat16* w_i = (const __nv_bfloat16*)d_in[2];
  const __nv_bfloat16* wg = (const __nv_bfloat16*)d_in[4];
  const __nv_bfloat16* wu = (const __nv_bfloat16*)d_in[5];
  const __nv_bfloat16* wd = (const __nv_bfloat16*)d_in[6];
  const __nv_bfloat16* cvec = (const __nv_bfloat16*)d_in[7];
  const __nv_bfloat16* wmod = (const __nv_bfloat16*)d_in[8];

  EncodeFn enc = nullptr;
  cudaDriverEntryPointQueryResult qr;
  cudaGetDriverEntryPoint("cuTensorMapEncodeTiled", (void**)&enc, cudaEnableDefault, &qr);
  void* eb = nullptr;
  cudaGetSymbolAddress(&eb, g_E);
  void* h2b = nullptr;
  cudaGetSymbolAddress(&h2b, g_H2);
  CUtensorMap tmMod, tmW, tmW2, tmE, tmH2, tmGU, tmGU2, tmOut, tmCr, tmCi, tmWd, tmS;
  {
    cuuint64_t d[3] = {3840, 160, 4}, s[2] = {7680, 7680 * 160}; cuuint32_t bx[3] = {16, 160, 2};
    make_map(enc, &tmMod, CU_TENSOR_MAP_DATA_TYPE_BFLOAT16, 3, wmod, d, s, bx, CU_TENSOR_MAP_SWIZZLE_NONE);
  }
  int split = 0;
  {
    const cuuint64_t dist = (cuuint64_t)w_i - (cuuint64_t)w_r;
    const bool one = w_i > w_r && dist < (1ull << 40) && dist % 16 == 0;
    if (!one) split |= 1;
    cuuint64_t d[4] = {5136, 8, 16, one ? 2u : 1u}, s[3] = {10272 * 16, 10272, one ? dist : 10272 * 128};
    cuuint32_t bx[4] = {56, 8, 16, one ? 2u : 1u};
    make_map(enc, &tmW, CU_TENSOR_MAP_DATA_TYPE_BFLOAT16, 4, w_r, d, s, bx, CU_TENSOR_MAP_SWIZZLE_NONE, W_PROMO);
    make_map(enc, &tmW2, CU_TENSOR_MAP_DATA_TYPE_BFLOAT16, 4, one ? w_r : w_i, d, s, bx, CU_TENSOR_MAP_SWIZZLE_NONE, W_PROMO);
  }
  {
    const cuuint64_t dist = (cuuint64_t)wu - (cuuint64_t)wg;
    const bool one = wu > wg && dist < (1ull << 40) && dist % 16 == 0;
    if (!one) split |= 2;
    cuuint64_t d[3] = {1536, 640, one ? 2u : 1u}, s[2] = {3072, one ? dist : 3072 * 640}; cuuint32_t bx[3] = {64, 64, one ? 2u : 1u};
    make_map(enc, &tmGU, CU_TENSOR_MAP_DATA_TYPE_BFLOAT16, 3, wg, d, s, bx, CU_TENSOR_MAP_SWIZZLE_128B);
    make_map(enc, &tmGU2, CU_TENSOR_MAP_DATA_TYPE_BFLOAT16, 3, one ? wg : wu, d, s, bx, CU_TENSOR_MAP_SWIZZLE_128B);
  }
  {
    cuuint64_t d[2] = {5136, 128}, s[1] = {10272}; cuuint32_t bx[2] = {8, 128};
    make_map(enc, &tmCr, CU_TENSOR_MAP_DATA_TYPE_BFLOAT16, 2, w_r, d, s, bx, CU_TENSOR_MAP_SWIZZLE_NONE);
    make_map(enc, &tmCi, CU_TENSOR_MAP_DATA_TYPE_BFLOAT16, 2, w_i, d, s, bx, CU_TENSOR_MAP_SWIZZLE_NONE);
  }
  {
    cuuint64_t d[5] = {16, 2, 192, 4, 40}, s[4] = {1280, 8 * 1280, 2 * 1280, 32}; cuuint32_t bx[5] = {16, 2, 4, 4, 5};
    make_map(enc, &tmWd, CU_TENSOR_MAP_DATA_TYPE_BFLOAT16, 5, wd, d, s, bx, CU_TENSOR_MAP_SWIZZLE_32B);
  }
  {
    cuuint64_t d[2] = {5120, 256}, s[1] = {20480}; cuuint32_t bx[2] = {40, 128};
    make_map(enc, &tmE, CU_TENSOR_MAP_DATA_TYPE_UINT32, 2, eb, d, s, bx, CU_TENSOR_MAP_SWIZZLE_NONE);
  }
  {
    cuuint64_t d[2] = {40, 128 * 128}, s[1] = {160}; cuuint32_t bx[2] = {24, 128};
    make_map(enc, &tmS, CU_TENSOR_MAP_DATA_TYPE_UINT32, 2, (uint32_t*)eb + 128 * 5120, d, s, bx, CU_TENSOR_MAP_SWIZZLE_NONE);
  }
  {
    cuuint64_t d[2] = {2048, 160}, s[1] = {16384}; cuuint32_t bx[2] = {256, 5};
    make_map(enc, &tmH2, CU_TENSOR_MAP_DATA_TYPE_UINT64, 2, h2b, d, s, bx, CU_TENSOR_MAP_SWIZZLE_NONE);
  }
  {
    cuuint64_t d[3] = {640, 16, 128}, s[2] = {128 * 1280, 1280}; cuuint32_t bx[3] = {80, 16, 4};
    make_map(enc, &tmOut, CU_TENSOR_MAP_DATA_TYPE_BFLOAT16, 3, d_out, d, s, bx, CU_TENSOR_MAP_SWIZZLE_NONE);
  }
  cudaFuncSetAttribute(fused_kernel, cudaFuncAttributeMaxDynamicSharedMemorySize, SMEM_BYTES);
  fused_kernel<<<NCTA, NTHR, SMEM_BYTES>>>(tmMod, tmW, tmE, tmH2, tmGU, tmOut, tmW2, tmGU2, tmCr, tmCi, tmWd, tmS, split, x, wd, cvec, wmod, (__nv_bfloat16*)d_out);
}
```
